```python
import torch

def _softmax(x, axis=-1):
    return torch.softmax(x, dim=axis)

def _gelu(x):
    return torch.nn.functional.gelu(x, approximate='tanh')

def _silu(x):
    return torch.nn.functional.silu(x)

def _sigmoid(x):
    return torch.sigmoid(x)

def _layernorm(x, axis=-1, eps=1e-05):
    m = x.mean(dim=axis, keepdim=True)
    v = x.var(dim=axis, keepdim=True, unbiased=False)
    return (x - m) / torch.sqrt(v + eps)

def _scatter_add(tgt, idx, src, axis=0):
    return tgt.clone().index_add_(axis, idx, src)

def _segment_sum(src, seg, n):
    out = torch.zeros((n,) + src.shape[1:], dtype=src.dtype)
    return out.index_add_(0, seg, src)

def _pad(x, pw):
    flat = tuple((v for pair in reversed(pw) for v in pair))
    return torch.nn.functional.pad(x, flat)
kernel_name = 'adaLN_cond__gqa_block_cached__geglu_ffn__decode'

def setup_inputs():

    _w = lambda a: (lambda t: t.to(torch.bfloat16) if t.is_floating_point() else t)(torch.as_tensor(a))

    def _A_setup():
        B, Sq, D = (4, 1, 640)
        Hq, Hkv, Sk, Dh = (32, 32, 4096, 192)
        assert Hq % Hkv == 0, (Hq, Hkv)
        return {'x': _w((lambda *s: torch.randn(*s, dtype=torch.bfloat16) * 0.05)(B, Sq, D)), 'k_cache': _w((lambda *s: torch.randn(*s, dtype=torch.bfloat16) * 3.2)(B, Hkv, Sk, Dh)), 'v_cache': _w((lambda *s: torch.randn(*s, dtype=torch.bfloat16) * 0.4)(B, Hkv, Sk, Dh)), 'wq': _w((lambda *s: torch.randn(*s, dtype=torch.bfloat16) * 3.2)(D, Hq * Dh) * D ** (-0.5)), 'wo': _w((lambda *s: torch.randn(*s, dtype=torch.bfloat16) * 0.4)(Hq * Dh, D) * (Hq * Dh) ** (-0.5))}
    _A_in = _A_setup()

    def _B_setup():
        B, S, D, F = (4, 1, 640, 1536)
        return {'x': _w((lambda *s: torch.randn(*s, dtype=torch.bfloat16) * 0.05)(B, S, D)), 'w_gate': _w((lambda *s: torch.randn(*s, dtype=torch.bfloat16) * 0.05)(D, F)), 'w_up': _w((lambda *s: torch.randn(*s, dtype=torch.bfloat16) * 0.05)(D, F)), 'w_down': _w((lambda *s: torch.randn(*s, dtype=torch.bfloat16) * 0.05)(F, D))}
    _B_in = _B_setup()
    return {'A_x': _A_in['x'], 'A_k_cache': _A_in['k_cache'], 'A_v_cache': _A_in['v_cache'], 'A_wq': _A_in['wq'], 'A_wo': _A_in['wo'], 'B_x': _B_in['x'], 'B_w_gate': _B_in['w_gate'], 'B_w_up': _B_in['w_up'], 'B_w_down': _B_in['w_down'], 'c': _w((lambda *s: torch.randn(*s, dtype=torch.bfloat16) * 0.1)(4, 640) * 8.0), 'w_mod': _w((lambda *s: torch.randn(*s, dtype=torch.bfloat16) * 0.1)(640, 6 * 640) * 640 ** (-0.5) * 8.0)}

def reference(A_x, A_k_cache, A_v_cache, A_wq, A_wo, B_x, B_w_gate, B_w_up, B_w_down, c, w_mod):

    def _A_ref(x, k_cache, v_cache, wq, wo):
        B, Sq, D = x.shape
        Hq, Dh = (32, 192)
        Hkv = k_cache.shape[1]
        rep = Hq // Hkv
        q = (lambda x, *d: x.permute(*d))((x @ wq).reshape(B, Sq, Hq, Dh), 0, 2, 1, 3)
        k = (lambda x, n, axis: torch.repeat_interleave(x, n, dim=axis))(k_cache, rep, axis=1)
        v = (lambda x, n, axis: torch.repeat_interleave(x, n, dim=axis))(v_cache, rep, axis=1)
        scores = torch.einsum('bhqd,bhkd->bhqk', q, k) * Dh ** (-0.5)
        p = _softmax(scores, axis=-1)
        o = torch.einsum('bhqk,bhkd->bhqd', p, v)
        return (lambda x, *d: x.permute(*d))(o, 0, 2, 1, 3).reshape(B, Sq, Hq * Dh) @ wo

    def _B_ref(x, w_gate, w_up, w_down):
        return _gelu(x @ w_gate) * (x @ w_up) @ w_down
    x = A_x
    mod = (_silu(c) @ w_mod).reshape(c.shape[0], 6, 1, -1)
    sa, ca, ga, sb, cb, gb = (mod[:, 0].clone(), mod[:, 1].clone(), mod[:, 2].clone(), mod[:, 3].clone(), mod[:, 4].clone(), mod[:, 5].clone())
    h = _layernorm(x, axis=-1) * (1 + ca) + sa
    x = x + ga * _A_ref(h, A_k_cache, A_v_cache, A_wq, A_wo)
    h = _layernorm(x, axis=-1) * (1 + cb) + sb
    x = x + gb * _B_ref(h, B_w_gate, B_w_up, B_w_down)
    return x
```

```cpp
#include <cuda_runtime.h>
#include <cuda_bf16.h>
#include <stdint.h>

namespace {

constexpr int NB = 4;
constexpr int DM = 640;
constexpr int NH = 32;
constexpr int SK = 4096;
constexpr int DH = 192;
constexpr int FF = 1536;
constexpr int MODN = 6 * DM;

constexpr int NCTA = NB * NH;
constexpr int NCONS = 256;
constexpr int NTHREADS = NCONS + 32;
constexpr int TILE_KEYS = 32;
constexpr int TILE_BYTES = TILE_KEYS * DH * 2;
constexpr int NST = 16;
constexpr int KT = SK / TILE_KEYS;
constexpr int WO_ROWS = 8;
constexpr int WO_TILE_BYTES = WO_ROWS * DM * 2;
constexpr int WOT = DH / WO_ROWS;
constexpr int NTILES = 2 * KT + WOT;

constexpr int SM_RING = 0;
constexpr int SM_P = SM_RING + NST * TILE_BYTES;
constexpr int SM_RED = SM_P;
constexpr int SM_A = SM_P + 8 * DM * 4;
constexpr int SM_X1 = SM_RING;
constexpr int SM_Q = SM_A + NB * DM * 4;
constexpr int SM_SMALL = SM_Q + DH * 4;
constexpr int SM_BAR = SM_SMALL + 256 * 4;
constexpr int SM_TOTAL = SM_BAR + 2 * NST * 8;

static_assert(SM_TOTAL <= 232448, "smem");

__device__ float g_mod[NB * MODN];
__device__ float g_attn[NB * DM];
__device__ float g_ffn[NB * DM];
__device__ unsigned int g_bar[4];

__device__ __forceinline__ float bf16r(float x) {
    return __bfloat162float(__float2bfloat16_rn(x));
}
__device__ __forceinline__ float bf_lo(uint32_t u) { return __uint_as_float(u << 16); }
__device__ __forceinline__ float bf_hi(uint32_t u) { return __uint_as_float(u & 0xffff0000u); }

__device__ __forceinline__ uint32_t smem_u32(const void* p) {
    return (uint32_t)__cvta_generic_to_shared(p);
}
__device__ __forceinline__ void mbar_init(uint32_t bar, uint32_t count) {
    asm volatile("mbarrier.init.shared::cta.b64 [%0], %1;" ::"r"(bar), "r"(count) : "memory");
}
__device__ __forceinline__ void mbar_expect_tx(uint32_t bar, uint32_t bytes) {
    asm volatile("mbarrier.arrive.expect_tx.shared::cta.b64 _, [%0], %1;" ::"r"(bar), "r"(bytes) : "memory");
}
__device__ __forceinline__ void mbar_arrive(uint32_t bar) {
    asm volatile("mbarrier.arrive.shared::cta.b64 _, [%0];" ::"r"(bar) : "memory");
}
constexpr long long WAIT_LIMIT_CYCLES = 200000000LL;
__device__ __forceinline__ uint32_t mbar_try(uint32_t bar, uint32_t parity) {
    uint32_t done;
    asm volatile(
        "{\n\t.reg .pred p;\n\t"
        "mbarrier.try_wait.parity.shared::cta.b64 p, [%1], %2;\n\t"
        "selp.u32 %0, 1, 0, p;\n\t}"
        : "=r"(done) : "r"(bar), "r"(parity) : "memory");
    return done;
}
__device__ __forceinline__ void mbar_wait(uint32_t bar, uint32_t parity) {
    if (mbar_try(bar, parity)) return;
    const long long t0 = clock64();
    while (!mbar_try(bar, parity)) {
        if (clock64() - t0 > WAIT_LIMIT_CYCLES) __trap();
    }
}
__device__ __forceinline__ void bulk_g2s(uint32_t dst, const void* src, uint32_t bytes, uint32_t bar) {
    asm volatile(
        "cp.async.bulk.shared::cluster.global.mbarrier::complete_tx::bytes [%0], [%1], %2, [%3];"
        ::"r"(dst), "l"(src), "r"(bytes), "r"(bar) : "memory");
}
__device__ __forceinline__ void cons_sync() { asm volatile("bar.sync 1, 256;" ::: "memory"); }

__device__ __forceinline__ void red_add_v4(float* p, float a, float b, float c, float d) {
    asm volatile("red.global.add.v4.f32 [%0], {%1, %2, %3, %4};" ::"l"(p), "f"(a), "f"(b), "f"(c), "f"(d) : "memory");
}
__device__ __forceinline__ unsigned int ld_acquire(const unsigned int* p) {
    unsigned int v;
    asm volatile("ld.acquire.gpu.global.u32 %0, [%1];" : "=r"(v) : "l"(p) : "memory");
    return v;
}

__device__ __forceinline__ void grid_barrier(unsigned int* ctr, int tid) {
    cons_sync();
    if (tid == 0) {
        __threadfence();
        unsigned int old = atomicAdd(ctr, 1u);
        unsigned int target = (old / NCTA + 1u) * NCTA;
        const long long t0 = clock64();
        while ((int)(ld_acquire(ctr) - target) < 0) {
            if (clock64() - t0 > WAIT_LIMIT_CYCLES) __trap();
        }
        __threadfence();
    }
    cons_sync();
}

__device__ __forceinline__ float warp_sum(float v) {
#pragma unroll
    for (int o = 16; o > 0; o >>= 1) v += __shfl_xor_sync(0xffffffffu, v, o);
    return v;
}
__device__ __forceinline__ float warp_max(float v) {
#pragma unroll
    for (int o = 16; o > 0; o >>= 1) v = fmaxf(v, __shfl_xor_sync(0xffffffffu, v, o));
    return v;
}

__device__ __forceinline__ void fma8(float (&acc)[8], const uint4& w, float s) {
    acc[0] = fmaf(s, bf_lo(w.x), acc[0]);
    acc[1] = fmaf(s, bf_hi(w.x), acc[1]);
    acc[2] = fmaf(s, bf_lo(w.y), acc[2]);
    acc[3] = fmaf(s, bf_hi(w.y), acc[3]);
    acc[4] = fmaf(s, bf_lo(w.z), acc[4]);
    acc[5] = fmaf(s, bf_hi(w.z), acc[5]);
    acc[6] = fmaf(s, bf_lo(w.w), acc[6]);
    acc[7] = fmaf(s, bf_hi(w.w), acc[7]);
}
__device__ __forceinline__ float dot8(const uint4& w, const float* q) {
    float s = q[0] * bf_lo(w.x);
    s = fmaf(q[1], bf_hi(w.x), s);
    s = fmaf(q[2], bf_lo(w.y), s);
    s = fmaf(q[3], bf_hi(w.y), s);
    s = fmaf(q[4], bf_lo(w.z), s);
    s = fmaf(q[5], bf_hi(w.z), s);
    s = fmaf(q[6], bf_lo(w.w), s);
    s = fmaf(q[7], bf_hi(w.w), s);
    return s;
}

__device__ __forceinline__ void gemv4x32(const uint4 (&w)[10], const float* s_act, float* s_red,
                                         float* s_res, int tid) {
    float acc[NB][8];
#pragma unroll
    for (int b = 0; b < NB; ++b)
#pragma unroll
        for (int k = 0; k < 8; ++k) acc[b][k] = 0.f;
    const int rg = tid >> 2;
#pragma unroll
    for (int j = 0; j < 10; ++j) {
        const int r = rg + 64 * j;
#pragma unroll
        for (int b = 0; b < NB; ++b) fma8(acc[b], w[j], s_act[b * DM + r]);
    }
#pragma unroll
    for (int b = 0; b < NB; ++b)
#pragma unroll
        for (int k = 0; k < 8; ++k) {
            float v = acc[b][k];
            v += __shfl_xor_sync(0xffffffffu, v, 4);
            v += __shfl_xor_sync(0xffffffffu, v, 8);
            v += __shfl_xor_sync(0xffffffffu, v, 16);
            acc[b][k] = v;
        }
    const int lane = tid & 31, warp = tid >> 5;
    if (lane < 4) {
#pragma unroll
        for (int b = 0; b < NB; ++b)
#pragma unroll
            for (int k = 0; k < 8; ++k) s_red[warp * 128 + b * 32 + lane * 8 + k] = acc[b][k];
    }
    cons_sync();
    if (tid < 128) {
        float s = 0.f;
#pragma unroll
        for (int wv = 0; wv < 8; ++wv) s += s_red[wv * 128 + tid];
        s_res[tid] = s;
    }
    cons_sync();
}

__device__ __forceinline__ void ln_mod_row(const float (&xv)[20], const float* shift, const float* scale,
                                           float* out, int lane) {
    float s = 0.f;
#pragma unroll
    for (int i = 0; i < 20; ++i) s += xv[i];
    s = warp_sum(s);
    const float mean_f = s * (1.0f / DM);
    float v = 0.f;
#pragma unroll
    for (int i = 0; i < 20; ++i) { float d = xv[i] - mean_f; v = fmaf(d, d, v); }
    v = warp_sum(v);
    const float mean = bf16r(mean_f);
    const float var = bf16r(v * (1.0f / DM));
    const float den = bf16r(sqrtf(bf16r(var + 1e-5f)));
#pragma unroll
    for (int i = 0; i < 20; ++i) {
        const int c = lane + 32 * i;
        const float ln = bf16r(bf16r(xv[i] - mean) / den);
        const float sc = bf16r(1.0f + __ldcg(scale + c));
        out[c] = bf16r(bf16r(ln * sc) + __ldcg(shift + c));
    }
}

__device__ __forceinline__ float gelu_tanh(float x) {
    const float kBeta = 0.7978845608028654f;
    const float inner = kBeta * (x + 0.044715f * x * x * x);
    return 0.5f * x * (1.0f + tanhf(inner));
}

__global__ void __launch_bounds__(NTHREADS, 1)
decode_block_kernel(const __nv_bfloat16* __restrict__ x_in, const __nv_bfloat16* __restrict__ k_cache,
                    const __nv_bfloat16* __restrict__ v_cache, const __nv_bfloat16* __restrict__ wq,
                    const __nv_bfloat16* __restrict__ wo, const __nv_bfloat16* __restrict__ w_gate,
                    const __nv_bfloat16* __restrict__ w_up, const __nv_bfloat16* __restrict__ w_down,
                    const __nv_bfloat16* __restrict__ cvec, const __nv_bfloat16* __restrict__ w_mod,
                    __nv_bfloat16* __restrict__ out) {
    extern __shared__ __align__(128) unsigned char smem[];
    const int tid = threadIdx.x;
    const int cta = blockIdx.x;
    const int head = cta >> 2, batch = cta & 3;

    const uint32_t ring = smem_u32(smem + SM_RING);
    const uint32_t bar_full = smem_u32(smem + SM_BAR);
    const uint32_t bar_empty = bar_full + NST * 8;

    if (tid == 0) {
        for (int s = 0; s < NST; ++s) {
            mbar_init(bar_full + s * 8, 1);
            mbar_init(bar_empty + s * 8, 1);
        }
        asm volatile("fence.mbarrier_init.release.cluster;" ::: "memory");
        asm volatile("fence.proxy.async.shared::cta;" ::: "memory");
    }
    __syncthreads();

    if (tid >= NCONS) {
        if (tid == NCONS) {
            const size_t bh = (size_t)batch * NH + head;
            const unsigned char* kp = (const unsigned char*)(k_cache + bh * SK * DH);
            const unsigned char* vp = (const unsigned char*)(v_cache + bh * SK * DH);
            const unsigned char* wop = (const unsigned char*)(wo + (size_t)head * DH * DM);
            for (int i = 0; i < NTILES; ++i) {
                const int st = i % NST;
                if (i >= NST) mbar_wait(bar_empty + st * 8, ((i / NST) - 1) & 1);
                const unsigned char* src;
                uint32_t bytes;
                if (i < KT) { src = kp + (size_t)i * TILE_BYTES; bytes = TILE_BYTES; }
                else if (i < 2 * KT) { src = vp + (size_t)(i - KT) * TILE_BYTES; bytes = TILE_BYTES; }
                else { src = wop + (size_t)(i - 2 * KT) * WO_TILE_BYTES; bytes = WO_TILE_BYTES; }
                mbar_expect_tx(bar_full + st * 8, bytes);
                bulk_g2s(ring + st * TILE_BYTES, src, bytes, bar_full + st * 8);
            }
        }
        return;
    }

    const int lane = tid & 31, warp = tid >> 5;
    float* s_p = (float*)(smem + SM_P);
    float* s_a = (float*)(smem + SM_A);
    float* s_x1 = (float*)(smem + SM_X1);
    float* s_red = (float*)(smem + SM_RED);
    float* s_q = (float*)(smem + SM_Q);
    float* s_small = (float*)(smem + SM_SMALL);

    {
        uint4 w[10];
        if (cta < MODN / 32) {
            const uint4* wp = (const uint4*)(w_mod + (size_t)(tid >> 2) * MODN + cta * 32 + (tid & 3) * 8);
#pragma unroll
            for (int j = 0; j < 10; ++j) w[j] = __ldg(wp + (size_t)j * 64 * (MODN / 8));
            for (int i = tid; i < NB * DM; i += NCONS) {
                const float c = __bfloat162float(cvec[i]);
                s_a[i] = bf16r(c / (1.0f + __expf(-c)));
            }
            cons_sync();
            gemv4x32(w, s_a, s_red, s_small, tid);
            if (tid < 128) g_mod[(tid >> 5) * MODN + cta * 32 + (tid & 31)] = bf16r(s_small[tid]);
        } else if (cta == NCTA - 1) {
            for (int i = tid; i < NB * DM; i += NCONS) { g_attn[i] = 0.f; g_ffn[i] = 0.f; }
        }
    }
    grid_barrier(&g_bar[0], tid);

    if (warp == 0) {
        float xv[20];
#pragma unroll
        for (int i = 0; i < 20; ++i) xv[i] = __bfloat162float(x_in[batch * DM + lane + 32 * i]);
        ln_mod_row(xv, g_mod + batch * MODN + 0 * DM, g_mod + batch * MODN + 1 * DM, s_a, lane);
    }
    cons_sync();
    if (tid < 240) {
        const int cc = tid % 24, rg = tid / 24;
        const uint4* wp = (const uint4*)(wq + (size_t)(rg * 64) * (NH * DH) + head * DH + cc * 8);
        float acc[8];
#pragma unroll
        for (int k = 0; k < 8; ++k) acc[k] = 0.f;
#pragma unroll 1
        for (int r0 = 0; r0 < 64; r0 += 16) {
            uint4 w[16];
#pragma unroll
            for (int j = 0; j < 16; ++j) w[j] = __ldg(wp + (size_t)(r0 + j) * (NH * DH / 8));
#pragma unroll
            for (int j = 0; j < 16; ++j) fma8(acc, w[j], s_a[rg * 64 + r0 + j]);
        }
#pragma unroll
        for (int k = 0; k < 8; ++k) s_red[rg * DH + cc * 8 + k] = acc[k];
    }
    cons_sync();
    if (tid < DH) {
        float s = 0.f;
#pragma unroll
        for (int rg = 0; rg < 10; ++rg) s += s_red[rg * DH + tid];
        s_q[tid] = bf16r(s);
    }
    cons_sync();

    const int sub = lane & 7, grp = lane >> 3;
    {
        float qr[24];
#pragma unroll
        for (int j = 0; j < 3; ++j)
#pragma unroll
            for (int e = 0; e < 8; ++e) qr[j * 8 + e] = s_q[(sub + 8 * j) * 8 + e];
        const float scale = 0.07216878364870323f;
        for (int i = warp; i < KT; i += 8) {
            const int st = i % NST;
            mbar_wait(bar_full + st * 8, (i / NST) & 1);
            const uint4* tile = (const uint4*)(smem + SM_RING + st * TILE_BYTES);
            float part[8];
#pragma unroll
            for (int it = 0; it < 8; ++it) {
                const uint4* row = tile + (it * 4 + grp) * 24 + sub;
                const uint4 a = row[0], b = row[8], c = row[16];
                part[it] = dot8(a, qr) + dot8(b, qr + 8) + dot8(c, qr + 16);
            }
            __syncwarp();
            if (lane == 0) mbar_arrive(bar_empty + st * 8);
#pragma unroll
            for (int j = 0; j < 4; ++j) {
                const float send = (sub & 4) ? part[j] : part[j + 4];
                const float keep = (sub & 4) ? part[j + 4] : part[j];
                part[j] = keep + __shfl_xor_sync(0xffffffffu, send, 4);
            }
#pragma unroll
            for (int j = 0; j < 2; ++j) {
                const float send = (sub & 2) ? part[j] : part[j + 2];
                const float keep = (sub & 2) ? part[j + 2] : part[j];
                part[j] = keep + __shfl_xor_sync(0xffffffffu, send, 2);
            }
            {
                const float send = (sub & 1) ? part[0] : part[1];
                const float keep = (sub & 1) ? part[1] : part[0];
                part[0] = keep + __shfl_xor_sync(0xffffffffu, send, 1);
            }
            s_p[i * TILE_KEYS + sub * 4 + grp] = bf16r(bf16r(part[0]) * scale);
        }
    }
    cons_sync();

    {
        float sv[16];
        float m = -INFINITY;
#pragma unroll
        for (int i = 0; i < 16; ++i) { sv[i] = s_p[tid + NCONS * i]; m = fmaxf(m, sv[i]); }
        m = warp_max(m);
        if (lane == 0) s_small[warp] = m;
        cons_sync();
        m = s_small[0];
#pragma unroll
        for (int wv = 1; wv < 8; ++wv) m = fmaxf(m, s_small[wv]);
        float sum = 0.f;
#pragma unroll
        for (int i = 0; i < 16; ++i) { sv[i] = __expf(sv[i] - m); sum += sv[i]; }
        sum = warp_sum(sum);
        if (lane == 0) s_small[8 + warp] = sum;
        cons_sync();
        sum = 0.f;
#pragma unroll
        for (int wv = 0; wv < 8; ++wv) sum += s_small[8 + wv];
#pragma unroll
        for (int i = 0; i < 16; ++i) s_p[tid + NCONS * i] = bf16r(sv[i] / sum);
    }
    cons_sync();

    {
        float acc[3][8];
#pragma unroll
        for (int j = 0; j < 3; ++j)
#pragma unroll
            for (int e = 0; e < 8; ++e) acc[j][e] = 0.f;
        for (int i = KT + warp; i < 2 * KT; i += 8) {
            const int st = i % NST;
            mbar_wait(bar_full + st * 8, (i / NST) & 1);
            const uint4* tile = (const uint4*)(smem + SM_RING + st * TILE_BYTES);
            const float* pp = s_p + (i - KT) * TILE_KEYS + grp;
#pragma unroll
            for (int it = 0; it < 8; ++it) {
                const uint4* row = tile + (it * 4 + grp) * 24 + sub;
                const uint4 a = row[0], b = row[8], c = row[16];
                const float p = pp[it * 4];
                fma8(acc[0], a, p);
                fma8(acc[1], b, p);
                fma8(acc[2], c, p);
            }
            __syncwarp();
            if (lane == 0) mbar_arrive(bar_empty + st * 8);
        }
#pragma unroll
        for (int j = 0; j < 3; ++j)
#pragma unroll
            for (int e = 0; e < 8; ++e) {
                float v = acc[j][e];
                v += __shfl_xor_sync(0xffffffffu, v, 8);
                v += __shfl_xor_sync(0xffffffffu, v, 16);
                if (grp == 0) s_a[warp * DH + (sub + 8 * j) * 8 + e] = v;
            }
    }
    cons_sync();
    if (tid < DH) {
        float s = 0.f;
#pragma unroll
        for (int wv = 0; wv < 8; ++wv) s += s_a[wv * DH + tid];
        s_q[tid] = bf16r(s);
    }
    cons_sync();

    uint4 wgu[10];
    uint4 wd[16];
    if (cta < FF / 16) {
        const __nv_bfloat16* base = ((tid >> 1) & 1) ? w_up : w_gate;
        const uint4* wp = (const uint4*)(base + (size_t)(tid >> 2) * FF + cta * 16 + (tid & 1) * 8);
#pragma unroll
        for (int j = 0; j < 10; ++j) wgu[j] = __ldg(wp + (size_t)j * 64 * (FF / 8));
        if (tid < 80) {
            const uint4* dp = (const uint4*)(w_down + (size_t)(cta * 16) * DM + tid * 8);
#pragma unroll
            for (int j = 0; j < 16; ++j) wd[j] = __ldg(dp + j * (DM / 8));
        }
    }
    {
        float acc[20];
#pragma unroll
        for (int m = 0; m < 20; ++m) acc[m] = 0.f;
        for (int i = 2 * KT + warp; i < NTILES; i += 8) {
            const int st = i % NST;
            mbar_wait(bar_full + st * 8, (i / NST) & 1);
            const uint32_t* tile = (const uint32_t*)(smem + SM_RING + st * TILE_BYTES);
            const float* op = s_q + (i - 2 * KT) * WO_ROWS;
#pragma unroll
            for (int r = 0; r < WO_ROWS; ++r) {
                const float o = op[r];
#pragma unroll
                for (int m = 0; m < 10; ++m) {
                    const uint32_t u = tile[r * (DM / 2) + lane + 32 * m];
                    acc[2 * m] = fmaf(o, bf_lo(u), acc[2 * m]);
                    acc[2 * m + 1] = fmaf(o, bf_hi(u), acc[2 * m + 1]);
                }
            }
            __syncwarp();
            if (lane == 0) mbar_arrive(bar_empty + st * 8);
        }
#pragma unroll
        for (int m = 0; m < 10; ++m)
            *(float2*)(s_red + warp * DM + 2 * lane + 64 * m) = make_float2(acc[2 * m], acc[2 * m + 1]);
    }
    cons_sync();
    if (tid < DM / 4) {
        float4 s = make_float4(0.f, 0.f, 0.f, 0.f);
#pragma unroll
        for (int wv = 0; wv < 8; ++wv) {
            const float4 v = *(const float4*)(s_red + wv * DM + tid * 4);
            s.x += v.x; s.y += v.y; s.z += v.z; s.w += v.w;
        }
        red_add_v4(g_attn + batch * DM + tid * 4, s.x, s.y, s.z, s.w);
    }
    grid_barrier(&g_bar[1], tid);

    if (warp < NB) {
        const int b = warp;
        float xv[20];
#pragma unroll
        for (int i = 0; i < 20; ++i) {
            const int c = lane + 32 * i;
            const float a = bf16r(__ldcg(g_attn + b * DM + c));
            const float ga = __ldcg(g_mod + b * MODN + 2 * DM + c);
            xv[i] = bf16r(__bfloat162float(x_in[b * DM + c]) + bf16r(ga * a));
            s_x1[b * DM + c] = xv[i];
        }
        ln_mod_row(xv, g_mod + b * MODN + 3 * DM, g_mod + b * MODN + 4 * DM, s_a + b * DM, lane);
    }
    cons_sync();
    if (cta < FF / 16) {
        gemv4x32(wgu, s_a, s_red, s_small, tid);
        if (tid < 64) {
            const int b = tid >> 4, c = tid & 15;
            const float g = bf16r(s_small[b * 32 + c]);
            const float u = bf16r(s_small[b * 32 + 16 + c]);
            s_small[128 + tid] = bf16r(bf16r(gelu_tanh(g)) * u);
        }
        cons_sync();
        if (tid < 80) {
            float acc[NB][8];
#pragma unroll
            for (int b = 0; b < NB; ++b)
#pragma unroll
                for (int k = 0; k < 8; ++k) acc[b][k] = 0.f;
#pragma unroll
            for (int j = 0; j < 16; ++j)
#pragma unroll
                for (int b = 0; b < NB; ++b) fma8(acc[b], wd[j], s_small[128 + b * 16 + j]);
#pragma unroll
            for (int b = 0; b < NB; ++b) {
                red_add_v4(g_ffn + b * DM + tid * 8, acc[b][0], acc[b][1], acc[b][2], acc[b][3]);
                red_add_v4(g_ffn + b * DM + tid * 8 + 4, acc[b][4], acc[b][5], acc[b][6], acc[b][7]);
            }
        }
    }
    cons_sync();
    if (tid == 0) {
        __threadfence();
        unsigned int old = atomicAdd(&g_bar[2], 1u);
        s_small[255] = ((old % NCTA) == NCTA - 1) ? 1.f : 0.f;
        __threadfence();
    }
    cons_sync();
    if (s_small[255] != 0.f) {
        for (int i = tid; i < NB * DM; i += NCONS) {
            const int b = i / DM, c = i % DM;
            const float f = bf16r(__ldcg(g_ffn + i));
            const float gb = __ldcg(g_mod + b * MODN + 5 * DM + c);
            out[i] = __float2bfloat16_rn(s_x1[i] + bf16r(gb * f));
        }
    }
}

}

extern "C" void kernel_launch(void* const* d_in, const int* in_sizes, int n_in, void* d_out, int out_size) {
    (void)in_sizes; (void)n_in; (void)out_size;
    const __nv_bfloat16* A_x = (const __nv_bfloat16*)d_in[0];
    const __nv_bfloat16* A_k = (const __nv_bfloat16*)d_in[1];
    const __nv_bfloat16* A_v = (const __nv_bfloat16*)d_in[2];
    const __nv_bfloat16* A_wq = (const __nv_bfloat16*)d_in[3];
    const __nv_bfloat16* A_wo = (const __nv_bfloat16*)d_in[4];
    const __nv_bfloat16* B_wg = (const __nv_bfloat16*)d_in[6];
    const __nv_bfloat16* B_wu = (const __nv_bfloat16*)d_in[7];
    const __nv_bfloat16* B_wd = (const __nv_bfloat16*)d_in[8];
    const __nv_bfloat16* c = (const __nv_bfloat16*)d_in[9];
    const __nv_bfloat16* w_mod = (const __nv_bfloat16*)d_in[10];
    static bool attr_set = false;
    if (!attr_set) {
        cudaFuncSetAttribute(decode_block_kernel, cudaFuncAttributeMaxDynamicSharedMemorySize, SM_TOTAL);
        attr_set = true;
    }
    decode_block_kernel<<<NCTA, NTHREADS, SM_TOTAL>>>(A_x, A_k, A_v, A_wq, A_wo, B_wg, B_wu, B_wd, c, w_mod,
                                                      (__nv_bfloat16*)d_out);
}
```

```cpp
#include <cuda_runtime.h>
#include <cuda_bf16.h>
#include <stdint.h>

namespace {

constexpr int NB = 4;
constexpr int DM = 640;
constexpr int NH = 32;
constexpr int SK = 4096;
constexpr int DH = 192;
constexpr int FF = 1536;
constexpr int MODN = 6 * DM;
constexpr int QN = NH * DH;
constexpr int NBH = NB * NH;

constexpr int NCONS = 256;
constexpr int NTHREADS = NCONS + 32;
constexpr int TILE_KEYS = 32;
constexpr int TILE_BYTES = TILE_KEYS * DH * 2;
constexpr int NST = 16;
constexpr int PRE = 6;
constexpr int TPI = 4;
constexpr int ITEM_KEYS = TPI * TILE_KEYS;
constexpr int CHUNKS = SK / ITEM_KEYS;
constexpr int NITEM_K = NBH * CHUNKS;
constexpr int NITEM = 2 * NITEM_K;

constexpr int A_PITCH = 1296;
constexpr int WIDE_PITCH = 1296;
constexpr int P32 = 80;
constexpr int P48 = 112;

constexpr int SM_RING = 0;
constexpr int SM_WMOD = PRE * TILE_BYTES;
constexpr int SM_WQ = SM_WMOD + DM * P32;
constexpr int SM_WO = 0;
constexpr int SM_WGU = SM_WO + 48 * WIDE_PITCH;
constexpr int SM_WD = SM_WGU + DM * P32;
constexpr int SM_X = SM_WD + 16 * WIDE_PITCH;
constexpr int SM_A = NST * TILE_BYTES;
constexpr int SM_PART = SM_A + NB * A_PITCH;
constexpr int SM_XP = SM_PART + 8 * 4 * 80 * 4;
constexpr int SM_ITEM = SM_XP + NB * DM * 4;
constexpr int SM_BAR = SM_ITEM + NST * 4;
constexpr int SM_TOTAL = SM_BAR + 2 * NST * 8;
static_assert(SM_WQ + DM * P48 <= NST * TILE_BYTES, "prologue overlay");
static_assert(SM_X + NB * DM * 4 <= NST * TILE_BYTES, "tail overlay");
static_assert(SM_TOTAL <= 232448, "smem");

__device__ __align__(128) float g_mod[NB * MODN];
__device__ __align__(128) __nv_bfloat16 g_q[NB * QN];
__device__ __align__(128) float g_s[NBH * SK];
__device__ __align__(128) float2 g_stat[NBH * CHUNKS];
__device__ __align__(128) float2 g_hstat[NBH];
__device__ __align__(128) unsigned int g_kcnt[NBH];
__device__ __align__(128) unsigned int g_hready[NBH];
__device__ __align__(128) float g_o[NB * QN];
__device__ __align__(128) float g_attn[NB * DM];
__device__ __align__(128) float g_ffn[NB * DM];
__device__ __align__(128) unsigned int g_bar[8];
__device__ unsigned int g_work;

#define PROF(k) do { } while (0)
#define PROFP(k) do { } while (0)

__device__ __forceinline__ float bf16r(float x) { return __bfloat162float(__float2bfloat16_rn(x)); }
__device__ __forceinline__ float bf_lo(uint32_t u) { return __uint_as_float(u << 16); }
__device__ __forceinline__ float bf_hi(uint32_t u) { return __uint_as_float(u & 0xffff0000u); }

__device__ __forceinline__ uint32_t smem_u32(const void* p) { return (uint32_t)__cvta_generic_to_shared(p); }
__device__ __forceinline__ void mbar_init(uint32_t bar, uint32_t count) {
    asm volatile("mbarrier.init.shared::cta.b64 [%0], %1;" ::"r"(bar), "r"(count) : "memory");
}
__device__ __forceinline__ void mbar_expect_tx(uint32_t bar, uint32_t bytes) {
    asm volatile("mbarrier.arrive.expect_tx.shared::cta.b64 _, [%0], %1;" ::"r"(bar), "r"(bytes) : "memory");
}
__device__ __forceinline__ void mbar_arrive(uint32_t bar) {
    asm volatile("mbarrier.arrive.shared::cta.b64 _, [%0];" ::"r"(bar) : "memory");
}
constexpr long long WAIT_LIMIT_CYCLES = 200000000LL;
__device__ __forceinline__ uint32_t mbar_try(uint32_t bar, uint32_t parity) {
    uint32_t done;
    asm volatile(
        "{\n\t.reg .pred p;\n\t"
        "mbarrier.try_wait.parity.shared::cta.b64 p, [%1], %2;\n\t"
        "selp.u32 %0, 1, 0, p;\n\t}"
        : "=r"(done) : "r"(bar), "r"(parity) : "memory");
    return done;
}
__device__ __noinline__ void mbar_wait_slow(uint32_t bar, uint32_t parity) {
    const long long t0 = clock64();
    while (!mbar_try(bar, parity)) {
        if (clock64() - t0 > WAIT_LIMIT_CYCLES) __trap();
    }
}
__device__ __forceinline__ void mbar_wait(uint32_t bar, uint32_t parity) {
    if (!mbar_try(bar, parity)) mbar_wait_slow(bar, parity);
}
__device__ __forceinline__ void stage_wait(uint32_t bar_full, uint32_t bar_empty, int u) {
    const uint32_t off = (u % NST) * 8, par = (u / NST) & 1;
    mbar_wait(bar_empty + off, par);
    mbar_wait(bar_full + off, par);
}
__device__ __forceinline__ void bulk_g2s(uint32_t dst, const void* src, uint32_t bytes, uint32_t bar) {
    asm volatile(
        "cp.async.bulk.shared::cluster.global.mbarrier::complete_tx::bytes [%0], [%1], %2, [%3];"
        ::"r"(dst), "l"(src), "r"(bytes), "r"(bar) : "memory");
}
__device__ __forceinline__ void cp_async16(uint32_t dst, const void* src) {
    asm volatile("cp.async.cg.shared.global [%0], [%1], 16;" ::"r"(dst), "l"(src) : "memory");
}
__device__ __forceinline__ void cp_async_wait_all() { asm volatile("cp.async.wait_all;" ::: "memory"); }
__device__ __forceinline__ void cons_sync() { asm volatile("bar.sync 1, 256;" ::: "memory"); }

__device__ __forceinline__ void red_add_v4(float* p, float a, float b, float c, float d) {
    asm volatile("red.global.add.v4.f32 [%0], {%1, %2, %3, %4};" ::"l"(p), "f"(a), "f"(b), "f"(c), "f"(d) : "memory");
}
__device__ __forceinline__ unsigned int ld_acquire(const unsigned int* p) {
    unsigned int v;
    asm volatile("ld.acquire.gpu.global.u32 %0, [%1];" : "=r"(v) : "l"(p) : "memory");
    return v;
}
__device__ __forceinline__ void st_release(unsigned int* p, unsigned int v) {
    asm volatile("st.release.gpu.global.u32 [%0], %1;" ::"l"(p), "r"(v) : "memory");
}

__device__ __noinline__ void grid_barrier(unsigned int* ctr, int tid) {
    cons_sync();
    if (tid == 0) {
        const unsigned int n = gridDim.x;
        __threadfence();
        const unsigned int old = atomicAdd(ctr, 1u);
        const unsigned int target = (old / n + 1u) * n;
        const long long t0 = clock64();
        while ((int)(ld_acquire(ctr) - target) < 0) {
            if (clock64() - t0 > WAIT_LIMIT_CYCLES) __trap();
        }
        __threadfence();
    }
    cons_sync();
}

__device__ __forceinline__ float warp_sum(float v) {
#pragma unroll
    for (int o = 16; o > 0; o >>= 1) v += __shfl_xor_sync(0xffffffffu, v, o);
    return v;
}
__device__ __forceinline__ float warp_max(float v) {
#pragma unroll
    for (int o = 16; o > 0; o >>= 1) v = fmaxf(v, __shfl_xor_sync(0xffffffffu, v, o));
    return v;
}

__device__ __forceinline__ void fma8(float (&acc)[8], const uint4& w, float s) {
    acc[0] = fmaf(s, bf_lo(w.x), acc[0]);
    acc[1] = fmaf(s, bf_hi(w.x), acc[1]);
    acc[2] = fmaf(s, bf_lo(w.y), acc[2]);
    acc[3] = fmaf(s, bf_hi(w.y), acc[3]);
    acc[4] = fmaf(s, bf_lo(w.z), acc[4]);
    acc[5] = fmaf(s, bf_hi(w.z), acc[5]);
    acc[6] = fmaf(s, bf_lo(w.w), acc[6]);
    acc[7] = fmaf(s, bf_hi(w.w), acc[7]);
}
__device__ __forceinline__ float dot8(const uint4& w, const float* q) {
    float s = q[0] * bf_lo(w.x);
    s = fmaf(q[1], bf_hi(w.x), s);
    s = fmaf(q[2], bf_lo(w.y), s);
    s = fmaf(q[3], bf_hi(w.y), s);
    s = fmaf(q[4], bf_lo(w.z), s);
    s = fmaf(q[5], bf_hi(w.z), s);
    s = fmaf(q[6], bf_lo(w.w), s);
    s = fmaf(q[7], bf_hi(w.w), s);
    return s;
}

__device__ __noinline__ void stage_rows(uint32_t dst, int dst_pitch, const void* src, int src_stride, int rows,
                                        int cpr, int tid) {
    const int n = rows * cpr;
    for (int i = tid; i < n; i += NCONS) {
        const int r = i / cpr, c = i - r * cpr;
        cp_async16(dst + r * dst_pitch + c * 16, (const unsigned char*)src + (size_t)r * src_stride + c * 16);
    }
}

__device__ __noinline__ void gemv_mma(uint32_t w, int w_pitch, uint32_t a, int ksteps, int ntiles, float* part,
                                      int lane) {
    float c[10][4];
#pragma unroll
    for (int nt = 0; nt < 10; ++nt) { c[nt][0] = 0.f; c[nt][1] = 0.f; c[nt][2] = 0.f; c[nt][3] = 0.f; }
    uint32_t ap = a + (lane >> 2) * A_PITCH + (lane & 3) * 4;
    uint32_t wp = w + (lane & 15) * w_pitch;
    for (int ks = 0; ks < ksteps; ++ks) {
        uint32_t a0 = 0, a2 = 0;
        if (lane < 16) {
            asm volatile("ld.shared.u32 %0, [%1];" : "=r"(a0) : "r"(ap));
            asm volatile("ld.shared.u32 %0, [%1];" : "=r"(a2) : "r"(ap + 16));
        }
#pragma unroll
        for (int nt = 0; nt < 10; ++nt) {
            if (nt < ntiles) {
                uint32_t b0, b1;
                asm volatile("ldmatrix.sync.aligned.m8n8.x2.trans.shared.b16 {%0, %1}, [%2];"
                             : "=r"(b0), "=r"(b1) : "r"(wp + nt * 16));
                asm volatile(
                    "mma.sync.aligned.m16n8k16.row.col.f32.bf16.bf16.f32 {%0, %1, %2, %3}, {%4, %5, %6, %7}, "
                    "{%8, %9}, {%0, %1, %2, %3};"
                    : "+f"(c[nt][0]), "+f"(c[nt][1]), "+f"(c[nt][2]), "+f"(c[nt][3])
                    : "r"(a0), "r"(0u), "r"(a2), "r"(0u), "r"(b0), "r"(b1));
            }
        }
        ap += 32;
        wp += 16 * w_pitch;
    }
    if (lane < 16) {
        float* pp = part + (lane >> 2) * 80 + (lane & 3) * 2;
#pragma unroll
        for (int nt = 0; nt < 10; ++nt)
            if (nt < ntiles) *(float2*)(pp + nt * 8) = make_float2(c[nt][0], c[nt][1]);
    }
}

__device__ __forceinline__ float tall_sum(const float* part, int b, int n) {
    float s = 0.f;
#pragma unroll
    for (int w = 0; w < 8; ++w) s += part[(w * 4 + b) * 80 + n];
    return s;
}

__device__ __noinline__ void wide_flush(const float* part, float* dst, int tid) {
    for (int i = tid; i < NB * DM / 4; i += NCONS) {
        const int b = i / 160, col = (i - b * 160) * 4;
        const int w = col / 80, n = col - w * 80;
        const float4 v = *(const float4*)(part + (w * 4 + b) * 80 + n);
        red_add_v4(dst + b * DM + col, v.x, v.y, v.z, v.w);
    }
}

__device__ __noinline__ void ln_mod_row(const float* xs, const float* shift, const float* scale,
                                        __nv_bfloat16* out, int lane) {
    float s = 0.f;
    for (int c = lane; c < DM; c += 32) s += xs[c];
    s = warp_sum(s);
    const float mean_f = s * (1.0f / DM);
    float v = 0.f;
    for (int c = lane; c < DM; c += 32) { const float d = xs[c] - mean_f; v = fmaf(d, d, v); }
    v = warp_sum(v);
    const float mean = bf16r(mean_f);
    const float den = bf16r(sqrtf(bf16r(bf16r(v * (1.0f / DM)) + 1e-5f)));
    for (int c = lane; c < DM; c += 32) {
        const float ln = bf16r(bf16r(xs[c] - mean) / den);
        const float sc = bf16r(1.0f + __ldcg(scale + c));
        out[c] = __float2bfloat16_rn(bf16r(ln * sc) + __ldcg(shift + c));
    }
}

__device__ __forceinline__ float gelu_tanh(float x) {
    const float kBeta = 0.7978845608028654f;
    const float inner = kBeta * (x + 0.044715f * x * x * x);
    return 0.5f * x * (1.0f + tanhf(inner));
}

__global__ void __launch_bounds__(NTHREADS, 1)
decode_block_kernel(const __nv_bfloat16* __restrict__ x_in, const __nv_bfloat16* __restrict__ k_cache,
                    const __nv_bfloat16* __restrict__ v_cache, const __nv_bfloat16* __restrict__ wq,
                    const __nv_bfloat16* __restrict__ wo, const __nv_bfloat16* __restrict__ w_gate,
                    const __nv_bfloat16* __restrict__ w_up, const __nv_bfloat16* __restrict__ w_down,
                    const __nv_bfloat16* __restrict__ cvec, const __nv_bfloat16* __restrict__ w_mod,
                    __nv_bfloat16* __restrict__ out) {
    extern __shared__ __align__(128) unsigned char smem[];
    const int tid = threadIdx.x;
    const int cta = blockIdx.x;

    const uint32_t sbase = smem_u32(smem);
    const uint32_t bar_full = sbase + SM_BAR;
    const uint32_t bar_empty = bar_full + NST * 8;
    volatile int* s_item = (volatile int*)(smem + SM_ITEM);

    if (tid == 0) {
        for (int s = 0; s < NST; ++s) {
            mbar_init(bar_full + s * 8, 1);
            mbar_init(bar_empty + s * 8, 1);
        }
        asm volatile("fence.mbarrier_init.release.cluster;" ::: "memory");
        asm volatile("fence.proxy.async.shared::cta;" ::: "memory");
        for (int s = 0; s < PRE; ++s) mbar_arrive(bar_empty + s * 8);
    }
    __syncthreads();

    if (tid >= NCONS) {
        if (tid == NCONS) {
            int item = cta;
            int u = 0;
            while (item < NITEM) {
                const int next = (int)atomicAdd(&g_work, 1u) + (int)gridDim.x;
                const unsigned char* src = (const unsigned char*)(item < NITEM_K ? k_cache : v_cache) +
                                           (size_t)(item & (NITEM_K - 1)) * (ITEM_KEYS * DH * 2);
                for (int t = 0; t < TPI; ++t, ++u) {
                    const int st = u % NST;
                    mbar_wait(bar_empty + st * 8, (u / NST) & 1);
                    s_item[st] = item;
                    mbar_expect_tx(bar_full + st * 8, TILE_BYTES);
                    bulk_g2s(sbase + SM_RING + st * TILE_BYTES, src + t * TILE_BYTES, TILE_BYTES, bar_full + st * 8);
                }
                item = next;
            }
            for (int j = 0; j < 8; ++j, u += TPI) {
                const int st = u % NST;
                mbar_wait(bar_empty + st * 8, (u / NST) & 1);
                s_item[st] = -1;
                mbar_arrive(bar_full + st * 8);
            }
            PROFP(13);
        }
        return;
    }

    const int lane = tid & 31, warp = tid >> 5;
    float* s_part = (float*)(smem + SM_PART);
    float* s_xp = (float*)(smem + SM_XP);
    __nv_bfloat16* s_a = (__nv_bfloat16*)(smem + SM_A);

    PROF(0);
    if (cta < MODN / 32) stage_rows(sbase + SM_WMOD, P32, w_mod + cta * 32, MODN * 2, DM, 4, tid);
    if (cta < QN / 48) stage_rows(sbase + SM_WQ, P48, wq + cta * 48, QN * 2, DM, 6, tid);
    for (int i = tid; i < NB * DM; i += NCONS) {
        const int b = i / DM, c = i - b * DM;
        const float cv = __bfloat162float(cvec[i]);
        s_a[b * (A_PITCH / 2) + c] = __float2bfloat16_rn(cv / (1.0f + __expf(-cv)));
        s_xp[i] = __bfloat162float(x_in[i]);
    }
    if (cta == gridDim.x - 1) {
        for (int i = tid; i < NB * QN; i += NCONS) g_o[i] = 0.f;
        for (int i = tid; i < NB * DM; i += NCONS) { g_attn[i] = 0.f; g_ffn[i] = 0.f; }
        if (tid < NBH) { g_kcnt[tid] = 0u; g_hready[tid] = 0u; }
    }
    cp_async_wait_all();
    cons_sync();
    if (cta < MODN / 32) {
        gemv_mma(sbase + SM_WMOD + warp * 80 * P32, P32, sbase + SM_A + warp * 160, 5, 4, s_part + warp * 320, lane);
        cons_sync();
        if (tid < 128) g_mod[(tid >> 5) * MODN + cta * 32 + (tid & 31)] = bf16r(tall_sum(s_part, tid >> 5, tid & 31));
    }
    PROF(1);
    grid_barrier(&g_bar[0], tid);
    PROF(2);

    if (cta < QN / 48) {
        if (warp < NB)
            ln_mod_row(s_xp + warp * DM, g_mod + warp * MODN, g_mod + warp * MODN + DM, s_a + warp * (A_PITCH / 2), lane);
        cons_sync();
        gemv_mma(sbase + SM_WQ + warp * 80 * P48, P48, sbase + SM_A + warp * 160, 5, 6, s_part + warp * 320, lane);
        cons_sync();
        if (tid < 192) {
            const int b = tid / 48, n = tid - b * 48;
            g_q[b * QN + cta * 48 + n] = __float2bfloat16_rn(tall_sum(s_part, b, n));
        }
    }
    PROF(3);
    grid_barrier(&g_bar[1], tid);
    if (tid == 0)
        for (int s = PRE; s < NST; ++s) mbar_arrive(bar_empty + s * 8);
    PROF(4);

    {
        const int sub = lane & 7, grp = lane >> 3;
        for (int u0 = warp * TPI;; u0 += 8 * TPI) {
            stage_wait(bar_full, bar_empty, u0);
            const int item = s_item[u0 % NST];
            if (item < 0) {
                __syncwarp();
                if (lane == 0) mbar_arrive(bar_empty + (u0 % NST) * 8);
                break;
            }
            const int bh = (item & (NITEM_K - 1)) / CHUNKS;
            float* gs = g_s + (size_t)(item & (NITEM_K - 1)) * ITEM_KEYS;
            if (item < NITEM_K) {
                float qr[24];
                {
                    const uint4* qp = (const uint4*)(g_q + (bh >> 5) * QN + (bh & 31) * DH) + sub;
#pragma unroll
                    for (int j = 0; j < 3; ++j) {
                        const uint4 v = __ldcg(qp + 8 * j);
                        qr[j * 8 + 0] = bf_lo(v.x); qr[j * 8 + 1] = bf_hi(v.x);
                        qr[j * 8 + 2] = bf_lo(v.y); qr[j * 8 + 3] = bf_hi(v.y);
                        qr[j * 8 + 4] = bf_lo(v.z); qr[j * 8 + 5] = bf_hi(v.z);
                        qr[j * 8 + 6] = bf_lo(v.w); qr[j * 8 + 7] = bf_hi(v.w);
                    }
                }
                float m_run = -INFINITY, l_run = 0.f;
#pragma unroll 1
                for (int t = 0; t < TPI; ++t) {
                    const int u = u0 + t, st = u % NST;
                    stage_wait(bar_full, bar_empty, u);
                    const uint4* tile = (const uint4*)(smem + SM_RING + st * TILE_BYTES);
                    float part[8];
#pragma unroll
                    for (int it = 0; it < 8; ++it) {
                        const uint4* row = tile + (it * 4 + grp) * 24 + sub;
                        const uint4 a = row[0], b = row[8], c = row[16];
                        part[it] = dot8(a, qr) + dot8(b, qr + 8) + dot8(c, qr + 16);
                    }
                    __syncwarp();
                    if (lane == 0) mbar_arrive(bar_empty + st * 8);
#pragma unroll
                    for (int j = 0; j < 4; ++j) {
                        const float send = (sub & 4) ? part[j] : part[j + 4];
                        const float keep = (sub & 4) ? part[j + 4] : part[j];
                        part[j] = keep + __shfl_xor_sync(0xffffffffu, send, 4);
                    }
#pragma unroll
                    for (int j = 0; j < 2; ++j) {
                        const float send = (sub & 2) ? part[j] : part[j + 2];
                        const float keep = (sub & 2) ? part[j + 2] : part[j];
                        part[j] = keep + __shfl_xor_sync(0xffffffffu, send, 2);
                    }
                    {
                        const float send = (sub & 1) ? part[0] : part[1];
                        const float keep = (sub & 1) ? part[1] : part[0];
                        part[0] = keep + __shfl_xor_sync(0xffffffffu, send, 1);
                    }
                    const float s = bf16r(bf16r(part[0]) * 0.07216878364870323f);
                    gs[t * TILE_KEYS + sub * 4 + grp] = s;
                    const float m_new = fmaxf(m_run, s);
                    l_run = l_run * __expf(m_run - m_new) + __expf(s - m_new);
                    m_run = m_new;
                }
                const float m = warp_max(m_run);
                const float l = warp_sum(l_run * __expf(m_run - m));
                __syncwarp();
                unsigned int old = 0;
                if (lane == 0) {
                    g_stat[item] = make_float2(m, l);
                    __threadfence();
                    old = atomicAdd(&g_kcnt[bh], 1u);
                    __threadfence();
                }
                old = __shfl_sync(0xffffffffu, old, 0);
                if (old == CHUNKS - 1) {
                    const float2 st2 = __ldcg(&g_stat[bh * CHUNKS + lane]);
                    const float mm = warp_max(st2.x);
                    const float ll = warp_sum(st2.y * __expf(st2.x - mm));
                    if (lane == 0) {
                        g_hstat[bh] = make_float2(mm, ll);
                        st_release(&g_hready[bh], 1u);
                    }
                }
            } else {
                if (ld_acquire(&g_hready[bh]) == 0u) {
                    const long long t0 = clock64();
                    while (ld_acquire(&g_hready[bh]) == 0u)
                        if (clock64() - t0 > WAIT_LIMIT_CYCLES) __trap();
                }
                const float2 hs = __ldcg(&g_hstat[bh]);
                float acc[3][8];
#pragma unroll
                for (int j = 0; j < 3; ++j)
#pragma unroll
                    for (int e = 0; e < 8; ++e) acc[j][e] = 0.f;
#pragma unroll 1
                for (int t = 0; t < TPI; ++t) {
                    const int u = u0 + t, st = u % NST;
                    const float pl = bf16r(__expf(__ldcg(gs + t * TILE_KEYS + lane) - hs.x) / hs.y);
                    stage_wait(bar_full, bar_empty, u);
                    const uint4* tile = (const uint4*)(smem + SM_RING + st * TILE_BYTES);
#pragma unroll
                    for (int it = 0; it < 8; ++it) {
                        const uint4* row = tile + (it * 4 + grp) * 24 + sub;
                        const uint4 a = row[0], b = row[8], c = row[16];
                        const float p = __shfl_sync(0xffffffffu, pl, it * 4 + grp);
                        fma8(acc[0], a, p);
                        fma8(acc[1], b, p);
                        fma8(acc[2], c, p);
                    }
                    __syncwarp();
                    if (lane == 0) mbar_arrive(bar_empty + st * 8);
                }
                float* go = g_o + (bh >> 5) * QN + (bh & 31) * DH + sub * 8;
#pragma unroll
                for (int j = 0; j < 3; ++j) {
#pragma unroll
                    for (int e = 0; e < 8; ++e) {
                        float v = acc[j][e];
                        v += __shfl_xor_sync(0xffffffffu, v, 8);
                        v += __shfl_xor_sync(0xffffffffu, v, 16);
                        acc[j][e] = v;
                    }
                    if (grp == 0) {
                        red_add_v4(go + j * 64, acc[j][0], acc[j][1], acc[j][2], acc[j][3]);
                        red_add_v4(go + j * 64 + 4, acc[j][4], acc[j][5], acc[j][6], acc[j][7]);
                    }
                }
            }
        }
    }
    PROF(5);
    cons_sync();
    if (cta < QN / 48) stage_rows(sbase + SM_WO, WIDE_PITCH, wo + (size_t)cta * 48 * DM, DM * 2, 48, 80, tid);
    if (cta < FF / 16) {
        stage_rows(sbase + SM_WGU, P32, w_gate + cta * 16, FF * 2, DM, 2, tid);
        stage_rows(sbase + SM_WGU + 32, P32, w_up + cta * 16, FF * 2, DM, 2, tid);
        stage_rows(sbase + SM_WD, WIDE_PITCH, w_down + (size_t)cta * 16 * DM, DM * 2, 16, 80, tid);
    }
    PROF(6);
    grid_barrier(&g_bar[2], tid);
    PROF(7);

    if (cta < QN / 48) {
        if (tid < 192) {
            const int b = tid / 48, n = tid - b * 48;
            s_a[b * (A_PITCH / 2) + n] = __float2bfloat16_rn(__ldcg(g_o + b * QN + cta * 48 + n));
        }
        cp_async_wait_all();
        cons_sync();
        gemv_mma(sbase + SM_WO + warp * 160, WIDE_PITCH, sbase + SM_A, 3, 10, s_part + warp * 320, lane);
        cons_sync();
        wide_flush(s_part, g_attn, tid);
    }
    PROF(8);
    grid_barrier(&g_bar[3], tid);
    PROF(9);

    float* s_x = (float*)(smem + SM_X);
    for (int i = tid; i < NB * DM; i += NCONS) {
        const int b = i / DM, c = i - b * DM;
        const float a = bf16r(__ldcg(g_attn + i));
        s_x[i] = bf16r(s_xp[i] + bf16r(__ldcg(g_mod + b * MODN + 2 * DM + c) * a));
    }
    cons_sync();
    if (cta < FF / 16) {
        if (warp < NB)
            ln_mod_row(s_x + warp * DM, g_mod + warp * MODN + 3 * DM, g_mod + warp * MODN + 4 * DM,
                       s_a + warp * (A_PITCH / 2), lane);
        cp_async_wait_all();
        cons_sync();
        gemv_mma(sbase + SM_WGU + warp * 80 * P32, P32, sbase + SM_A + warp * 160, 5, 4, s_part + warp * 320, lane);
        cons_sync();
        if (tid < 64) {
            const int b = tid >> 4, n = tid & 15;
            const float g = bf16r(tall_sum(s_part, b, n));
            const float up = bf16r(tall_sum(s_part, b, 16 + n));
            s_a[b * (A_PITCH / 2) + n] = __float2bfloat16_rn(bf16r(gelu_tanh(g)) * up);
        }
        cons_sync();
        gemv_mma(sbase + SM_WD + warp * 160, WIDE_PITCH, sbase + SM_A, 1, 10, s_part + warp * 320, lane);
        cons_sync();
        wide_flush(s_part, g_ffn, tid);
    }
    PROF(10);
    cons_sync();
    if (tid == 0) {
        __threadfence();
        const unsigned int old = atomicAdd(&g_bar[4], 1u);
        s_item[0] = ((old % gridDim.x) == gridDim.x - 1) ? 1 : 0;
        __threadfence();
    }
    cons_sync();
    if (s_item[0] != 0) {
        for (int i = tid; i < NB * DM; i += NCONS) {
            const int b = i / DM, c = i - b * DM;
            const float f = bf16r(__ldcg(g_ffn + i));
            const float gb = __ldcg(g_mod + b * MODN + 5 * DM + c);
            out[i] = __float2bfloat16_rn(s_x[i] + bf16r(gb * f));
        }
        if (tid == 0) g_work = 0u;
        PROF(11);
    }
}

}

extern "C" void kernel_launch(void* const* d_in, const int* in_sizes, int n_in, void* d_out, int out_size) {
    (void)in_sizes; (void)n_in; (void)out_size;
    const __nv_bfloat16* A_x = (const __nv_bfloat16*)d_in[0];
    const __nv_bfloat16* A_k = (const __nv_bfloat16*)d_in[1];
    const __nv_bfloat16* A_v = (const __nv_bfloat16*)d_in[2];
    const __nv_bfloat16* A_wq = (const __nv_bfloat16*)d_in[3];
    const __nv_bfloat16* A_wo = (const __nv_bfloat16*)d_in[4];
    const __nv_bfloat16* B_wg = (const __nv_bfloat16*)d_in[6];
    const __nv_bfloat16* B_wu = (const __nv_bfloat16*)d_in[7];
    const __nv_bfloat16* B_wd = (const __nv_bfloat16*)d_in[8];
    const __nv_bfloat16* c = (const __nv_bfloat16*)d_in[9];
    const __nv_bfloat16* w_mod = (const __nv_bfloat16*)d_in[10];
    static int grid = 0;
    if (grid == 0) {
        cudaFuncSetAttribute(decode_block_kernel, cudaFuncAttributeMaxDynamicSharedMemorySize, SM_TOTAL);
        int dev = 0, sms = 0;
        cudaGetDevice(&dev);
        cudaDeviceGetAttribute(&sms, cudaDevAttrMultiProcessorCount, dev);
        grid = sms < 132 ? sms : 132;
    }
    decode_block_kernel<<<grid, NTHREADS, SM_TOTAL>>>(A_x, A_k, A_v, A_wq, A_wo, B_wg, B_wu, B_wd, c, w_mod,
                                                      (__nv_bfloat16*)d_out);
}
```

```cpp
#include <cuda_runtime.h>
#include <cuda_bf16.h>
#include <stdint.h>

namespace {

constexpr int NB = 4;
constexpr int DM = 640;
constexpr int NH = 32;
constexpr int SK = 4096;
constexpr int DH = 192;
constexpr int FF = 1536;
constexpr int MODN = 6 * DM;
constexpr int QN = NH * DH;
constexpr int NBH = NB * NH;

constexpr int NCONS = 256;
constexpr int NTHREADS = NCONS + 32;
constexpr int TILE_KEYS = 32;
constexpr int TILE_BYTES = TILE_KEYS * DH * 2;
constexpr int NST = 12;
constexpr int PRE = 6;
constexpr int TPI = 4;
constexpr int ITEM_KEYS = TPI * TILE_KEYS;
constexpr int CHUNKS = SK / ITEM_KEYS;
constexpr int NITEM_K = NBH * CHUNKS;
constexpr int NITEM = 2 * NITEM_K;

constexpr int A_PITCH = 1296;
constexpr int WIDE_PITCH = 1296;
constexpr int P32 = 80;
constexpr int P48 = 112;

constexpr int SM_RING = 0;
constexpr int SM_WQ = PRE * TILE_BYTES;
constexpr int SM_WO = 0;
constexpr int SM_WD = SM_WO + 48 * WIDE_PITCH;
constexpr int SM_W32 = NST * TILE_BYTES;
constexpr int SM_A = SM_W32 + DM * P32;
constexpr int SM_PART = SM_A + NB * A_PITCH;
constexpr int SM_XP = SM_PART + 8 * 4 * 80 * 4;
constexpr int SM_ITEM = SM_XP + NB * DM * 4;
constexpr int SM_TAG = SM_ITEM + 16 * 4;
constexpr int SM_BAR = SM_TAG + 16 * 4;
constexpr int SM_TOTAL = SM_BAR + (2 * NST + 1) * 8;
static_assert(SM_WQ + DM * P48 <= NST * TILE_BYTES, "prologue overlay");
static_assert(SM_WD + 16 * WIDE_PITCH <= NST * TILE_BYTES, "tail overlay");
static_assert(SM_TOTAL <= 232448, "smem");

__device__ __align__(128) float g_mod[NB * MODN];
__device__ __align__(128) __nv_bfloat16 g_q[NB * QN];
__device__ __align__(128) float g_s[NBH * SK];
__device__ __align__(128) float2 g_stat[NBH * CHUNKS];
__device__ __align__(128) float2 g_hstat[NBH];
__device__ __align__(128) unsigned int g_kcnt[NBH];
__device__ __align__(128) unsigned int g_hready[NBH];
__device__ __align__(128) float g_o[NB * QN];
__device__ __align__(128) float g_attn[NB * DM];
__device__ __align__(128) float g_ffn[NB * DM];
__device__ __align__(128) unsigned int g_bar[8];
__device__ unsigned int g_work;

#define PROF(k) do { } while (0)
#define PROFP(k) do { } while (0)

__device__ __forceinline__ float bf16r(float x) { return __bfloat162float(__float2bfloat16_rn(x)); }
__device__ __forceinline__ float bf_lo(uint32_t u) { return __uint_as_float(u << 16); }
__device__ __forceinline__ float bf_hi(uint32_t u) { return __uint_as_float(u & 0xffff0000u); }

__device__ __forceinline__ uint32_t smem_u32(const void* p) { return (uint32_t)__cvta_generic_to_shared(p); }
__device__ __forceinline__ void mbar_init(uint32_t bar, uint32_t count) {
    asm volatile("mbarrier.init.shared::cta.b64 [%0], %1;" ::"r"(bar), "r"(count) : "memory");
}
__device__ __forceinline__ void mbar_expect_tx(uint32_t bar, uint32_t bytes) {
    asm volatile("mbarrier.arrive.expect_tx.shared::cta.b64 _, [%0], %1;" ::"r"(bar), "r"(bytes) : "memory");
}
__device__ __forceinline__ void mbar_arrive(uint32_t bar) {
    asm volatile("mbarrier.arrive.shared::cta.b64 _, [%0];" ::"r"(bar) : "memory");
}
constexpr long long WAIT_LIMIT_CYCLES = 200000000LL;
__device__ __forceinline__ uint32_t mbar_try(uint32_t bar, uint32_t parity) {
    uint32_t done;
    asm volatile(
        "{\n\t.reg .pred p;\n\t"
        "mbarrier.try_wait.parity.shared::cta.b64 p, [%1], %2;\n\t"
        "selp.u32 %0, 1, 0, p;\n\t}"
        : "=r"(done) : "r"(bar), "r"(parity) : "memory");
    return done;
}
__device__ __noinline__ void mbar_wait_slow(uint32_t bar, uint32_t parity) {
    const long long t0 = clock64();
    while (!mbar_try(bar, parity)) {
        if (clock64() - t0 > WAIT_LIMIT_CYCLES) __trap();
    }
}
__device__ __forceinline__ void mbar_wait(uint32_t bar, uint32_t parity) {
    if (!mbar_try(bar, parity)) mbar_wait_slow(bar, parity);
}
__device__ __noinline__ void tag_wait_slow(volatile int* tag, int u) {
    const long long t0 = clock64();
    while (*tag != u) {
        __nanosleep(32);
        if (clock64() - t0 > WAIT_LIMIT_CYCLES) __trap();
    }
}
__device__ __forceinline__ void stage_wait(uint32_t bar_full, volatile int* s_tag, int u) {
    const int st = u % NST;
    if (s_tag[st] != u) tag_wait_slow(s_tag + st, u);
    mbar_wait(bar_full + st * 8, (u / NST) & 1);
}
__device__ __forceinline__ void bulk_g2s(uint32_t dst, const void* src, uint32_t bytes, uint32_t bar) {
    asm volatile(
        "cp.async.bulk.shared::cluster.global.mbarrier::complete_tx::bytes [%0], [%1], %2, [%3];"
        ::"r"(dst), "l"(src), "r"(bytes), "r"(bar) : "memory");
}
__device__ __forceinline__ void cp_async16(uint32_t dst, const void* src) {
    asm volatile("cp.async.cg.shared.global [%0], [%1], 16;" ::"r"(dst), "l"(src) : "memory");
}
__device__ __forceinline__ void cp_async_wait_all() { asm volatile("cp.async.wait_all;" ::: "memory"); }
__device__ __forceinline__ void cons_sync() { asm volatile("bar.sync 1, 256;" ::: "memory"); }

__device__ __forceinline__ void red_add_v4(float* p, float a, float b, float c, float d) {
    asm volatile("red.global.add.v4.f32 [%0], {%1, %2, %3, %4};" ::"l"(p), "f"(a), "f"(b), "f"(c), "f"(d) : "memory");
}
__device__ __forceinline__ unsigned int ld_acquire(const unsigned int* p) {
    unsigned int v;
    asm volatile("ld.acquire.gpu.global.u32 %0, [%1];" : "=r"(v) : "l"(p) : "memory");
    return v;
}
__device__ __forceinline__ void st_release(unsigned int* p, unsigned int v) {
    asm volatile("st.release.gpu.global.u32 [%0], %1;" ::"l"(p), "r"(v) : "memory");
}

__device__ __noinline__ void grid_barrier(unsigned int* ctr, int tid) {
    cons_sync();
    if (tid == 0) {
        const unsigned int n = gridDim.x;
        __threadfence();
        const unsigned int old = atomicAdd(ctr, 1u);
        const unsigned int target = (old / n + 1u) * n;
        const long long t0 = clock64();
        while ((int)(ld_acquire(ctr) - target) < 0) {
            if (clock64() - t0 > WAIT_LIMIT_CYCLES) __trap();
        }
        __threadfence();
    }
    cons_sync();
}

__device__ __forceinline__ float warp_sum(float v) {
#pragma unroll
    for (int o = 16; o > 0; o >>= 1) v += __shfl_xor_sync(0xffffffffu, v, o);
    return v;
}
__device__ __forceinline__ float warp_max(float v) {
#pragma unroll
    for (int o = 16; o > 0; o >>= 1) v = fmaxf(v, __shfl_xor_sync(0xffffffffu, v, o));
    return v;
}

__device__ __forceinline__ void fma8(float (&acc)[8], const uint4& w, float s) {
    acc[0] = fmaf(s, bf_lo(w.x), acc[0]);
    acc[1] = fmaf(s, bf_hi(w.x), acc[1]);
    acc[2] = fmaf(s, bf_lo(w.y), acc[2]);
    acc[3] = fmaf(s, bf_hi(w.y), acc[3]);
    acc[4] = fmaf(s, bf_lo(w.z), acc[4]);
    acc[5] = fmaf(s, bf_hi(w.z), acc[5]);
    acc[6] = fmaf(s, bf_lo(w.w), acc[6]);
    acc[7] = fmaf(s, bf_hi(w.w), acc[7]);
}
__device__ __forceinline__ float dot8(const uint4& w, const float* q) {
    float s = q[0] * bf_lo(w.x);
    s = fmaf(q[1], bf_hi(w.x), s);
    s = fmaf(q[2], bf_lo(w.y), s);
    s = fmaf(q[3], bf_hi(w.y), s);
    s = fmaf(q[4], bf_lo(w.z), s);
    s = fmaf(q[5], bf_hi(w.z), s);
    s = fmaf(q[6], bf_lo(w.w), s);
    s = fmaf(q[7], bf_hi(w.w), s);
    return s;
}

__device__ __noinline__ void stage_rows(uint32_t dst, int dst_pitch, const void* src, int src_stride, int rows,
                                        int cpr, int tid) {
    const int n = rows * cpr;
#pragma unroll 1
    for (int i = tid; i < n; i += NCONS) {
        const int r = i / cpr, c = i - r * cpr;
        cp_async16(dst + r * dst_pitch + c * 16, (const unsigned char*)src + (size_t)r * src_stride + c * 16);
    }
}

__device__ __noinline__ void gemv_mma(uint32_t w, int w_pitch, uint32_t a, int ksteps, int ntiles, float* part,
                                      int lane) {
    float c[10][4];
#pragma unroll
    for (int nt = 0; nt < 10; ++nt) { c[nt][0] = 0.f; c[nt][1] = 0.f; c[nt][2] = 0.f; c[nt][3] = 0.f; }
    uint32_t ap = a + (lane >> 2) * A_PITCH + (lane & 3) * 4;
    uint32_t wp = w + (lane & 15) * w_pitch;
    for (int ks = 0; ks < ksteps; ++ks) {
        uint32_t a0 = 0, a2 = 0;
        if (lane < 16) {
            asm volatile("ld.shared.u32 %0, [%1];" : "=r"(a0) : "r"(ap));
            asm volatile("ld.shared.u32 %0, [%1];" : "=r"(a2) : "r"(ap + 16));
        }
#pragma unroll
        for (int nt = 0; nt < 10; ++nt) {
            if (nt < ntiles) {
                uint32_t b0, b1;
                asm volatile("ldmatrix.sync.aligned.m8n8.x2.trans.shared.b16 {%0, %1}, [%2];"
                             : "=r"(b0), "=r"(b1) : "r"(wp + nt * 16));
                asm volatile(
                    "mma.sync.aligned.m16n8k16.row.col.f32.bf16.bf16.f32 {%0, %1, %2, %3}, {%4, %5, %6, %7}, "
                    "{%8, %9}, {%0, %1, %2, %3};"
                    : "+f"(c[nt][0]), "+f"(c[nt][1]), "+f"(c[nt][2]), "+f"(c[nt][3])
                    : "r"(a0), "r"(0u), "r"(a2), "r"(0u), "r"(b0), "r"(b1));
            }
        }
        ap += 32;
        wp += 16 * w_pitch;
    }
    if (lane < 16) {
        float* pp = part + (lane >> 2) * 80 + (lane & 3) * 2;
#pragma unroll
        for (int nt = 0; nt < 10; ++nt)
            if (nt < ntiles) *(float2*)(pp + nt * 8) = make_float2(c[nt][0], c[nt][1]);
    }
}

__device__ __forceinline__ float tall_sum(const float* part, int b, int n) {
    float s = 0.f;
#pragma unroll
    for (int w = 0; w < 8; ++w) s += part[(w * 4 + b) * 80 + n];
    return s;
}

__device__ __noinline__ void wide_flush(const float* part, float* dst, int tid) {
#pragma unroll 1
    for (int i = tid; i < NB * DM / 4; i += NCONS) {
        const int b = i / 160, col = (i - b * 160) * 4;
        const int w = col / 80, n = col - w * 80;
        const float4 v = *(const float4*)(part + (w * 4 + b) * 80 + n);
        red_add_v4(dst + b * DM + col, v.x, v.y, v.z, v.w);
    }
}

__device__ __noinline__ void ln_mod_row(const float* xs, const float* attn, const float* gate, const float* shift,
                                        const float* scale, __nv_bfloat16* out, int lane) {
    float4 xv[5], sh[5], sc[5];
#pragma unroll
    for (int i = 0; i < 5; ++i) {
        sh[i] = __ldcg((const float4*)shift + lane + 32 * i);
        sc[i] = __ldcg((const float4*)scale + lane + 32 * i);
        xv[i] = *((const float4*)xs + lane + 32 * i);
    }
    if (attn != nullptr) {
        float4 av[5], gv[5];
#pragma unroll
        for (int i = 0; i < 5; ++i) {
            av[i] = __ldcg((const float4*)attn + lane + 32 * i);
            gv[i] = __ldcg((const float4*)gate + lane + 32 * i);
        }
#pragma unroll
        for (int i = 0; i < 5; ++i) {
            xv[i].x = bf16r(xv[i].x + bf16r(gv[i].x * bf16r(av[i].x)));
            xv[i].y = bf16r(xv[i].y + bf16r(gv[i].y * bf16r(av[i].y)));
            xv[i].z = bf16r(xv[i].z + bf16r(gv[i].z * bf16r(av[i].z)));
            xv[i].w = bf16r(xv[i].w + bf16r(gv[i].w * bf16r(av[i].w)));
        }
    }
    float s = 0.f;
#pragma unroll
    for (int i = 0; i < 5; ++i) s += (xv[i].x + xv[i].y) + (xv[i].z + xv[i].w);
    s = warp_sum(s);
    const float mean_f = s * (1.0f / DM);
    float v = 0.f;
#pragma unroll
    for (int i = 0; i < 5; ++i) {
        float d;
        d = xv[i].x - mean_f; v = fmaf(d, d, v);
        d = xv[i].y - mean_f; v = fmaf(d, d, v);
        d = xv[i].z - mean_f; v = fmaf(d, d, v);
        d = xv[i].w - mean_f; v = fmaf(d, d, v);
    }
    v = warp_sum(v);
    const float mean = bf16r(mean_f);
    const float den = bf16r(sqrtf(bf16r(bf16r(v * (1.0f / DM)) + 1e-5f)));
#pragma unroll
    for (int i = 0; i < 5; ++i) {
        const float h0 = bf16r(bf16r(__fdiv_rn(bf16r(xv[i].x - mean), den)) * bf16r(1.0f + sc[i].x)) + sh[i].x;
        const float h1 = bf16r(bf16r(__fdiv_rn(bf16r(xv[i].y - mean), den)) * bf16r(1.0f + sc[i].y)) + sh[i].y;
        const float h2 = bf16r(bf16r(__fdiv_rn(bf16r(xv[i].z - mean), den)) * bf16r(1.0f + sc[i].z)) + sh[i].z;
        const float h3 = bf16r(bf16r(__fdiv_rn(bf16r(xv[i].w - mean), den)) * bf16r(1.0f + sc[i].w)) + sh[i].w;
        __nv_bfloat162 p0 = __floats2bfloat162_rn(h0, h1), p1 = __floats2bfloat162_rn(h2, h3);
        uint2 u;
        u.x = *(uint32_t*)&p0; u.y = *(uint32_t*)&p1;
        *((uint2*)out + lane + 32 * i) = u;
    }
}

__device__ __forceinline__ float gelu_tanh(float x) {
    const float kBeta = 0.7978845608028654f;
    const float inner = kBeta * (x + 0.044715f * x * x * x);
    return 0.5f * x * (1.0f + tanhf(inner));
}

__global__ void __launch_bounds__(NTHREADS, 1)
decode_block_kernel(const __nv_bfloat16* __restrict__ x_in, const __nv_bfloat16* __restrict__ k_cache,
                    const __nv_bfloat16* __restrict__ v_cache, const __nv_bfloat16* __restrict__ wq,
                    const __nv_bfloat16* __restrict__ wo, const __nv_bfloat16* __restrict__ w_gate,
                    const __nv_bfloat16* __restrict__ w_up, const __nv_bfloat16* __restrict__ w_down,
                    const __nv_bfloat16* __restrict__ cvec, const __nv_bfloat16* __restrict__ w_mod,
                    __nv_bfloat16* __restrict__ out) {
    extern __shared__ __align__(128) unsigned char smem[];
    const int tid = threadIdx.x;
    const int cta = blockIdx.x;

    const uint32_t sbase = smem_u32(smem);
    const uint32_t bar_full = sbase + SM_BAR;
    const uint32_t bar_empty = bar_full + NST * 8;
    volatile int* s_item = (volatile int*)(smem + SM_ITEM);
    volatile int* s_tag = (volatile int*)(smem + SM_TAG);

    const uint32_t bar_tail = bar_empty + NST * 8;
    if (tid < NST) s_tag[tid] = -1;
    if (tid == 0) {
#pragma unroll 1
        for (int s = 0; s < 2 * NST + 1; ++s) mbar_init(bar_full + s * 8, 1);
        asm volatile("fence.mbarrier_init.release.cluster;" ::: "memory");
        asm volatile("fence.proxy.async.shared::cta;" ::: "memory");
#pragma unroll 1
        for (int s = 0; s < PRE; ++s) mbar_arrive(bar_empty + s * 8);
    }
    __syncthreads();

    if (tid >= NCONS) {
        if (tid == NCONS) {
            int item = cta;
            int u = 0;
            bool pf = false;
            while (item < NITEM) {
                const int next = (int)atomicAdd(&g_work, 1u) + (int)gridDim.x;
                const unsigned char* src = (const unsigned char*)(item < NITEM_K ? k_cache : v_cache) +
                                           (size_t)(item & (NITEM_K - 1)) * (ITEM_KEYS * DH * 2);
#pragma unroll 1
                for (int t = 0; t < TPI; ++t, ++u) {
                    const int st = u % NST;
                    mbar_wait(bar_empty + st * 8, (u / NST) & 1);
                    s_item[st] = item;
                    s_tag[st] = u;
                    mbar_expect_tx(bar_full + st * 8, TILE_BYTES);
                    bulk_g2s(sbase + SM_RING + st * TILE_BYTES, src + t * TILE_BYTES, TILE_BYTES, bar_full + st * 8);
                }
                if (!pf && next >= NITEM - 8 * (int)gridDim.x) {
                    pf = true;
                    if (cta < QN / 48)
                        asm volatile("cp.async.bulk.prefetch.L2.global [%0], %1;" ::"l"(wo + (size_t)cta * 48 * DM), "r"(48 * DM * 2) : "memory");
                    if (cta < FF / 16)
                        asm volatile("cp.async.bulk.prefetch.L2.global [%0], %1;" ::"l"(w_down + (size_t)cta * 16 * DM), "r"(16 * DM * 2) : "memory");
                }
                item = next;
            }
#pragma unroll 1
            for (int j = 0; j < 8; ++j, u += TPI) {
                const int st = u % NST;
                mbar_wait(bar_empty + st * 8, (u / NST) & 1);
                s_item[st] = -1;
                s_tag[st] = u;
                mbar_arrive(bar_full + st * 8);
            }
            PROFP(13);
        }
        return;
    }

    const int lane = tid & 31, warp = tid >> 5;
    float* s_part = (float*)(smem + SM_PART);
    float* s_xp = (float*)(smem + SM_XP);
    __nv_bfloat16* s_a = (__nv_bfloat16*)(smem + SM_A);

    PROF(0);
    {
        const int i1 = tid + NCONS;
        const uint4 c0 = __ldg((const uint4*)cvec + tid), x0 = __ldg((const uint4*)x_in + tid);
        uint4 c1 = c0, x1 = x0;
        if (i1 < 320) { c1 = __ldg((const uint4*)cvec + i1); x1 = __ldg((const uint4*)x_in + i1); }
        if (cta < MODN / 32) stage_rows(sbase + SM_W32, P32, w_mod + cta * 32, MODN * 2, DM, 4, tid);
        if (cta < QN / 48) stage_rows(sbase + SM_WQ, P48, wq + cta * 48, QN * 2, DM, 6, tid);
#pragma unroll 1
        for (int r = 0; r < 2; ++r) {
            const int i = r ? i1 : tid;
            if (i < 320) {
                const uint4 cc = r ? c1 : c0, xx = r ? x1 : x0;
                const uint32_t cw[4] = {cc.x, cc.y, cc.z, cc.w}, xw[4] = {xx.x, xx.y, xx.z, xx.w};
                uint32_t ow[4];
#pragma unroll
                for (int k = 0; k < 4; ++k) {
                    const float a = bf_lo(cw[k]), b = bf_hi(cw[k]);
                    __nv_bfloat162 p = __floats2bfloat162_rn(__fdiv_rn(a, 1.0f + __expf(-a)), __fdiv_rn(b, 1.0f + __expf(-b)));
                    ow[k] = *(uint32_t*)&p;
                    s_xp[i * 8 + 2 * k] = bf_lo(xw[k]);
                    s_xp[i * 8 + 2 * k + 1] = bf_hi(xw[k]);
                }
                const int b = i / 80, c8 = i - b * 80;
                *(uint4*)(smem + SM_A + b * A_PITCH + c8 * 16) = make_uint4(ow[0], ow[1], ow[2], ow[3]);
            }
        }
    }
    if (cta == gridDim.x - 1) {
#pragma unroll 1
        for (int i = tid; i < NB * QN / 4; i += NCONS) ((float4*)g_o)[i] = make_float4(0.f, 0.f, 0.f, 0.f);
#pragma unroll 1
        for (int i = tid; i < NB * DM; i += NCONS) { g_attn[i] = 0.f; g_ffn[i] = 0.f; }
        if (tid < NBH) { g_kcnt[tid] = 0u; g_hready[tid] = 0u; }
    }
    cp_async_wait_all();
    cons_sync();
    if (cta < MODN / 32) {
        gemv_mma(sbase + SM_W32 + warp * 80 * P32, P32, sbase + SM_A + warp * 160, 5, 4, s_part + warp * 320, lane);
        cons_sync();
        if (tid < 128) g_mod[(tid >> 5) * MODN + cta * 32 + (tid & 31)] = bf16r(tall_sum(s_part, tid >> 5, tid & 31));
    }
    PROF(1);
    grid_barrier(&g_bar[0], tid);
    PROF(2);

    if (cta < QN / 48) {
        if (warp < NB)
            ln_mod_row(s_xp + warp * DM, nullptr, nullptr, g_mod + warp * MODN, g_mod + warp * MODN + DM,
                       s_a + warp * (A_PITCH / 2), lane);
        cons_sync();
        gemv_mma(sbase + SM_WQ + warp * 80 * P48, P48, sbase + SM_A + warp * 160, 5, 6, s_part + warp * 320, lane);
        cons_sync();
        if (tid < 192) {
            const int b = tid / 48, n = tid - b * 48;
            g_q[b * QN + cta * 48 + n] = __float2bfloat16_rn(tall_sum(s_part, b, n));
        }
    }
    PROF(3);
    grid_barrier(&g_bar[1], tid);
    if (tid == 0) {
#pragma unroll 1
        for (int s = PRE; s < NST; ++s) mbar_arrive(bar_empty + s * 8);
    }
    if (cta < FF / 16) {
        stage_rows(sbase + SM_W32, P32, w_gate + cta * 16, FF * 2, DM, 2, tid);
        stage_rows(sbase + SM_W32 + 32, P32, w_up + cta * 16, FF * 2, DM, 2, tid);
    }
    PROF(4);

    {
        const int sub = lane & 7, grp = lane >> 3;
        for (int u0 = warp * TPI;; u0 += 8 * TPI) {
            stage_wait(bar_full, s_tag, u0);
            const int item = s_item[u0 % NST];
            if (item < 0) {
                __syncwarp();
                if (lane == 0) mbar_arrive(bar_empty + (u0 % NST) * 8);
                break;
            }
            const int bh = (item & (NITEM_K - 1)) / CHUNKS;
            float* gs = g_s + (size_t)(item & (NITEM_K - 1)) * ITEM_KEYS;
            if (item < NITEM_K) {
                float qr[24];
                {
                    const uint4* qp = (const uint4*)(g_q + (bh >> 5) * QN + (bh & 31) * DH) + sub;
#pragma unroll
                    for (int j = 0; j < 3; ++j) {
                        const uint4 v = __ldcg(qp + 8 * j);
                        qr[j * 8 + 0] = bf_lo(v.x); qr[j * 8 + 1] = bf_hi(v.x);
                        qr[j * 8 + 2] = bf_lo(v.y); qr[j * 8 + 3] = bf_hi(v.y);
                        qr[j * 8 + 4] = bf_lo(v.z); qr[j * 8 + 5] = bf_hi(v.z);
                        qr[j * 8 + 6] = bf_lo(v.w); qr[j * 8 + 7] = bf_hi(v.w);
                    }
                }
                float m_run = -INFINITY, l_run = 0.f;
#pragma unroll 1
                for (int t = 0; t < TPI; ++t) {
                    const int u = u0 + t, st = u % NST;
                    stage_wait(bar_full, s_tag, u);
                    const uint4* tile = (const uint4*)(smem + SM_RING + st * TILE_BYTES);
                    float part[8];
#pragma unroll
                    for (int it = 0; it < 8; ++it) {
                        const uint4* row = tile + (it * 4 + grp) * 24 + sub;
                        const uint4 a = row[0], b = row[8], c = row[16];
                        part[it] = dot8(a, qr) + dot8(b, qr + 8) + dot8(c, qr + 16);
                    }
                    __syncwarp();
                    if (lane == 0) mbar_arrive(bar_empty + st * 8);
#pragma unroll
                    for (int j = 0; j < 4; ++j) {
                        const float send = (sub & 4) ? part[j] : part[j + 4];
                        const float keep = (sub & 4) ? part[j + 4] : part[j];
                        part[j] = keep + __shfl_xor_sync(0xffffffffu, send, 4);
                    }
#pragma unroll
                    for (int j = 0; j < 2; ++j) {
                        const float send = (sub & 2) ? part[j] : part[j + 2];
                        const float keep = (sub & 2) ? part[j + 2] : part[j];
                        part[j] = keep + __shfl_xor_sync(0xffffffffu, send, 2);
                    }
                    {
                        const float send = (sub & 1) ? part[0] : part[1];
                        const float keep = (sub & 1) ? part[1] : part[0];
                        part[0] = keep + __shfl_xor_sync(0xffffffffu, send, 1);
                    }
                    const float s = bf16r(bf16r(part[0]) * 0.07216878364870323f);
                    gs[t * TILE_KEYS + sub * 4 + grp] = s;
                    const float m_new = fmaxf(m_run, s);
                    l_run = l_run * __expf(m_run - m_new) + __expf(s - m_new);
                    m_run = m_new;
                }
                const float m = warp_max(m_run);
                const float l = warp_sum(l_run * __expf(m_run - m));
                __syncwarp();
                unsigned int old = 0;
                if (lane == 0) {
                    g_stat[item] = make_float2(m, l);
                    __threadfence();
                    old = atomicAdd(&g_kcnt[bh], 1u);
                    __threadfence();
                }
                old = __shfl_sync(0xffffffffu, old, 0);
                if (old == CHUNKS - 1) {
                    const float2 st2 = __ldcg(&g_stat[bh * CHUNKS + lane]);
                    const float mm = warp_max(st2.x);
                    const float ll = warp_sum(st2.y * __expf(st2.x - mm));
                    if (lane == 0) {
                        g_hstat[bh] = make_float2(mm, ll);
                        st_release(&g_hready[bh], 1u);
                    }
                }
            } else {
                if (ld_acquire(&g_hready[bh]) == 0u) {
                    const long long t0 = clock64();
                    while (ld_acquire(&g_hready[bh]) == 0u)
                        if (clock64() - t0 > WAIT_LIMIT_CYCLES) __trap();
                }
                const float2 hs = __ldcg(&g_hstat[bh]);
                float acc[3][8];
#pragma unroll
                for (int j = 0; j < 3; ++j)
#pragma unroll
                    for (int e = 0; e < 8; ++e) acc[j][e] = 0.f;
#pragma unroll 1
                for (int t = 0; t < TPI; ++t) {
                    const int u = u0 + t, st = u % NST;
                    const float pl = bf16r(__expf(__ldcg(gs + t * TILE_KEYS + lane) - hs.x) / hs.y);
                    stage_wait(bar_full, s_tag, u);
                    const uint4* tile = (const uint4*)(smem + SM_RING + st * TILE_BYTES);
#pragma unroll
                    for (int it = 0; it < 8; ++it) {
                        const uint4* row = tile + (it * 4 + grp) * 24 + sub;
                        const uint4 a = row[0], b = row[8], c = row[16];
                        const float p = __shfl_sync(0xffffffffu, pl, it * 4 + grp);
                        fma8(acc[0], a, p);
                        fma8(acc[1], b, p);
                        fma8(acc[2], c, p);
                    }
                    __syncwarp();
                    if (lane == 0) mbar_arrive(bar_empty + st * 8);
                }
                float* go = g_o + (bh >> 5) * QN + (bh & 31) * DH + sub * 8;
#pragma unroll
                for (int j = 0; j < 3; ++j) {
#pragma unroll
                    for (int e = 0; e < 8; ++e) {
                        float v = acc[j][e];
                        v += __shfl_xor_sync(0xffffffffu, v, 8);
                        v += __shfl_xor_sync(0xffffffffu, v, 16);
                        acc[j][e] = v;
                    }
                    if (grp == 0) {
                        red_add_v4(go + j * 64, acc[j][0], acc[j][1], acc[j][2], acc[j][3]);
                        red_add_v4(go + j * 64 + 4, acc[j][4], acc[j][5], acc[j][6], acc[j][7]);
                    }
                }
            }
        }
    }
    PROF(5);
    cons_sync();
    if (warp == 0) {
        asm volatile("fence.proxy.async.shared::cta;" ::: "memory");
        const int nrows = (cta < QN / 48 ? 48 : 0) + (cta < FF / 16 ? 16 : 0);
        if (lane == 0) mbar_expect_tx(bar_tail, nrows * DM * 2);
        __syncwarp();
#pragma unroll 1
        for (int r = lane; r < nrows; r += 32) {
            const __nv_bfloat16* src = r < 48 ? wo + ((size_t)cta * 48 + r) * DM : w_down + ((size_t)cta * 16 + r - 48) * DM;
            bulk_g2s(sbase + SM_WO + r * WIDE_PITCH, src, DM * 2, bar_tail);
        }
    }
    PROF(6);
    grid_barrier(&g_bar[2], tid);
    PROF(7);

    if (cta < QN / 48) {
        if (tid < 192) {
            const int b = tid / 48, n = tid - b * 48;
            s_a[b * (A_PITCH / 2) + n] = __float2bfloat16_rn(__ldcg(g_o + b * QN + cta * 48 + n));
        }
        mbar_wait(bar_tail, 0);
        cons_sync();
        gemv_mma(sbase + SM_WO + warp * 160, WIDE_PITCH, sbase + SM_A, 3, 10, s_part + warp * 320, lane);
        cons_sync();
        wide_flush(s_part, g_attn, tid);
    }
    PROF(8);
    grid_barrier(&g_bar[3], tid);
    PROF(9);

    if (cta < FF / 16) {
        if (warp < NB)
            ln_mod_row(s_xp + warp * DM, g_attn + warp * DM, g_mod + warp * MODN + 2 * DM, g_mod + warp * MODN + 3 * DM,
                       g_mod + warp * MODN + 4 * DM, s_a + warp * (A_PITCH / 2), lane);
        cp_async_wait_all();
        cons_sync();
        gemv_mma(sbase + SM_W32 + warp * 80 * P32, P32, sbase + SM_A + warp * 160, 5, 4, s_part + warp * 320, lane);
        cons_sync();
        if (tid < 64) {
            const int b = tid >> 4, n = tid & 15;
            const float g = bf16r(tall_sum(s_part, b, n));
            const float up = bf16r(tall_sum(s_part, b, 16 + n));
            s_a[b * (A_PITCH / 2) + n] = __float2bfloat16_rn(bf16r(gelu_tanh(g)) * up);
        }
        cons_sync();
        gemv_mma(sbase + SM_WD + warp * 160, WIDE_PITCH, sbase + SM_A, 1, 10, s_part + warp * 320, lane);
        cons_sync();
        wide_flush(s_part, g_ffn, tid);
    }
    PROF(10);
    cons_sync();
    if (tid == 0) {
        __threadfence();
        const unsigned int old = atomicAdd(&g_bar[4], 1u);
        s_item[0] = ((old % gridDim.x) == gridDim.x - 1) ? 1 : 0;
        __threadfence();
    }
    cons_sync();
    if (s_item[0] != 0) {
        float4 f[3], a[3], ga[3], gb[3];
#pragma unroll
        for (int r = 0; r < 3; ++r) {
            const int i = tid + r * NCONS;
            if (i < NB * DM / 4) {
                const int b = i / 160, c4 = i - b * 160;
                f[r] = __ldcg((const float4*)g_ffn + i);
                a[r] = __ldcg((const float4*)g_attn + i);
                ga[r] = __ldcg((const float4*)(g_mod + b * MODN + 2 * DM) + c4);
                gb[r] = __ldcg((const float4*)(g_mod + b * MODN + 5 * DM) + c4);
            }
        }
#pragma unroll
        for (int r = 0; r < 3; ++r) {
            const int i = tid + r * NCONS;
            if (i < NB * DM / 4) {
                const float4 x = *((const float4*)s_xp + i);
                const float o0 = bf16r(x.x + bf16r(ga[r].x * bf16r(a[r].x))) + bf16r(gb[r].x * bf16r(f[r].x));
                const float o1 = bf16r(x.y + bf16r(ga[r].y * bf16r(a[r].y))) + bf16r(gb[r].y * bf16r(f[r].y));
                const float o2 = bf16r(x.z + bf16r(ga[r].z * bf16r(a[r].z))) + bf16r(gb[r].z * bf16r(f[r].z));
                const float o3 = bf16r(x.w + bf16r(ga[r].w * bf16r(a[r].w))) + bf16r(gb[r].w * bf16r(f[r].w));
                __nv_bfloat162 p0 = __floats2bfloat162_rn(o0, o1), p1 = __floats2bfloat162_rn(o2, o3);
                uint2 u;
                u.x = *(uint32_t*)&p0; u.y = *(uint32_t*)&p1;
                *((uint2*)out + i) = u;
            }
        }
        if (tid == 0) g_work = 0u;
        PROF(11);
    }
}

}

extern "C" void kernel_launch(void* const* d_in, const int* in_sizes, int n_in, void* d_out, int out_size) {
    (void)in_sizes; (void)n_in; (void)out_size;
    const __nv_bfloat16* A_x = (const __nv_bfloat16*)d_in[0];
    const __nv_bfloat16* A_k = (const __nv_bfloat16*)d_in[1];
    const __nv_bfloat16* A_v = (const __nv_bfloat16*)d_in[2];
    const __nv_bfloat16* A_wq = (const __nv_bfloat16*)d_in[3];
    const __nv_bfloat16* A_wo = (const __nv_bfloat16*)d_in[4];
    const __nv_bfloat16* B_wg = (const __nv_bfloat16*)d_in[6];
    const __nv_bfloat16* B_wu = (const __nv_bfloat16*)d_in[7];
    const __nv_bfloat16* B_wd = (const __nv_bfloat16*)d_in[8];
    const __nv_bfloat16* c = (const __nv_bfloat16*)d_in[9];
    const __nv_bfloat16* w_mod = (const __nv_bfloat16*)d_in[10];
    static int grid = 0;
    if (grid == 0) {
        cudaFuncSetAttribute(decode_block_kernel, cudaFuncAttributeMaxDynamicSharedMemorySize, SM_TOTAL);
        int dev = 0, sms = 0;
        cudaGetDevice(&dev);
        cudaDeviceGetAttribute(&sms, cudaDevAttrMultiProcessorCount, dev);
        grid = sms < 132 ? sms : 132;
    }
    decode_block_kernel<<<grid, NTHREADS, SM_TOTAL>>>(A_x, A_k, A_v, A_wq, A_wo, B_wg, B_wu, B_wd, c, w_mod,
                                                      (__nv_bfloat16*)d_out);
}
```

```cpp
#include <cuda_runtime.h>
#include <cuda_bf16.h>
#include <stdint.h>

namespace {

constexpr int NB = 4;
constexpr int DM = 640;
constexpr int NH = 32;
constexpr int SK = 4096;
constexpr int DH = 192;
constexpr int FF = 1536;
constexpr int MODN = 6 * DM;
constexpr int QN = NH * DH;
constexpr int NBH = NB * NH;

constexpr int NCONS = 256;
constexpr int NTHREADS = NCONS + 32;
constexpr int TILE_KEYS = 32;
constexpr int TILE_BYTES = TILE_KEYS * DH * 2;
constexpr int AUX_BYTES = 384;
constexpr int STAGE_BYTES = TILE_BYTES + AUX_BYTES;
constexpr int NST = 12;
constexpr int PRE = 6;
constexpr int TPI = 4;
constexpr int ITEM_KEYS = TPI * TILE_KEYS;
constexpr int CHUNKS = SK / ITEM_KEYS;
constexpr int NITEM_K = NBH * CHUNKS;
constexpr int NITEM = 2 * NITEM_K;

constexpr int A_PITCH = 1296;
constexpr int WIDE_PITCH = 1296;
constexpr int P32 = 80;
constexpr int P48 = 112;

constexpr int SM_RING = 0;
constexpr int SM_WQ = PRE * STAGE_BYTES;
constexpr int SM_WO = 0;
constexpr int SM_WD = SM_WO + 48 * WIDE_PITCH;
constexpr int SM_W32 = NST * STAGE_BYTES;
constexpr int SM_A = SM_W32 + DM * P32;
constexpr int SM_PART = SM_A + NB * A_PITCH;
constexpr int SM_XP = SM_PART + 8 * 4 * 80 * 4;
constexpr int SM_ITEM = SM_XP + NB * DM * 4;
constexpr int SM_TAG = SM_ITEM + 16 * 4;
constexpr int SM_BAR = SM_TAG + 16 * 4;
constexpr int SM_TOTAL = SM_BAR + (2 * NST + 1) * 8;
static_assert(SM_WQ + DM * P48 <= NST * STAGE_BYTES, "prologue overlay");
static_assert(SM_WD + 16 * WIDE_PITCH <= NST * STAGE_BYTES, "tail overlay");
static_assert(SM_TOTAL <= 232448, "smem");

__device__ __align__(128) float g_mod[NB * MODN];
__device__ __align__(128) __nv_bfloat16 g_q[NB * QN];
__device__ __align__(128) float g_s[NBH * SK];
__device__ __align__(128) float2 g_stat[NBH * CHUNKS];
__device__ __align__(128) unsigned int g_kcnt[NBH];
__device__ __align__(128) float g_o[NB * QN];
__device__ __align__(128) float g_attn[NB * DM];
__device__ __align__(128) float g_ffn[NB * DM];
__device__ __align__(128) unsigned int g_bar[8];
__device__ unsigned int g_work;

#define PROF(k) do { } while (0)
#define PROFP(k) do { } while (0)

__device__ __forceinline__ float bf16r(float x) { return __bfloat162float(__float2bfloat16_rn(x)); }
__device__ __forceinline__ float bf_lo(uint32_t u) { return __uint_as_float(u << 16); }
__device__ __forceinline__ float bf_hi(uint32_t u) { return __uint_as_float(u & 0xffff0000u); }

__device__ __forceinline__ uint32_t smem_u32(const void* p) { return (uint32_t)__cvta_generic_to_shared(p); }
__device__ __forceinline__ void mbar_init(uint32_t bar, uint32_t count) {
    asm volatile("mbarrier.init.shared::cta.b64 [%0], %1;" ::"r"(bar), "r"(count) : "memory");
}
__device__ __forceinline__ void mbar_expect_tx(uint32_t bar, uint32_t bytes) {
    asm volatile("mbarrier.arrive.expect_tx.shared::cta.b64 _, [%0], %1;" ::"r"(bar), "r"(bytes) : "memory");
}
__device__ __forceinline__ void mbar_arrive(uint32_t bar) {
    asm volatile("mbarrier.arrive.shared::cta.b64 _, [%0];" ::"r"(bar) : "memory");
}
constexpr long long WAIT_LIMIT_CYCLES = 200000000LL;
__device__ __forceinline__ uint32_t mbar_try(uint32_t bar, uint32_t parity) {
    uint32_t done;
    asm volatile(
        "{\n\t.reg .pred p;\n\t"
        "mbarrier.try_wait.parity.shared::cta.b64 p, [%1], %2;\n\t"
        "selp.u32 %0, 1, 0, p;\n\t}"
        : "=r"(done) : "r"(bar), "r"(parity) : "memory");
    return done;
}
__device__ __noinline__ void mbar_wait_slow(uint32_t bar, uint32_t parity) {
    const long long t0 = clock64();
    while (!mbar_try(bar, parity)) {
        if (clock64() - t0 > WAIT_LIMIT_CYCLES) __trap();
    }
}
__device__ __forceinline__ void mbar_wait(uint32_t bar, uint32_t parity) {
    if (!mbar_try(bar, parity)) mbar_wait_slow(bar, parity);
}
__device__ __noinline__ void tag_wait_slow(volatile int* tag, int u) {
    const long long t0 = clock64();
    while (*tag != u) {
        __nanosleep(32);
        if (clock64() - t0 > WAIT_LIMIT_CYCLES) __trap();
    }
}
__device__ __forceinline__ void stage_wait(uint32_t bar_full, volatile int* s_tag, int u) {
    const int st = u % NST;
    if (s_tag[st] != u) tag_wait_slow(s_tag + st, u);
    mbar_wait(bar_full + st * 8, (u / NST) & 1);
}
__device__ __forceinline__ void bulk_g2s(uint32_t dst, const void* src, uint32_t bytes, uint32_t bar) {
    asm volatile(
        "cp.async.bulk.shared::cluster.global.mbarrier::complete_tx::bytes [%0], [%1], %2, [%3];"
        ::"r"(dst), "l"(src), "r"(bytes), "r"(bar) : "memory");
}
__device__ __forceinline__ void cp_async16(uint32_t dst, const void* src) {
    asm volatile("cp.async.cg.shared.global [%0], [%1], 16;" ::"r"(dst), "l"(src) : "memory");
}
__device__ __forceinline__ void cp_async_wait_all() { asm volatile("cp.async.wait_all;" ::: "memory"); }
__device__ __forceinline__ void cp_async_commit() { asm volatile("cp.async.commit_group;" ::: "memory"); }
__device__ __forceinline__ void cp_async_wait1() { asm volatile("cp.async.wait_group 1;" ::: "memory"); }
__device__ __forceinline__ void red_release_add(unsigned int* p, unsigned int v) {
    asm volatile("red.release.gpu.global.add.u32 [%0], %1;" ::"l"(p), "r"(v) : "memory");
}
__device__ __forceinline__ void cons_sync() { asm volatile("bar.sync 1, 256;" ::: "memory"); }

__device__ __forceinline__ void red_add_v4(float* p, float a, float b, float c, float d) {
    asm volatile("red.global.add.v4.f32 [%0], {%1, %2, %3, %4};" ::"l"(p), "f"(a), "f"(b), "f"(c), "f"(d) : "memory");
}
__device__ __forceinline__ unsigned int ld_acquire(const unsigned int* p) {
    unsigned int v;
    asm volatile("ld.acquire.gpu.global.u32 %0, [%1];" : "=r"(v) : "l"(p) : "memory");
    return v;
}
__device__ __forceinline__ void st_release(unsigned int* p, unsigned int v) {
    asm volatile("st.release.gpu.global.u32 [%0], %1;" ::"l"(p), "r"(v) : "memory");
}

__device__ __noinline__ void grid_barrier(unsigned int* ctr, int tid) {
    cons_sync();
    if (tid == 0) {
        const unsigned int n = gridDim.x;
        __threadfence();
        const unsigned int old = atomicAdd(ctr, 1u);
        const unsigned int target = (old / n + 1u) * n;
        const long long t0 = clock64();
        while ((int)(ld_acquire(ctr) - target) < 0) {
            if (clock64() - t0 > WAIT_LIMIT_CYCLES) __trap();
        }
        __threadfence();
    }
    cons_sync();
}

__device__ __forceinline__ float warp_sum(float v) {
#pragma unroll
    for (int o = 16; o > 0; o >>= 1) v += __shfl_xor_sync(0xffffffffu, v, o);
    return v;
}
__device__ __forceinline__ float warp_max(float v) {
#pragma unroll
    for (int o = 16; o > 0; o >>= 1) v = fmaxf(v, __shfl_xor_sync(0xffffffffu, v, o));
    return v;
}

__device__ __forceinline__ void fma8(float (&acc)[8], const uint4& w, float s) {
    acc[0] = fmaf(s, bf_lo(w.x), acc[0]);
    acc[1] = fmaf(s, bf_hi(w.x), acc[1]);
    acc[2] = fmaf(s, bf_lo(w.y), acc[2]);
    acc[3] = fmaf(s, bf_hi(w.y), acc[3]);
    acc[4] = fmaf(s, bf_lo(w.z), acc[4]);
    acc[5] = fmaf(s, bf_hi(w.z), acc[5]);
    acc[6] = fmaf(s, bf_lo(w.w), acc[6]);
    acc[7] = fmaf(s, bf_hi(w.w), acc[7]);
}
__device__ __forceinline__ float dot8(const uint4& w, const float* q) {
    float s = q[0] * bf_lo(w.x);
    s = fmaf(q[1], bf_hi(w.x), s);
    s = fmaf(q[2], bf_lo(w.y), s);
    s = fmaf(q[3], bf_hi(w.y), s);
    s = fmaf(q[4], bf_lo(w.z), s);
    s = fmaf(q[5], bf_hi(w.z), s);
    s = fmaf(q[6], bf_lo(w.w), s);
    s = fmaf(q[7], bf_hi(w.w), s);
    return s;
}

__device__ __noinline__ void stage_rows(uint32_t dst, int dst_pitch, const void* src, int src_stride, int rows,
                                        int cpr, int tid) {
    const int n = rows * cpr;
#pragma unroll 1
    for (int i = tid; i < n; i += NCONS) {
        const int r = i / cpr, c = i - r * cpr;
        cp_async16(dst + r * dst_pitch + c * 16, (const unsigned char*)src + (size_t)r * src_stride + c * 16);
    }
}

__device__ __noinline__ void gemv_mma(uint32_t w, int w_pitch, uint32_t a, int ksteps, int ntiles, float* part,
                                      int lane) {
    float c[10][4];
#pragma unroll
    for (int nt = 0; nt < 10; ++nt) { c[nt][0] = 0.f; c[nt][1] = 0.f; c[nt][2] = 0.f; c[nt][3] = 0.f; }
    uint32_t ap = a + (lane >> 2) * A_PITCH + (lane & 3) * 4;
    uint32_t wp = w + (lane & 15) * w_pitch;
    for (int ks = 0; ks < ksteps; ++ks) {
        uint32_t a0 = 0, a2 = 0;
        if (lane < 16) {
            asm volatile("ld.shared.u32 %0, [%1];" : "=r"(a0) : "r"(ap));
            asm volatile("ld.shared.u32 %0, [%1];" : "=r"(a2) : "r"(ap + 16));
        }
#pragma unroll
        for (int nt = 0; nt < 10; ++nt) {
            if (nt < ntiles) {
                uint32_t b0, b1;
                asm volatile("ldmatrix.sync.aligned.m8n8.x2.trans.shared.b16 {%0, %1}, [%2];"
                             : "=r"(b0), "=r"(b1) : "r"(wp + nt * 16));
                asm volatile(
                    "mma.sync.aligned.m16n8k16.row.col.f32.bf16.bf16.f32 {%0, %1, %2, %3}, {%4, %5, %6, %7}, "
                    "{%8, %9}, {%0, %1, %2, %3};"
                    : "+f"(c[nt][0]), "+f"(c[nt][1]), "+f"(c[nt][2]), "+f"(c[nt][3])
                    : "r"(a0), "r"(0u), "r"(a2), "r"(0u), "r"(b0), "r"(b1));
            }
        }
        ap += 32;
        wp += 16 * w_pitch;
    }
    if (lane < 16) {
        float* pp = part + (lane >> 2) * 80 + (lane & 3) * 2;
#pragma unroll
        for (int nt = 0; nt < 10; ++nt)
            if (nt < ntiles) *(float2*)(pp + nt * 8) = make_float2(c[nt][0], c[nt][1]);
    }
}

__device__ __forceinline__ float tall_sum(const float* part, int b, int n) {
    float s = 0.f;
#pragma unroll
    for (int w = 0; w < 8; ++w) s += part[(w * 4 + b) * 80 + n];
    return s;
}

__device__ __noinline__ void wide_flush(const float* part, float* dst, int tid) {
#pragma unroll 1
    for (int i = tid; i < NB * DM / 4; i += NCONS) {
        const int b = i / 160, col = (i - b * 160) * 4;
        const int w = col / 80, n = col - w * 80;
        const float4 v = *(const float4*)(part + (w * 4 + b) * 80 + n);
        red_add_v4(dst + b * DM + col, v.x, v.y, v.z, v.w);
    }
}

__device__ __noinline__ void ln_mod_row(const float* xs, const float* attn, const float* gate, const float* shift,
                                        const float* scale, __nv_bfloat16* out, int lane) {
    float4 xv[5], sh[5], sc[5];
#pragma unroll
    for (int i = 0; i < 5; ++i) {
        sh[i] = __ldcg((const float4*)shift + lane + 32 * i);
        sc[i] = __ldcg((const float4*)scale + lane + 32 * i);
        xv[i] = *((const float4*)xs + lane + 32 * i);
    }
    if (attn != nullptr) {
        float4 av[5], gv[5];
#pragma unroll
        for (int i = 0; i < 5; ++i) {
            av[i] = __ldcg((const float4*)attn + lane + 32 * i);
            gv[i] = __ldcg((const float4*)gate + lane + 32 * i);
        }
#pragma unroll
        for (int i = 0; i < 5; ++i) {
            xv[i].x = bf16r(xv[i].x + bf16r(gv[i].x * bf16r(av[i].x)));
            xv[i].y = bf16r(xv[i].y + bf16r(gv[i].y * bf16r(av[i].y)));
            xv[i].z = bf16r(xv[i].z + bf16r(gv[i].z * bf16r(av[i].z)));
            xv[i].w = bf16r(xv[i].w + bf16r(gv[i].w * bf16r(av[i].w)));
        }
    }
    float s = 0.f;
#pragma unroll
    for (int i = 0; i < 5; ++i) s += (xv[i].x + xv[i].y) + (xv[i].z + xv[i].w);
    s = warp_sum(s);
    const float mean_f = s * (1.0f / DM);
    float v = 0.f;
#pragma unroll
    for (int i = 0; i < 5; ++i) {
        float d;
        d = xv[i].x - mean_f; v = fmaf(d, d, v);
        d = xv[i].y - mean_f; v = fmaf(d, d, v);
        d = xv[i].z - mean_f; v = fmaf(d, d, v);
        d = xv[i].w - mean_f; v = fmaf(d, d, v);
    }
    v = warp_sum(v);
    const float mean = bf16r(mean_f);
    const float den = bf16r(sqrtf(bf16r(bf16r(v * (1.0f / DM)) + 1e-5f)));
#pragma unroll
    for (int i = 0; i < 5; ++i) {
        const float h0 = bf16r(bf16r(__fdiv_rn(bf16r(xv[i].x - mean), den)) * bf16r(1.0f + sc[i].x)) + sh[i].x;
        const float h1 = bf16r(bf16r(__fdiv_rn(bf16r(xv[i].y - mean), den)) * bf16r(1.0f + sc[i].y)) + sh[i].y;
        const float h2 = bf16r(bf16r(__fdiv_rn(bf16r(xv[i].z - mean), den)) * bf16r(1.0f + sc[i].z)) + sh[i].z;
        const float h3 = bf16r(bf16r(__fdiv_rn(bf16r(xv[i].w - mean), den)) * bf16r(1.0f + sc[i].w)) + sh[i].w;
        __nv_bfloat162 p0 = __floats2bfloat162_rn(h0, h1), p1 = __floats2bfloat162_rn(h2, h3);
        uint2 u;
        u.x = *(uint32_t*)&p0; u.y = *(uint32_t*)&p1;
        *((uint2*)out + lane + 32 * i) = u;
    }
}

__device__ __forceinline__ float gelu_tanh(float x) {
    const float kBeta = 0.7978845608028654f;
    const float inner = kBeta * (x + 0.044715f * x * x * x);
    return 0.5f * x * (1.0f + tanhf(inner));
}

__global__ void __launch_bounds__(NTHREADS, 1)
decode_block_kernel(const __nv_bfloat16* __restrict__ x_in, const __nv_bfloat16* __restrict__ k_cache,
                    const __nv_bfloat16* __restrict__ v_cache, const __nv_bfloat16* __restrict__ wq,
                    const __nv_bfloat16* __restrict__ wo, const __nv_bfloat16* __restrict__ w_gate,
                    const __nv_bfloat16* __restrict__ w_up, const __nv_bfloat16* __restrict__ w_down,
                    const __nv_bfloat16* __restrict__ cvec, const __nv_bfloat16* __restrict__ w_mod,
                    __nv_bfloat16* __restrict__ out) {
    extern __shared__ __align__(128) unsigned char smem[];
    const int tid = threadIdx.x;
    const int cta = blockIdx.x;

    const uint32_t sbase = smem_u32(smem);
    const uint32_t bar_full = sbase + SM_BAR;
    const uint32_t bar_empty = bar_full + NST * 8;
    volatile int* s_item = (volatile int*)(smem + SM_ITEM);
    volatile int* s_tag = (volatile int*)(smem + SM_TAG);

    const uint32_t bar_tail = bar_empty + NST * 8;
    if (tid < NST) s_tag[tid] = -1;
    if (tid == 0) {
#pragma unroll 1
        for (int s = 0; s < 2 * NST + 1; ++s) mbar_init(bar_full + s * 8, 1);
        asm volatile("fence.mbarrier_init.release.cluster;" ::: "memory");
        asm volatile("fence.proxy.async.shared::cta;" ::: "memory");
#pragma unroll 1
        for (int s = 0; s < PRE; ++s) mbar_arrive(bar_empty + s * 8);
    }
    __syncthreads();

    if (tid >= NCONS) {
        if (tid == NCONS) {
            int item = cta;
            int u = 0;
            bool pf = false;
            while (item < NITEM) {
                const int next = (int)atomicAdd(&g_work, 1u) + (int)gridDim.x;
                const int it = item & (NITEM_K - 1), bh = it / CHUNKS;
                const bool is_v = item >= NITEM_K;
                const unsigned char* src = (const unsigned char*)(is_v ? v_cache : k_cache) + (size_t)it * (ITEM_KEYS * DH * 2);
                if (is_v) {
                    if (ld_acquire(&g_kcnt[bh]) < CHUNKS) {
                        const long long t0 = clock64();
                        while (ld_acquire(&g_kcnt[bh]) < CHUNKS)
                            if (clock64() - t0 > WAIT_LIMIT_CYCLES) __trap();
                    }
                    asm volatile("fence.proxy.async;" ::: "memory");
                }
#pragma unroll 1
                for (int t = 0; t < TPI; ++t, ++u) {
                    const int st = u % NST;
                    const uint32_t dst = sbase + SM_RING + st * STAGE_BYTES, fb = bar_full + st * 8;
                    mbar_wait(bar_empty + st * 8, (u / NST) & 1);
                    if (u == PRE) {
                        asm volatile("fence.proxy.async;" ::: "memory");
#pragma unroll 1
                        for (int e = 0; e < PRE; ++e) {
                            const int ebh = s_item[e] / CHUNKS;
                            bulk_g2s(sbase + SM_RING + e * STAGE_BYTES + TILE_BYTES, g_q + (ebh >> 5) * QN + (ebh & 31) * DH,
                                     AUX_BYTES, bar_full + e * 8);
                        }
                    }
                    s_item[st] = item;
                    s_tag[st] = u;
                    mbar_expect_tx(fb, STAGE_BYTES);
                    bulk_g2s(dst, src + t * TILE_BYTES, TILE_BYTES, fb);
                    if (is_v) {
                        bulk_g2s(dst + TILE_BYTES, g_s + (size_t)it * ITEM_KEYS + t * TILE_KEYS, TILE_KEYS * 4, fb);
                        bulk_g2s(dst + TILE_BYTES + TILE_KEYS * 4, g_stat + bh * CHUNKS, CHUNKS * 8, fb);
                    } else if (u >= PRE) {
                        bulk_g2s(dst + TILE_BYTES, g_q + (bh >> 5) * QN + (bh & 31) * DH, AUX_BYTES, fb);
                    }
                }
                if (!pf && next >= NITEM - 8 * (int)gridDim.x) {
                    pf = true;
                    if (cta < QN / 48)
                        asm volatile("cp.async.bulk.prefetch.L2.global [%0], %1;" ::"l"(wo + (size_t)cta * 48 * DM), "r"(48 * DM * 2) : "memory");
                    if (cta < FF / 16)
                        asm volatile("cp.async.bulk.prefetch.L2.global [%0], %1;" ::"l"(w_down + (size_t)cta * 16 * DM), "r"(16 * DM * 2) : "memory");
                }
                item = next;
            }
#pragma unroll 1
            for (int j = 0; j < 8; ++j, u += TPI) {
                const int st = u % NST;
                mbar_wait(bar_empty + st * 8, (u / NST) & 1);
                s_item[st] = -1;
                s_tag[st] = u;
                mbar_arrive(bar_full + st * 8);
            }
            PROFP(13);
        }
        return;
    }

    const int lane = tid & 31, warp = tid >> 5;
    float* s_part = (float*)(smem + SM_PART);
    float* s_xp = (float*)(smem + SM_XP);
    __nv_bfloat16* s_a = (__nv_bfloat16*)(smem + SM_A);

    PROF(0);
    {
        const int i1 = tid + NCONS;
        const uint4 c0 = __ldg((const uint4*)cvec + tid), x0 = __ldg((const uint4*)x_in + tid);
        uint4 c1 = c0, x1 = x0;
        if (i1 < 320) { c1 = __ldg((const uint4*)cvec + i1); x1 = __ldg((const uint4*)x_in + i1); }
        if (cta < MODN / 32) stage_rows(sbase + SM_W32, P32, w_mod + cta * 32, MODN * 2, DM, 4, tid);
        cp_async_commit();
        if (cta < QN / 48) stage_rows(sbase + SM_WQ, P48, wq + cta * 48, QN * 2, DM, 6, tid);
        cp_async_commit();
#pragma unroll 1
        for (int r = 0; r < 2; ++r) {
            const int i = r ? i1 : tid;
            if (i < 320) {
                const uint4 cc = r ? c1 : c0, xx = r ? x1 : x0;
                const uint32_t cw[4] = {cc.x, cc.y, cc.z, cc.w}, xw[4] = {xx.x, xx.y, xx.z, xx.w};
                uint32_t ow[4];
#pragma unroll
                for (int k = 0; k < 4; ++k) {
                    const float a = bf_lo(cw[k]), b = bf_hi(cw[k]);
                    __nv_bfloat162 p = __floats2bfloat162_rn(__fdiv_rn(a, 1.0f + __expf(-a)), __fdiv_rn(b, 1.0f + __expf(-b)));
                    ow[k] = *(uint32_t*)&p;
                    s_xp[i * 8 + 2 * k] = bf_lo(xw[k]);
                    s_xp[i * 8 + 2 * k + 1] = bf_hi(xw[k]);
                }
                const int b = i / 80, c8 = i - b * 80;
                *(uint4*)(smem + SM_A + b * A_PITCH + c8 * 16) = make_uint4(ow[0], ow[1], ow[2], ow[3]);
            }
        }
    }
    if (cta == gridDim.x - 1) {
#pragma unroll 1
        for (int i = tid; i < NB * QN / 4; i += NCONS) ((float4*)g_o)[i] = make_float4(0.f, 0.f, 0.f, 0.f);
#pragma unroll 1
        for (int i = tid; i < NB * DM; i += NCONS) { g_attn[i] = 0.f; g_ffn[i] = 0.f; }
        if (tid < NBH) g_kcnt[tid] = 0u;
    }
    cp_async_wait1();
    cons_sync();
    if (cta < MODN / 32) {
        gemv_mma(sbase + SM_W32 + warp * 80 * P32, P32, sbase + SM_A + warp * 160, 5, 4, s_part + warp * 320, lane);
        cons_sync();
        if (tid < 128) g_mod[(tid >> 5) * MODN + cta * 32 + (tid & 31)] = bf16r(tall_sum(s_part, tid >> 5, tid & 31));
    }
    PROF(1);
    grid_barrier(&g_bar[0], tid);
    PROF(2);

    if (cta < QN / 48) {
        if (warp < NB)
            ln_mod_row(s_xp + warp * DM, nullptr, nullptr, g_mod + warp * MODN, g_mod + warp * MODN + DM,
                       s_a + warp * (A_PITCH / 2), lane);
        cp_async_wait_all();
        cons_sync();
        gemv_mma(sbase + SM_WQ + warp * 80 * P48, P48, sbase + SM_A + warp * 160, 5, 6, s_part + warp * 320, lane);
        cons_sync();
        if (tid < 192) {
            const int b = tid / 48, n = tid - b * 48;
            g_q[b * QN + cta * 48 + n] = __float2bfloat16_rn(tall_sum(s_part, b, n));
        }
    }
    PROF(3);
    grid_barrier(&g_bar[1], tid);
    if (tid == 0) {
#pragma unroll 1
        for (int s = PRE; s < NST; ++s) mbar_arrive(bar_empty + s * 8);
    }
    if (cta < FF / 16) {
        stage_rows(sbase + SM_W32, P32, w_gate + cta * 16, FF * 2, DM, 2, tid);
        stage_rows(sbase + SM_W32 + 32, P32, w_up + cta * 16, FF * 2, DM, 2, tid);
    }
    PROF(4);

    {
        const int sub = lane & 7, grp = lane >> 3;
        for (int u0 = warp * TPI;; u0 += 8 * TPI) {
            stage_wait(bar_full, s_tag, u0);
            const int item = s_item[u0 % NST];
            if (item < 0) {
                __syncwarp();
                if (lane == 0) mbar_arrive(bar_empty + (u0 % NST) * 8);
                break;
            }
            const int bh = (item & (NITEM_K - 1)) / CHUNKS;
            if (item < NITEM_K) {
                float* gs = g_s + (size_t)item * ITEM_KEYS;
                float qr[24];
                {
                    const uint4* qp = (const uint4*)(smem + SM_RING + (u0 % NST) * STAGE_BYTES + TILE_BYTES) + sub;
#pragma unroll
                    for (int j = 0; j < 3; ++j) {
                        const uint4 v = qp[8 * j];
                        qr[j * 8 + 0] = bf_lo(v.x); qr[j * 8 + 1] = bf_hi(v.x);
                        qr[j * 8 + 2] = bf_lo(v.y); qr[j * 8 + 3] = bf_hi(v.y);
                        qr[j * 8 + 4] = bf_lo(v.z); qr[j * 8 + 5] = bf_hi(v.z);
                        qr[j * 8 + 6] = bf_lo(v.w); qr[j * 8 + 7] = bf_hi(v.w);
                    }
                }
                float m_run = -INFINITY, l_run = 0.f;
#pragma unroll 1
                for (int t = 0; t < TPI; ++t) {
                    const int u = u0 + t, st = u % NST;
                    stage_wait(bar_full, s_tag, u);
                    const uint4* tile = (const uint4*)(smem + SM_RING + st * STAGE_BYTES);
                    float part[8];
#pragma unroll
                    for (int it = 0; it < 8; ++it) {
                        const uint4* row = tile + (it * 4 + grp) * 24 + sub;
                        const uint4 a = row[0], b = row[8], c = row[16];
                        part[it] = dot8(a, qr) + dot8(b, qr + 8) + dot8(c, qr + 16);
                    }
                    __syncwarp();
                    if (lane == 0) mbar_arrive(bar_empty + st * 8);
#pragma unroll
                    for (int j = 0; j < 4; ++j) {
                        const float send = (sub & 4) ? part[j] : part[j + 4];
                        const float keep = (sub & 4) ? part[j + 4] : part[j];
                        part[j] = keep + __shfl_xor_sync(0xffffffffu, send, 4);
                    }
#pragma unroll
                    for (int j = 0; j < 2; ++j) {
                        const float send = (sub & 2) ? part[j] : part[j + 2];
                        const float keep = (sub & 2) ? part[j + 2] : part[j];
                        part[j] = keep + __shfl_xor_sync(0xffffffffu, send, 2);
                    }
                    {
                        const float send = (sub & 1) ? part[0] : part[1];
                        const float keep = (sub & 1) ? part[1] : part[0];
                        part[0] = keep + __shfl_xor_sync(0xffffffffu, send, 1);
                    }
                    const float s = bf16r(bf16r(part[0]) * 0.07216878364870323f);
                    gs[t * TILE_KEYS + sub * 4 + grp] = s;
                    const float m_new = fmaxf(m_run, s);
                    l_run = l_run * __expf(m_run - m_new) + __expf(s - m_new);
                    m_run = m_new;
                }
                const float m = warp_max(m_run);
                const float l = warp_sum(l_run * __expf(m_run - m));
                __syncwarp();
                if (lane == 0) {
                    g_stat[item] = make_float2(m, l);
                    red_release_add(&g_kcnt[bh], 1u);
                }
            } else {
                float acc[3][8];
#pragma unroll
                for (int j = 0; j < 3; ++j)
#pragma unroll
                    for (int e = 0; e < 8; ++e) acc[j][e] = 0.f;
#pragma unroll 1
                for (int t = 0; t < TPI; ++t) {
                    const int u = u0 + t, st = u % NST;
                    stage_wait(bar_full, s_tag, u);
                    const uint4* tile = (const uint4*)(smem + SM_RING + st * STAGE_BYTES);
                    const float* aux = (const float*)(smem + SM_RING + st * STAGE_BYTES + TILE_BYTES);
                    const float2 st2 = *(const float2*)(aux + TILE_KEYS + 2 * lane);
                    const float mm = warp_max(st2.x);
                    const float ll = warp_sum(st2.y * __expf(st2.x - mm));
                    const float pl = bf16r(__fdiv_rn(__expf(aux[lane] - mm), ll));
#pragma unroll
                    for (int it = 0; it < 8; ++it) {
                        const uint4* row = tile + (it * 4 + grp) * 24 + sub;
                        const uint4 a = row[0], b = row[8], c = row[16];
                        const float p = __shfl_sync(0xffffffffu, pl, it * 4 + grp);
                        fma8(acc[0], a, p);
                        fma8(acc[1], b, p);
                        fma8(acc[2], c, p);
                    }
                    __syncwarp();
                    if (lane == 0) mbar_arrive(bar_empty + st * 8);
                }
                float* go = g_o + (bh >> 5) * QN + (bh & 31) * DH + sub * 8;
#pragma unroll
                for (int j = 0; j < 3; ++j) {
#pragma unroll
                    for (int e = 0; e < 8; ++e) {
                        float v = acc[j][e];
                        v += __shfl_xor_sync(0xffffffffu, v, 8);
                        v += __shfl_xor_sync(0xffffffffu, v, 16);
                        acc[j][e] = v;
                    }
                    if (grp == 0) {
                        red_add_v4(go + j * 64, acc[j][0], acc[j][1], acc[j][2], acc[j][3]);
                        red_add_v4(go + j * 64 + 4, acc[j][4], acc[j][5], acc[j][6], acc[j][7]);
                    }
                }
            }
        }
    }
    PROF(5);
    cons_sync();
    if (warp == 0) {
        asm volatile("fence.proxy.async.shared::cta;" ::: "memory");
        const int nrows = (cta < QN / 48 ? 48 : 0) + (cta < FF / 16 ? 16 : 0);
        if (lane == 0) mbar_expect_tx(bar_tail, nrows * DM * 2);
        __syncwarp();
#pragma unroll 1
        for (int r = lane; r < nrows; r += 32) {
            const __nv_bfloat16* src = r < 48 ? wo + ((size_t)cta * 48 + r) * DM : w_down + ((size_t)cta * 16 + r - 48) * DM;
            bulk_g2s(sbase + SM_WO + r * WIDE_PITCH, src, DM * 2, bar_tail);
        }
    }
    PROF(6);
    grid_barrier(&g_bar[2], tid);
    PROF(7);

    if (cta < QN / 48) {
        if (tid < 192) {
            const int b = tid / 48, n = tid - b * 48;
            s_a[b * (A_PITCH / 2) + n] = __float2bfloat16_rn(__ldcg(g_o + b * QN + cta * 48 + n));
        }
        mbar_wait(bar_tail, 0);
        cons_sync();
        gemv_mma(sbase + SM_WO + warp * 160, WIDE_PITCH, sbase + SM_A, 3, 10, s_part + warp * 320, lane);
        cons_sync();
        wide_flush(s_part, g_attn, tid);
    }
    PROF(8);
    grid_barrier(&g_bar[3], tid);
    PROF(9);

    if (cta < FF / 16) {
        if (warp < NB)
            ln_mod_row(s_xp + warp * DM, g_attn + warp * DM, g_mod + warp * MODN + 2 * DM, g_mod + warp * MODN + 3 * DM,
                       g_mod + warp * MODN + 4 * DM, s_a + warp * (A_PITCH / 2), lane);
        cp_async_wait_all();
        cons_sync();
        gemv_mma(sbase + SM_W32 + warp * 80 * P32, P32, sbase + SM_A + warp * 160, 5, 4, s_part + warp * 320, lane);
        cons_sync();
        if (tid < 64) {
            const int b = tid >> 4, n = tid & 15;
            const float g = bf16r(tall_sum(s_part, b, n));
            const float up = bf16r(tall_sum(s_part, b, 16 + n));
            s_a[b * (A_PITCH / 2) + n] = __float2bfloat16_rn(bf16r(gelu_tanh(g)) * up);
        }
        cons_sync();
        gemv_mma(sbase + SM_WD + warp * 160, WIDE_PITCH, sbase + SM_A, 1, 10, s_part + warp * 320, lane);
        cons_sync();
        wide_flush(s_part, g_ffn, tid);
    }
    PROF(10);
    cons_sync();
    if (tid == 0) {
        __threadfence();
        const unsigned int old = atomicAdd(&g_bar[4], 1u);
        s_item[0] = ((old % gridDim.x) == gridDim.x - 1) ? 1 : 0;
        __threadfence();
    }
    cons_sync();
    if (s_item[0] != 0) {
        float4 f[3], a[3], ga[3], gb[3];
#pragma unroll
        for (int r = 0; r < 3; ++r) {
            const int i = tid + r * NCONS;
            if (i < NB * DM / 4) {
                const int b = i / 160, c4 = i - b * 160;
                f[r] = __ldcg((const float4*)g_ffn + i);
                a[r] = __ldcg((const float4*)g_attn + i);
                ga[r] = __ldcg((const float4*)(g_mod + b * MODN + 2 * DM) + c4);
                gb[r] = __ldcg((const float4*)(g_mod + b * MODN + 5 * DM) + c4);
            }
        }
#pragma unroll
        for (int r = 0; r < 3; ++r) {
            const int i = tid + r * NCONS;
            if (i < NB * DM / 4) {
                const float4 x = *((const float4*)s_xp + i);
                const float o0 = bf16r(x.x + bf16r(ga[r].x * bf16r(a[r].x))) + bf16r(gb[r].x * bf16r(f[r].x));
                const float o1 = bf16r(x.y + bf16r(ga[r].y * bf16r(a[r].y))) + bf16r(gb[r].y * bf16r(f[r].y));
                const float o2 = bf16r(x.z + bf16r(ga[r].z * bf16r(a[r].z))) + bf16r(gb[r].z * bf16r(f[r].z));
                const float o3 = bf16r(x.w + bf16r(ga[r].w * bf16r(a[r].w))) + bf16r(gb[r].w * bf16r(f[r].w));
                __nv_bfloat162 p0 = __floats2bfloat162_rn(o0, o1), p1 = __floats2bfloat162_rn(o2, o3);
                uint2 u;
                u.x = *(uint32_t*)&p0; u.y = *(uint32_t*)&p1;
                *((uint2*)out + i) = u;
            }
        }
        if (tid == 0) g_work = 0u;
        PROF(11);
    }
}

}

extern "C" void kernel_launch(void* const* d_in, const int* in_sizes, int n_in, void* d_out, int out_size) {
    (void)in_sizes; (void)n_in; (void)out_size;
    const __nv_bfloat16* A_x = (const __nv_bfloat16*)d_in[0];
    const __nv_bfloat16* A_k = (const __nv_bfloat16*)d_in[1];
    const __nv_bfloat16* A_v = (const __nv_bfloat16*)d_in[2];
    const __nv_bfloat16* A_wq = (const __nv_bfloat16*)d_in[3];
    const __nv_bfloat16* A_wo = (const __nv_bfloat16*)d_in[4];
    const __nv_bfloat16* B_wg = (const __nv_bfloat16*)d_in[6];
    const __nv_bfloat16* B_wu = (const __nv_bfloat16*)d_in[7];
    const __nv_bfloat16* B_wd = (const __nv_bfloat16*)d_in[8];
    const __nv_bfloat16* c = (const __nv_bfloat16*)d_in[9];
    const __nv_bfloat16* w_mod = (const __nv_bfloat16*)d_in[10];
    static int grid = 0;
    if (grid == 0) {
        cudaFuncSetAttribute(decode_block_kernel, cudaFuncAttributeMaxDynamicSharedMemorySize, SM_TOTAL);
        int dev = 0, sms = 0;
        cudaGetDevice(&dev);
        cudaDeviceGetAttribute(&sms, cudaDevAttrMultiProcessorCount, dev);
        grid = sms < 132 ? sms : 132;
    }
    decode_block_kernel<<<grid, NTHREADS, SM_TOTAL>>>(A_x, A_k, A_v, A_wq, A_wo, B_wg, B_wu, B_wd, c, w_mod,
                                                      (__nv_bfloat16*)d_out);
}
```

```cpp
#include <cuda_runtime.h>
#include <cuda_bf16.h>
#include <stdint.h>

namespace {

constexpr int NB = 4;
constexpr int DM = 640;
constexpr int NH = 32;
constexpr int SK = 4096;
constexpr int DH = 192;
constexpr int FF = 1536;
constexpr int MODN = 6 * DM;
constexpr int QN = NH * DH;
constexpr int NBH = NB * NH;

constexpr int NCONS = 256;
constexpr int NTHREADS = NCONS + 32;
constexpr int TILE_KEYS = 64;
constexpr int TILE_BYTES = TILE_KEYS * DH * 2;
constexpr int AUX_BYTES = 512;
constexpr int STAGE_BYTES = TILE_BYTES + AUX_BYTES;
constexpr int NST = 6;
constexpr int PRE = 3;
constexpr int TPI = 2;
constexpr int ITEM_KEYS = TPI * TILE_KEYS;
constexpr int CHUNKS = SK / ITEM_KEYS;
constexpr int NITEM_K = NBH * CHUNKS;
constexpr int NITEM = 2 * NITEM_K;

constexpr int A_PITCH = 1296;
constexpr int WIDE_PITCH = 1296;
constexpr int P32 = 80;
constexpr int P48 = 112;

constexpr int SM_RING = 0;
constexpr int SM_WQ = PRE * STAGE_BYTES;
constexpr int SM_WO = 0;
constexpr int SM_WD = SM_WO + 48 * WIDE_PITCH;
constexpr int SM_W32 = NST * STAGE_BYTES;
constexpr int SM_A = SM_W32 + DM * P32;
constexpr int SM_PART = SM_A + NB * A_PITCH;
constexpr int SM_XP = SM_PART + 8 * 4 * 80 * 4;
constexpr int SM_ITEM = SM_XP + NB * DM * 4;
constexpr int SM_TAG = SM_ITEM + 16 * 4;
constexpr int SM_BAR = SM_TAG + 16 * 4;
constexpr int SM_TOTAL = SM_BAR + (2 * NST + 1) * 8;
static_assert(SM_WQ + DM * P48 <= NST * STAGE_BYTES, "prologue overlay");
static_assert(SM_WD + 16 * WIDE_PITCH <= NST * STAGE_BYTES, "tail overlay");
static_assert(SM_TOTAL <= 232448, "smem");

__device__ __align__(128) float g_mod[NB * MODN];
__device__ __align__(128) __nv_bfloat16 g_q[NB * QN];
__device__ __align__(128) float g_s[NBH * SK];
__device__ __align__(128) float2 g_stat[NBH * CHUNKS];
__device__ __align__(128) unsigned int g_kcnt[NBH];
__device__ __align__(128) float g_o[NB * QN];
__device__ __align__(128) float g_attn[NB * DM];
__device__ __align__(128) float g_ffn[NB * DM];
__device__ __align__(128) unsigned int g_bar[8];
__device__ unsigned int g_work;
__device__ unsigned int g_kall;

#define PROF(k) do { } while (0)
#define PROFP(k) do { } while (0)

__device__ __forceinline__ float bf16r(float x) { return __bfloat162float(__float2bfloat16_rn(x)); }
__device__ __forceinline__ float bf_lo(uint32_t u) { return __uint_as_float(u << 16); }
__device__ __forceinline__ float bf_hi(uint32_t u) { return __uint_as_float(u & 0xffff0000u); }

__device__ __forceinline__ uint32_t smem_u32(const void* p) { return (uint32_t)__cvta_generic_to_shared(p); }
__device__ __forceinline__ void mbar_init(uint32_t bar, uint32_t count) {
    asm volatile("mbarrier.init.shared::cta.b64 [%0], %1;" ::"r"(bar), "r"(count) : "memory");
}
__device__ __forceinline__ void mbar_expect_tx(uint32_t bar, uint32_t bytes) {
    asm volatile("mbarrier.arrive.expect_tx.shared::cta.b64 _, [%0], %1;" ::"r"(bar), "r"(bytes) : "memory");
}
__device__ __forceinline__ void mbar_arrive(uint32_t bar) {
    asm volatile("mbarrier.arrive.shared::cta.b64 _, [%0];" ::"r"(bar) : "memory");
}
constexpr long long WAIT_LIMIT_CYCLES = 200000000LL;
__device__ __forceinline__ uint32_t mbar_try(uint32_t bar, uint32_t parity) {
    uint32_t done;
    asm volatile(
        "{\n\t.reg .pred p;\n\t"
        "mbarrier.try_wait.parity.shared::cta.b64 p, [%1], %2;\n\t"
        "selp.u32 %0, 1, 0, p;\n\t}"
        : "=r"(done) : "r"(bar), "r"(parity) : "memory");
    return done;
}
__device__ __noinline__ void mbar_wait_slow(uint32_t bar, uint32_t parity) {
    const long long t0 = clock64();
    while (!mbar_try(bar, parity)) {
        if (clock64() - t0 > WAIT_LIMIT_CYCLES) __trap();
    }
}
__device__ __forceinline__ void mbar_wait(uint32_t bar, uint32_t parity) {
    if (!mbar_try(bar, parity)) mbar_wait_slow(bar, parity);
}
__device__ __noinline__ void tag_wait_slow(volatile int* tag, int u) {
    const long long t0 = clock64();
    while (*tag != u) {
        __nanosleep(32);
        if (clock64() - t0 > WAIT_LIMIT_CYCLES) __trap();
    }
}
__device__ __forceinline__ void stage_wait(uint32_t bar_full, volatile int* s_tag, int u) {
    const int st = u % NST;
    if (s_tag[st] != u) tag_wait_slow(s_tag + st, u);
    mbar_wait(bar_full + st * 8, (u / NST) & 1);
}
__device__ __forceinline__ void bulk_g2s(uint32_t dst, const void* src, uint32_t bytes, uint32_t bar) {
    asm volatile(
        "cp.async.bulk.shared::cluster.global.mbarrier::complete_tx::bytes [%0], [%1], %2, [%3];"
        ::"r"(dst), "l"(src), "r"(bytes), "r"(bar) : "memory");
}
__device__ __forceinline__ void cp_async16(uint32_t dst, const void* src) {
    asm volatile("cp.async.cg.shared.global [%0], [%1], 16;" ::"r"(dst), "l"(src) : "memory");
}
__device__ __forceinline__ void cp_async_wait_all() { asm volatile("cp.async.wait_all;" ::: "memory"); }
__device__ __forceinline__ void cp_async_commit() { asm volatile("cp.async.commit_group;" ::: "memory"); }
__device__ __forceinline__ void cp_async_wait1() { asm volatile("cp.async.wait_group 1;" ::: "memory"); }
__device__ __forceinline__ void red_release_add(unsigned int* p, unsigned int v) {
    asm volatile("red.release.gpu.global.add.u32 [%0], %1;" ::"l"(p), "r"(v) : "memory");
}
__device__ __forceinline__ void cons_sync() { asm volatile("bar.sync 1, 256;" ::: "memory"); }

__device__ __forceinline__ void red_add_v4(float* p, float a, float b, float c, float d) {
    asm volatile("red.global.add.v4.f32 [%0], {%1, %2, %3, %4};" ::"l"(p), "f"(a), "f"(b), "f"(c), "f"(d) : "memory");
}
__device__ __forceinline__ unsigned int ld_acquire(const unsigned int* p) {
    unsigned int v;
    asm volatile("ld.acquire.gpu.global.u32 %0, [%1];" : "=r"(v) : "l"(p) : "memory");
    return v;
}
__device__ __forceinline__ void st_release(unsigned int* p, unsigned int v) {
    asm volatile("st.release.gpu.global.u32 [%0], %1;" ::"l"(p), "r"(v) : "memory");
}

__device__ __noinline__ void grid_barrier(unsigned int* ctr, int tid) {
    cons_sync();
    if (tid == 0) {
        const unsigned int n = gridDim.x;
        __threadfence();
        const unsigned int old = atomicAdd(ctr, 1u);
        const unsigned int target = (old / n + 1u) * n;
        const long long t0 = clock64();
        while ((int)(ld_acquire(ctr) - target) < 0) {
            if (clock64() - t0 > WAIT_LIMIT_CYCLES) __trap();
        }
        __threadfence();
    }
    cons_sync();
}

__device__ __forceinline__ float warp_sum(float v) {
#pragma unroll
    for (int o = 16; o > 0; o >>= 1) v += __shfl_xor_sync(0xffffffffu, v, o);
    return v;
}
__device__ __forceinline__ float warp_max(float v) {
#pragma unroll
    for (int o = 16; o > 0; o >>= 1) v = fmaxf(v, __shfl_xor_sync(0xffffffffu, v, o));
    return v;
}

__device__ __forceinline__ void fma8(float (&acc)[8], const uint4& w, float s) {
    acc[0] = fmaf(s, bf_lo(w.x), acc[0]);
    acc[1] = fmaf(s, bf_hi(w.x), acc[1]);
    acc[2] = fmaf(s, bf_lo(w.y), acc[2]);
    acc[3] = fmaf(s, bf_hi(w.y), acc[3]);
    acc[4] = fmaf(s, bf_lo(w.z), acc[4]);
    acc[5] = fmaf(s, bf_hi(w.z), acc[5]);
    acc[6] = fmaf(s, bf_lo(w.w), acc[6]);
    acc[7] = fmaf(s, bf_hi(w.w), acc[7]);
}
__device__ __forceinline__ float dot8(const uint4& w, const float* q) {
    float s = q[0] * bf_lo(w.x);
    s = fmaf(q[1], bf_hi(w.x), s);
    s = fmaf(q[2], bf_lo(w.y), s);
    s = fmaf(q[3], bf_hi(w.y), s);
    s = fmaf(q[4], bf_lo(w.z), s);
    s = fmaf(q[5], bf_hi(w.z), s);
    s = fmaf(q[6], bf_lo(w.w), s);
    s = fmaf(q[7], bf_hi(w.w), s);
    return s;
}

__device__ __noinline__ void stage_rows(uint32_t dst, int dst_pitch, const void* src, int src_stride, int rows,
                                        int cpr, int tid) {
    const int n = rows * cpr;
#pragma unroll 1
    for (int i = tid; i < n; i += NCONS) {
        const int r = i / cpr, c = i - r * cpr;
        cp_async16(dst + r * dst_pitch + c * 16, (const unsigned char*)src + (size_t)r * src_stride + c * 16);
    }
}

__device__ __noinline__ void gemv_mma(uint32_t w, int w_pitch, uint32_t a, int ksteps, int ntiles, float* part,
                                      int lane) {
    float c[10][4];
#pragma unroll
    for (int nt = 0; nt < 10; ++nt) { c[nt][0] = 0.f; c[nt][1] = 0.f; c[nt][2] = 0.f; c[nt][3] = 0.f; }
    uint32_t ap = a + (lane >> 2) * A_PITCH + (lane & 3) * 4;
    uint32_t wp = w + (lane & 15) * w_pitch;
    for (int ks = 0; ks < ksteps; ++ks) {
        uint32_t a0 = 0, a2 = 0;
        if (lane < 16) {
            asm volatile("ld.shared.u32 %0, [%1];" : "=r"(a0) : "r"(ap));
            asm volatile("ld.shared.u32 %0, [%1];" : "=r"(a2) : "r"(ap + 16));
        }
#pragma unroll
        for (int nt = 0; nt < 10; ++nt) {
            if (nt < ntiles) {
                uint32_t b0, b1;
                asm volatile("ldmatrix.sync.aligned.m8n8.x2.trans.shared.b16 {%0, %1}, [%2];"
                             : "=r"(b0), "=r"(b1) : "r"(wp + nt * 16));
                asm volatile(
                    "mma.sync.aligned.m16n8k16.row.col.f32.bf16.bf16.f32 {%0, %1, %2, %3}, {%4, %5, %6, %7}, "
                    "{%8, %9}, {%0, %1, %2, %3};"
                    : "+f"(c[nt][0]), "+f"(c[nt][1]), "+f"(c[nt][2]), "+f"(c[nt][3])
                    : "r"(a0), "r"(0u), "r"(a2), "r"(0u), "r"(b0), "r"(b1));
            }
        }
        ap += 32;
        wp += 16 * w_pitch;
    }
    if (lane < 16) {
        float* pp = part + (lane >> 2) * 80 + (lane & 3) * 2;
#pragma unroll
        for (int nt = 0; nt < 10; ++nt)
            if (nt < ntiles) *(float2*)(pp + nt * 8) = make_float2(c[nt][0], c[nt][1]);
    }
}

__device__ __forceinline__ float tall_sum(const float* part, int b, int n) {
    float s = 0.f;
#pragma unroll
    for (int w = 0; w < 8; ++w) s += part[(w * 4 + b) * 80 + n];
    return s;
}

__device__ __noinline__ void wide_flush(const float* part, float* dst, int tid) {
#pragma unroll 1
    for (int i = tid; i < NB * DM / 4; i += NCONS) {
        const int b = i / 160, col = (i - b * 160) * 4;
        const int w = col / 80, n = col - w * 80;
        const float4 v = *(const float4*)(part + (w * 4 + b) * 80 + n);
        red_add_v4(dst + b * DM + col, v.x, v.y, v.z, v.w);
    }
}

__device__ __noinline__ void ln_mod_row(const float* xs, const float* attn, const float* gate, const float* shift,
                                        const float* scale, __nv_bfloat16* out, int lane) {
    float4 xv[5], sh[5], sc[5];
#pragma unroll
    for (int i = 0; i < 5; ++i) {
        sh[i] = __ldcg((const float4*)shift + lane + 32 * i);
        sc[i] = __ldcg((const float4*)scale + lane + 32 * i);
        xv[i] = *((const float4*)xs + lane + 32 * i);
    }
    if (attn != nullptr) {
        float4 av[5], gv[5];
#pragma unroll
        for (int i = 0; i < 5; ++i) {
            av[i] = __ldcg((const float4*)attn + lane + 32 * i);
            gv[i] = __ldcg((const float4*)gate + lane + 32 * i);
        }
#pragma unroll
        for (int i = 0; i < 5; ++i) {
            xv[i].x = bf16r(xv[i].x + bf16r(gv[i].x * bf16r(av[i].x)));
            xv[i].y = bf16r(xv[i].y + bf16r(gv[i].y * bf16r(av[i].y)));
            xv[i].z = bf16r(xv[i].z + bf16r(gv[i].z * bf16r(av[i].z)));
            xv[i].w = bf16r(xv[i].w + bf16r(gv[i].w * bf16r(av[i].w)));
        }
    }
    float s = 0.f;
#pragma unroll
    for (int i = 0; i < 5; ++i) s += (xv[i].x + xv[i].y) + (xv[i].z + xv[i].w);
    s = warp_sum(s);
    const float mean_f = s * (1.0f / DM);
    float v = 0.f;
#pragma unroll
    for (int i = 0; i < 5; ++i) {
        float d;
        d = xv[i].x - mean_f; v = fmaf(d, d, v);
        d = xv[i].y - mean_f; v = fmaf(d, d, v);
        d = xv[i].z - mean_f; v = fmaf(d, d, v);
        d = xv[i].w - mean_f; v = fmaf(d, d, v);
    }
    v = warp_sum(v);
    const float mean = bf16r(mean_f);
    const float den = bf16r(sqrtf(bf16r(bf16r(v * (1.0f / DM)) + 1e-5f)));
#pragma unroll
    for (int i = 0; i < 5; ++i) {
        const float h0 = bf16r(bf16r(__fdiv_rn(bf16r(xv[i].x - mean), den)) * bf16r(1.0f + sc[i].x)) + sh[i].x;
        const float h1 = bf16r(bf16r(__fdiv_rn(bf16r(xv[i].y - mean), den)) * bf16r(1.0f + sc[i].y)) + sh[i].y;
        const float h2 = bf16r(bf16r(__fdiv_rn(bf16r(xv[i].z - mean), den)) * bf16r(1.0f + sc[i].z)) + sh[i].z;
        const float h3 = bf16r(bf16r(__fdiv_rn(bf16r(xv[i].w - mean), den)) * bf16r(1.0f + sc[i].w)) + sh[i].w;
        __nv_bfloat162 p0 = __floats2bfloat162_rn(h0, h1), p1 = __floats2bfloat162_rn(h2, h3);
        uint2 u;
        u.x = *(uint32_t*)&p0; u.y = *(uint32_t*)&p1;
        *((uint2*)out + lane + 32 * i) = u;
    }
}

__device__ __forceinline__ float gelu_tanh(float x) {
    const float kBeta = 0.7978845608028654f;
    const float inner = kBeta * (x + 0.044715f * x * x * x);
    return 0.5f * x * (1.0f + tanhf(inner));
}

__global__ void __launch_bounds__(NTHREADS, 1)
decode_block_kernel(const __nv_bfloat16* __restrict__ x_in, const __nv_bfloat16* __restrict__ k_cache,
                    const __nv_bfloat16* __restrict__ v_cache, const __nv_bfloat16* __restrict__ wq,
                    const __nv_bfloat16* __restrict__ wo, const __nv_bfloat16* __restrict__ w_gate,
                    const __nv_bfloat16* __restrict__ w_up, const __nv_bfloat16* __restrict__ w_down,
                    const __nv_bfloat16* __restrict__ cvec, const __nv_bfloat16* __restrict__ w_mod,
                    __nv_bfloat16* __restrict__ out) {
    extern __shared__ __align__(128) unsigned char smem[];
    const int tid = threadIdx.x;
    const int cta = blockIdx.x;

    const uint32_t sbase = smem_u32(smem);
    const uint32_t bar_full = sbase + SM_BAR;
    const uint32_t bar_empty = bar_full + NST * 8;
    volatile int* s_item = (volatile int*)(smem + SM_ITEM);
    volatile int* s_tag = (volatile int*)(smem + SM_TAG);

    const uint32_t bar_tail = bar_empty + NST * 8;
    if (tid < NST) s_tag[tid] = -1;
    if (tid == 0) {
#pragma unroll 1
        for (int s = 0; s < 2 * NST + 1; ++s) mbar_init(bar_full + s * 8, 1);
        asm volatile("fence.mbarrier_init.release.cluster;" ::: "memory");
        asm volatile("fence.proxy.async.shared::cta;" ::: "memory");
#pragma unroll 1
        for (int s = 0; s < PRE; ++s) mbar_arrive(bar_empty + s * 8);
    }
    __syncthreads();

    if (tid >= NCONS) {
        if (tid == NCONS) {
            int item = cta;
            int u = 0;
            bool pf = false, kdone = false;
            while (item < NITEM) {
                const int next = (int)atomicAdd(&g_work, 1u) + (int)gridDim.x;
                const int it = item & (NITEM_K - 1), bh = it / CHUNKS;
                const bool is_v = item >= NITEM_K;
                const unsigned char* src = (const unsigned char*)(is_v ? v_cache : k_cache) + (size_t)it * (ITEM_KEYS * DH * 2);
                if (is_v && !kdone) {
                    if (ld_acquire(&g_kall) == NITEM_K) {
                        kdone = true;
                    } else {
                        const long long t0 = clock64();
                        while (ld_acquire(&g_kcnt[bh]) < CHUNKS)
                            if (clock64() - t0 > WAIT_LIMIT_CYCLES) __trap();
                    }
                    asm volatile("fence.proxy.async;" ::: "memory");
                }
#pragma unroll 1
                for (int t = 0; t < TPI; ++t, ++u) {
                    const int st = u % NST;
                    const uint32_t dst = sbase + SM_RING + st * STAGE_BYTES, fb = bar_full + st * 8;
                    mbar_wait(bar_empty + st * 8, (u / NST) & 1);
                    if (u == PRE) {
                        asm volatile("fence.proxy.async;" ::: "memory");
#pragma unroll 1
                        for (int e = 0; e < PRE; ++e) {
                            const int ebh = s_item[e] / CHUNKS;
                            bulk_g2s(sbase + SM_RING + e * STAGE_BYTES + TILE_BYTES, g_q + (ebh >> 5) * QN + (ebh & 31) * DH,
                                     DH * 2, bar_full + e * 8);
                        }
                    }
                    s_item[st] = item;
                    s_tag[st] = u;
                    mbar_expect_tx(fb, is_v ? STAGE_BYTES : TILE_BYTES + DH * 2);
                    bulk_g2s(dst, src + t * TILE_BYTES, TILE_BYTES, fb);
                    if (is_v) {
                        bulk_g2s(dst + TILE_BYTES, g_s + (size_t)it * ITEM_KEYS + t * TILE_KEYS, TILE_KEYS * 4, fb);
                        bulk_g2s(dst + TILE_BYTES + TILE_KEYS * 4, g_stat + bh * CHUNKS, CHUNKS * 8, fb);
                    } else if (u >= PRE) {
                        bulk_g2s(dst + TILE_BYTES, g_q + (bh >> 5) * QN + (bh & 31) * DH, DH * 2, fb);
                    }
                }
                if (!pf && next >= NITEM - 8 * (int)gridDim.x) {
                    pf = true;
                    if (cta < QN / 48)
                        asm volatile("cp.async.bulk.prefetch.L2.global [%0], %1;" ::"l"(wo + (size_t)cta * 48 * DM), "r"(48 * DM * 2) : "memory");
                    if (cta < FF / 16)
                        asm volatile("cp.async.bulk.prefetch.L2.global [%0], %1;" ::"l"(w_down + (size_t)cta * 16 * DM), "r"(16 * DM * 2) : "memory");
                }
                item = next;
            }
#pragma unroll 1
            for (int j = 0; j < 8; ++j, u += TPI) {
                const int st = u % NST;
                mbar_wait(bar_empty + st * 8, (u / NST) & 1);
                s_item[st] = -1;
                s_tag[st] = u;
                mbar_arrive(bar_full + st * 8);
            }
            PROFP(13);
        }
        return;
    }

    const int lane = tid & 31, warp = tid >> 5;
    float* s_part = (float*)(smem + SM_PART);
    float* s_xp = (float*)(smem + SM_XP);
    __nv_bfloat16* s_a = (__nv_bfloat16*)(smem + SM_A);

    PROF(0);
    {
        const int i1 = tid + NCONS;
        const uint4 c0 = __ldg((const uint4*)cvec + tid), x0 = __ldg((const uint4*)x_in + tid);
        uint4 c1 = c0, x1 = x0;
        if (i1 < 320) { c1 = __ldg((const uint4*)cvec + i1); x1 = __ldg((const uint4*)x_in + i1); }
        if (cta < MODN / 32) stage_rows(sbase + SM_W32, P32, w_mod + cta * 32, MODN * 2, DM, 4, tid);
        cp_async_commit();
        if (cta < QN / 48) stage_rows(sbase + SM_WQ, P48, wq + cta * 48, QN * 2, DM, 6, tid);
        cp_async_commit();
#pragma unroll 1
        for (int r = 0; r < 2; ++r) {
            const int i = r ? i1 : tid;
            if (i < 320) {
                const uint4 cc = r ? c1 : c0, xx = r ? x1 : x0;
                const uint32_t cw[4] = {cc.x, cc.y, cc.z, cc.w}, xw[4] = {xx.x, xx.y, xx.z, xx.w};
                uint32_t ow[4];
#pragma unroll
                for (int k = 0; k < 4; ++k) {
                    const float a = bf_lo(cw[k]), b = bf_hi(cw[k]);
                    __nv_bfloat162 p = __floats2bfloat162_rn(__fdiv_rn(a, 1.0f + __expf(-a)), __fdiv_rn(b, 1.0f + __expf(-b)));
                    ow[k] = *(uint32_t*)&p;
                    s_xp[i * 8 + 2 * k] = bf_lo(xw[k]);
                    s_xp[i * 8 + 2 * k + 1] = bf_hi(xw[k]);
                }
                const int b = i / 80, c8 = i - b * 80;
                *(uint4*)(smem + SM_A + b * A_PITCH + c8 * 16) = make_uint4(ow[0], ow[1], ow[2], ow[3]);
            }
        }
    }
    if (cta == gridDim.x - 1) {
#pragma unroll 1
        for (int i = tid; i < NB * QN / 4; i += NCONS) ((float4*)g_o)[i] = make_float4(0.f, 0.f, 0.f, 0.f);
#pragma unroll 1
        for (int i = tid; i < NB * DM; i += NCONS) { g_attn[i] = 0.f; g_ffn[i] = 0.f; }
        if (tid < NBH) g_kcnt[tid] = 0u;
        if (tid == 0) g_kall = 0u;
    }
    cp_async_wait1();
    cons_sync();
    if (cta < MODN / 32) {
        gemv_mma(sbase + SM_W32 + warp * 80 * P32, P32, sbase + SM_A + warp * 160, 5, 4, s_part + warp * 320, lane);
        cons_sync();
        if (tid < 128) g_mod[(tid >> 5) * MODN + cta * 32 + (tid & 31)] = bf16r(tall_sum(s_part, tid >> 5, tid & 31));
    }
    PROF(1);
    grid_barrier(&g_bar[0], tid);
    PROF(2);

    if (cta < QN / 48) {
        if (warp < NB)
            ln_mod_row(s_xp + warp * DM, nullptr, nullptr, g_mod + warp * MODN, g_mod + warp * MODN + DM,
                       s_a + warp * (A_PITCH / 2), lane);
        cp_async_wait_all();
        cons_sync();
        gemv_mma(sbase + SM_WQ + warp * 80 * P48, P48, sbase + SM_A + warp * 160, 5, 6, s_part + warp * 320, lane);
        cons_sync();
        if (tid < 192) {
            const int b = tid / 48, n = tid - b * 48;
            g_q[b * QN + cta * 48 + n] = __float2bfloat16_rn(tall_sum(s_part, b, n));
        }
    }
    PROF(3);
    grid_barrier(&g_bar[1], tid);
    if (tid == 0) {
#pragma unroll 1
        for (int s = PRE; s < NST; ++s) mbar_arrive(bar_empty + s * 8);
    }
    if (cta < FF / 16) {
        stage_rows(sbase + SM_W32, P32, w_gate + cta * 16, FF * 2, DM, 2, tid);
        stage_rows(sbase + SM_W32 + 32, P32, w_up + cta * 16, FF * 2, DM, 2, tid);
    }
    PROF(4);

    {
        const int sub = lane & 7, grp = lane >> 3;
        for (int u0 = warp * TPI;; u0 += 8 * TPI) {
            stage_wait(bar_full, s_tag, u0);
            const int item = s_item[u0 % NST];
            if (item < 0) {
                __syncwarp();
                if (lane == 0) mbar_arrive(bar_empty + (u0 % NST) * 8);
                break;
            }
            const int bh = (item & (NITEM_K - 1)) / CHUNKS;
            if (item < NITEM_K) {
                float* gs = g_s + (size_t)item * ITEM_KEYS;
                float qr[24];
                {
                    const uint4* qp = (const uint4*)(smem + SM_RING + (u0 % NST) * STAGE_BYTES + TILE_BYTES) + sub;
#pragma unroll
                    for (int j = 0; j < 3; ++j) {
                        const uint4 v = qp[8 * j];
                        qr[j * 8 + 0] = bf_lo(v.x); qr[j * 8 + 1] = bf_hi(v.x);
                        qr[j * 8 + 2] = bf_lo(v.y); qr[j * 8 + 3] = bf_hi(v.y);
                        qr[j * 8 + 4] = bf_lo(v.z); qr[j * 8 + 5] = bf_hi(v.z);
                        qr[j * 8 + 6] = bf_lo(v.w); qr[j * 8 + 7] = bf_hi(v.w);
                    }
                }
                float m_run = -INFINITY, l_run = 0.f;
#pragma unroll 1
                for (int hh = 0; hh < 2 * TPI; ++hh) {
                    const int u = u0 + (hh >> 1), st = u % NST;
                    if (!(hh & 1)) stage_wait(bar_full, s_tag, u);
                    const uint4* tile = (const uint4*)(smem + SM_RING + st * STAGE_BYTES) + (hh & 1) * (32 * 24);
                    float part[8];
#pragma unroll
                    for (int it = 0; it < 8; ++it) {
                        const uint4* row = tile + (it * 4 + grp) * 24 + sub;
                        const uint4 a = row[0], b = row[8], c = row[16];
                        part[it] = dot8(a, qr) + dot8(b, qr + 8) + dot8(c, qr + 16);
                    }
                    if (hh & 1) {
                        __syncwarp();
                        if (lane == 0) mbar_arrive(bar_empty + st * 8);
                    }
#pragma unroll
                    for (int j = 0; j < 4; ++j) {
                        const float send = (sub & 4) ? part[j] : part[j + 4];
                        const float keep = (sub & 4) ? part[j + 4] : part[j];
                        part[j] = keep + __shfl_xor_sync(0xffffffffu, send, 4);
                    }
#pragma unroll
                    for (int j = 0; j < 2; ++j) {
                        const float send = (sub & 2) ? part[j] : part[j + 2];
                        const float keep = (sub & 2) ? part[j + 2] : part[j];
                        part[j] = keep + __shfl_xor_sync(0xffffffffu, send, 2);
                    }
                    {
                        const float send = (sub & 1) ? part[0] : part[1];
                        const float keep = (sub & 1) ? part[1] : part[0];
                        part[0] = keep + __shfl_xor_sync(0xffffffffu, send, 1);
                    }
                    const float s = bf16r(bf16r(part[0]) * 0.07216878364870323f);
                    gs[hh * 32 + sub * 4 + grp] = s;
                    const float m_new = fmaxf(m_run, s);
                    l_run = l_run * __expf(m_run - m_new) + __expf(s - m_new);
                    m_run = m_new;
                }
                const float m = warp_max(m_run);
                const float l = warp_sum(l_run * __expf(m_run - m));
                __syncwarp();
                if (lane == 0) {
                    g_stat[item] = make_float2(m, l);
                    red_release_add(&g_kcnt[bh], 1u);
                    red_release_add(&g_kall, 1u);
                }
            } else {
                float acc[3][8];
#pragma unroll
                for (int j = 0; j < 3; ++j)
#pragma unroll
                    for (int e = 0; e < 8; ++e) acc[j][e] = 0.f;
#pragma unroll 1
                for (int hh = 0; hh < 2 * TPI; ++hh) {
                    const int u = u0 + (hh >> 1), st = u % NST;
                    if (!(hh & 1)) stage_wait(bar_full, s_tag, u);
                    const uint4* tile = (const uint4*)(smem + SM_RING + st * STAGE_BYTES) + (hh & 1) * (32 * 24);
                    const float* aux = (const float*)(smem + SM_RING + st * STAGE_BYTES + TILE_BYTES);
                    const float2 st2 = *(const float2*)(aux + TILE_KEYS + 2 * lane);
                    const float mm = warp_max(st2.x);
                    const float ll = warp_sum(st2.y * __expf(st2.x - mm));
                    const float pl = bf16r(__fdiv_rn(__expf(aux[(hh & 1) * 32 + lane] - mm), ll));
#pragma unroll
                    for (int it = 0; it < 8; ++it) {
                        const uint4* row = tile + (it * 4 + grp) * 24 + sub;
                        const uint4 a = row[0], b = row[8], c = row[16];
                        const float p = __shfl_sync(0xffffffffu, pl, it * 4 + grp);
                        fma8(acc[0], a, p);
                        fma8(acc[1], b, p);
                        fma8(acc[2], c, p);
                    }
                    if (hh & 1) {
                        __syncwarp();
                        if (lane == 0) mbar_arrive(bar_empty + st * 8);
                    }
                }
                float* go = g_o + (bh >> 5) * QN + (bh & 31) * DH + sub * 8;
#pragma unroll
                for (int j = 0; j < 3; ++j) {
#pragma unroll
                    for (int e = 0; e < 8; ++e) {
                        float v = acc[j][e];
                        v += __shfl_xor_sync(0xffffffffu, v, 8);
                        v += __shfl_xor_sync(0xffffffffu, v, 16);
                        acc[j][e] = v;
                    }
                    if (grp == 0) {
                        red_add_v4(go + j * 64, acc[j][0], acc[j][1], acc[j][2], acc[j][3]);
                        red_add_v4(go + j * 64 + 4, acc[j][4], acc[j][5], acc[j][6], acc[j][7]);
                    }
                }
            }
        }
    }
    PROF(5);
    cons_sync();
    if (warp == 0) {
        asm volatile("fence.proxy.async.shared::cta;" ::: "memory");
        const int nrows = (cta < QN / 48 ? 48 : 0) + (cta < FF / 16 ? 16 : 0);
        if (lane == 0) mbar_expect_tx(bar_tail, nrows * DM * 2);
        __syncwarp();
#pragma unroll 1
        for (int r = lane; r < nrows; r += 32) {
            const __nv_bfloat16* src = r < 48 ? wo + ((size_t)cta * 48 + r) * DM : w_down + ((size_t)cta * 16 + r - 48) * DM;
            bulk_g2s(sbase + SM_WO + r * WIDE_PITCH, src, DM * 2, bar_tail);
        }
    }
    PROF(6);
    grid_barrier(&g_bar[2], tid);
    PROF(7);

    if (cta < QN / 48) {
        if (tid < 192) {
            const int b = tid / 48, n = tid - b * 48;
            s_a[b * (A_PITCH / 2) + n] = __float2bfloat16_rn(__ldcg(g_o + b * QN + cta * 48 + n));
        }
        mbar_wait(bar_tail, 0);
        cons_sync();
        gemv_mma(sbase + SM_WO + warp * 160, WIDE_PITCH, sbase + SM_A, 3, 10, s_part + warp * 320, lane);
        cons_sync();
        wide_flush(s_part, g_attn, tid);
    }
    PROF(8);
    grid_barrier(&g_bar[3], tid);
    PROF(9);

    if (cta < FF / 16) {
        if (warp < NB)
            ln_mod_row(s_xp + warp * DM, g_attn + warp * DM, g_mod + warp * MODN + 2 * DM, g_mod + warp * MODN + 3 * DM,
                       g_mod + warp * MODN + 4 * DM, s_a + warp * (A_PITCH / 2), lane);
        cp_async_wait_all();
        cons_sync();
        gemv_mma(sbase + SM_W32 + warp * 80 * P32, P32, sbase + SM_A + warp * 160, 5, 4, s_part + warp * 320, lane);
        cons_sync();
        if (tid < 64) {
            const int b = tid >> 4, n = tid & 15;
            const float g = bf16r(tall_sum(s_part, b, n));
            const float up = bf16r(tall_sum(s_part, b, 16 + n));
            s_a[b * (A_PITCH / 2) + n] = __float2bfloat16_rn(bf16r(gelu_tanh(g)) * up);
        }
        cons_sync();
        gemv_mma(sbase + SM_WD + warp * 160, WIDE_PITCH, sbase + SM_A, 1, 10, s_part + warp * 320, lane);
        cons_sync();
        wide_flush(s_part, g_ffn, tid);
    }
    PROF(10);
    cons_sync();
    if (tid == 0) {
        __threadfence();
        const unsigned int old = atomicAdd(&g_bar[4], 1u);
        s_item[0] = ((old % gridDim.x) == gridDim.x - 1) ? 1 : 0;
        __threadfence();
    }
    cons_sync();
    if (s_item[0] != 0) {
        float4 f[3], a[3], ga[3], gb[3];
#pragma unroll
        for (int r = 0; r < 3; ++r) {
            const int i = tid + r * NCONS;
            if (i < NB * DM / 4) {
                const int b = i / 160, c4 = i - b * 160;
                f[r] = __ldcg((const float4*)g_ffn + i);
                a[r] = __ldcg((const float4*)g_attn + i);
                ga[r] = __ldcg((const float4*)(g_mod + b * MODN + 2 * DM) + c4);
                gb[r] = __ldcg((const float4*)(g_mod + b * MODN + 5 * DM) + c4);
            }
        }
#pragma unroll
        for (int r = 0; r < 3; ++r) {
            const int i = tid + r * NCONS;
            if (i < NB * DM / 4) {
                const float4 x = *((const float4*)s_xp + i);
                const float o0 = bf16r(x.x + bf16r(ga[r].x * bf16r(a[r].x))) + bf16r(gb[r].x * bf16r(f[r].x));
                const float o1 = bf16r(x.y + bf16r(ga[r].y * bf16r(a[r].y))) + bf16r(gb[r].y * bf16r(f[r].y));
                const float o2 = bf16r(x.z + bf16r(ga[r].z * bf16r(a[r].z))) + bf16r(gb[r].z * bf16r(f[r].z));
                const float o3 = bf16r(x.w + bf16r(ga[r].w * bf16r(a[r].w))) + bf16r(gb[r].w * bf16r(f[r].w));
                __nv_bfloat162 p0 = __floats2bfloat162_rn(o0, o1), p1 = __floats2bfloat162_rn(o2, o3);
                uint2 u;
                u.x = *(uint32_t*)&p0; u.y = *(uint32_t*)&p1;
                *((uint2*)out + i) = u;
            }
        }
        if (tid == 0) g_work = 0u;
        PROF(11);
    }
}

}

extern "C" void kernel_launch(void* const* d_in, const int* in_sizes, int n_in, void* d_out, int out_size) {
    (void)in_sizes; (void)n_in; (void)out_size;
    const __nv_bfloat16* A_x = (const __nv_bfloat16*)d_in[0];
    const __nv_bfloat16* A_k = (const __nv_bfloat16*)d_in[1];
    const __nv_bfloat16* A_v = (const __nv_bfloat16*)d_in[2];
    const __nv_bfloat16* A_wq = (const __nv_bfloat16*)d_in[3];
    const __nv_bfloat16* A_wo = (const __nv_bfloat16*)d_in[4];
    const __nv_bfloat16* B_wg = (const __nv_bfloat16*)d_in[6];
    const __nv_bfloat16* B_wu = (const __nv_bfloat16*)d_in[7];
    const __nv_bfloat16* B_wd = (const __nv_bfloat16*)d_in[8];
    const __nv_bfloat16* c = (const __nv_bfloat16*)d_in[9];
    const __nv_bfloat16* w_mod = (const __nv_bfloat16*)d_in[10];
    static int grid = 0;
    if (grid == 0) {
        cudaFuncSetAttribute(decode_block_kernel, cudaFuncAttributeMaxDynamicSharedMemorySize, SM_TOTAL);
        int dev = 0, sms = 0;
        cudaGetDevice(&dev);
        cudaDeviceGetAttribute(&sms, cudaDevAttrMultiProcessorCount, dev);
        grid = sms < 132 ? sms : 132;
    }
    decode_block_kernel<<<grid, NTHREADS, SM_TOTAL>>>(A_x, A_k, A_v, A_wq, A_wo, B_wg, B_wu, B_wd, c, w_mod,
                                                      (__nv_bfloat16*)d_out);
}
```

```cpp
#include <cuda_runtime.h>
#include <cuda_bf16.h>
#include <stdint.h>

namespace {

constexpr int NB = 4;
constexpr int DM = 640;
constexpr int NH = 32;
constexpr int SK = 4096;
constexpr int DH = 192;
constexpr int FF = 1536;
constexpr int MODN = 6 * DM;
constexpr int QN = NH * DH;
constexpr int NBH = NB * NH;

constexpr int NCONS = 256;
constexpr int NTHREADS = NCONS + 32;
constexpr int TILE_KEYS = 64;
constexpr int TILE_BYTES = TILE_KEYS * DH * 2;
constexpr int STAGE_BYTES = TILE_BYTES;
constexpr int NST = 6;
constexpr int PRE = 3;
constexpr int TPI = 2;
constexpr int ITEM_KEYS = TPI * TILE_KEYS;
constexpr int CHUNKS = SK / ITEM_KEYS;
constexpr int NITEM_K = NBH * CHUNKS;
constexpr int NITEM = 2 * NITEM_K;

constexpr int A_PITCH = 1296;
constexpr int ACT_PITCH = FF * 2 + 16;
constexpr int P32 = 80;
constexpr int P48 = 112;
constexpr int P80 = 176;
constexpr int WO_ROWS = 384;

constexpr int SM_RING = 0;
constexpr int SM_WQ = PRE * STAGE_BYTES;
constexpr int SM_WO = 0;
constexpr int SM_WD = SM_WO + WO_ROWS * P80;
constexpr int SM_ACT = SM_WD + FF * 16;
constexpr int SM_W32 = NST * STAGE_BYTES;
constexpr int SM_A = SM_W32 + DM * P32;
constexpr int SM_PART = SM_A + NB * A_PITCH;
constexpr int SM_XP = SM_PART + 8 * 4 * 80 * 4;
constexpr int SM_RED = SM_XP + NB * DM * 4;
constexpr int SM_ITEM = SM_RED + 16 * 4;
constexpr int SM_TAG = SM_ITEM + 16 * 4;
constexpr int SM_BAR = SM_TAG + 16 * 4;
constexpr int SM_TOTAL = SM_BAR + (2 * NST + 1) * 8;
static_assert(SM_WQ + DM * P48 <= NST * STAGE_BYTES, "prologue overlay");
static_assert(SM_ACT + NB * ACT_PITCH <= NST * STAGE_BYTES, "tail overlay");
static_assert(SM_TOTAL <= 232448, "smem");
#define PSTART 0

__device__ __align__(128) float g_mod[NB * MODN];
__device__ __align__(128) __nv_bfloat16 g_q[NB * QN];
__device__ __align__(128) float g_s[NBH * SK];
__device__ __align__(128) float2 g_stat[NBH * CHUNKS];
__device__ __align__(128) unsigned int g_kcnt[NBH];
__device__ __align__(128) float g_o[NB * QN];
__device__ __align__(128) float g_attn[NB * DM];
__device__ __align__(128) __nv_bfloat16 g_act[NB * FF];
__device__ __align__(128) unsigned int g_bar[8];
__device__ unsigned int g_work;
__device__ unsigned int g_kall;

#define PROF(k) do { } while (0)
#define PROFP(k) do { } while (0)

__device__ __forceinline__ float bf16r(float x) { return __bfloat162float(__float2bfloat16_rn(x)); }
__device__ __forceinline__ float bf_lo(uint32_t u) { return __uint_as_float(u << 16); }
__device__ __forceinline__ float bf_hi(uint32_t u) { return __uint_as_float(u & 0xffff0000u); }

__device__ __forceinline__ uint32_t smem_u32(const void* p) { return (uint32_t)__cvta_generic_to_shared(p); }
__device__ __forceinline__ void mbar_init(uint32_t bar, uint32_t count) {
    asm volatile("mbarrier.init.shared::cta.b64 [%0], %1;" ::"r"(bar), "r"(count) : "memory");
}
__device__ __forceinline__ void mbar_expect_tx(uint32_t bar, uint32_t bytes) {
    asm volatile("mbarrier.arrive.expect_tx.shared::cta.b64 _, [%0], %1;" ::"r"(bar), "r"(bytes) : "memory");
}
__device__ __forceinline__ void mbar_arrive(uint32_t bar) {
    asm volatile("mbarrier.arrive.shared::cta.b64 _, [%0];" ::"r"(bar) : "memory");
}
constexpr long long WAIT_LIMIT_CYCLES = 200000000LL;
__device__ __forceinline__ uint32_t mbar_try(uint32_t bar, uint32_t parity) {
    uint32_t done;
    asm volatile(
        "{\n\t.reg .pred p;\n\t"
        "mbarrier.try_wait.parity.shared::cta.b64 p, [%1], %2;\n\t"
        "selp.u32 %0, 1, 0, p;\n\t}"
        : "=r"(done) : "r"(bar), "r"(parity) : "memory");
    return done;
}
__device__ __noinline__ void mbar_wait_slow(uint32_t bar, uint32_t parity) {
    const long long t0 = clock64();
    while (!mbar_try(bar, parity)) {
        if (clock64() - t0 > WAIT_LIMIT_CYCLES) __trap();
    }
}
__device__ __forceinline__ void mbar_wait(uint32_t bar, uint32_t parity) {
    if (!mbar_try(bar, parity)) mbar_wait_slow(bar, parity);
}
__device__ __noinline__ void tag_wait_slow(volatile int* tag, int u) {
    const long long t0 = clock64();
    while (*tag != u) {
        __nanosleep(32);
        if (clock64() - t0 > WAIT_LIMIT_CYCLES) __trap();
    }
}
__device__ __forceinline__ void stage_wait(uint32_t bar_full, volatile int* s_tag, int u) {
    const int st = u % NST;
    if (s_tag[st] != u) tag_wait_slow(s_tag + st, u);
    mbar_wait(bar_full + st * 8, (u / NST) & 1);
}
__device__ __forceinline__ void bulk_g2s(uint32_t dst, const void* src, uint32_t bytes, uint32_t bar) {
    asm volatile(
        "cp.async.bulk.shared::cluster.global.mbarrier::complete_tx::bytes [%0], [%1], %2, [%3];"
        ::"r"(dst), "l"(src), "r"(bytes), "r"(bar) : "memory");
}
__device__ __forceinline__ void cp_async16(uint32_t dst, const void* src) {
    asm volatile("cp.async.cg.shared.global [%0], [%1], 16;" ::"r"(dst), "l"(src) : "memory");
}
__device__ __forceinline__ void cp_async_wait_all() { asm volatile("cp.async.wait_all;" ::: "memory"); }
__device__ __forceinline__ void cp_async_commit() { asm volatile("cp.async.commit_group;" ::: "memory"); }
__device__ __forceinline__ void cp_async_wait1() { asm volatile("cp.async.wait_group 1;" ::: "memory"); }
__device__ __forceinline__ void red_release_add(unsigned int* p, unsigned int v) {
    asm volatile("red.release.gpu.global.add.u32 [%0], %1;" ::"l"(p), "r"(v) : "memory");
}
__device__ __forceinline__ void cons_sync() { asm volatile("bar.sync 1, 256;" ::: "memory"); }

__device__ __forceinline__ void red_add_v4(float* p, float a, float b, float c, float d) {
    asm volatile("red.global.add.v4.f32 [%0], {%1, %2, %3, %4};" ::"l"(p), "f"(a), "f"(b), "f"(c), "f"(d) : "memory");
}
__device__ __forceinline__ unsigned int ld_acquire(const unsigned int* p) {
    unsigned int v;
    asm volatile("ld.acquire.gpu.global.u32 %0, [%1];" : "=r"(v) : "l"(p) : "memory");
    return v;
}

__device__ __forceinline__ void grid_arrive(unsigned int* ctr, int tid) {
    cons_sync();
    if (tid == 0) red_release_add(ctr, 1u);
}
__device__ __noinline__ void grid_wait(const unsigned int* ctr, unsigned int target, int tid) {
    if (tid == 0) {
        const long long t0 = clock64();
        while ((int)(ld_acquire(ctr) - target) < 0) {
            if (clock64() - t0 > WAIT_LIMIT_CYCLES) __trap();
        }
    }
    cons_sync();
}

__device__ __forceinline__ float warp_sum(float v) {
#pragma unroll
    for (int o = 16; o > 0; o >>= 1) v += __shfl_xor_sync(0xffffffffu, v, o);
    return v;
}
__device__ __forceinline__ float warp_max(float v) {
#pragma unroll
    for (int o = 16; o > 0; o >>= 1) v = fmaxf(v, __shfl_xor_sync(0xffffffffu, v, o));
    return v;
}

__device__ __forceinline__ void fma8(float (&acc)[8], const uint4& w, float s) {
    acc[0] = fmaf(s, bf_lo(w.x), acc[0]);
    acc[1] = fmaf(s, bf_hi(w.x), acc[1]);
    acc[2] = fmaf(s, bf_lo(w.y), acc[2]);
    acc[3] = fmaf(s, bf_hi(w.y), acc[3]);
    acc[4] = fmaf(s, bf_lo(w.z), acc[4]);
    acc[5] = fmaf(s, bf_hi(w.z), acc[5]);
    acc[6] = fmaf(s, bf_lo(w.w), acc[6]);
    acc[7] = fmaf(s, bf_hi(w.w), acc[7]);
}
__device__ __forceinline__ float dot8(const uint4& w, const float* q) {
    float s = q[0] * bf_lo(w.x);
    s = fmaf(q[1], bf_hi(w.x), s);
    s = fmaf(q[2], bf_lo(w.y), s);
    s = fmaf(q[3], bf_hi(w.y), s);
    s = fmaf(q[4], bf_lo(w.z), s);
    s = fmaf(q[5], bf_hi(w.z), s);
    s = fmaf(q[6], bf_lo(w.w), s);
    s = fmaf(q[7], bf_hi(w.w), s);
    return s;
}

__device__ __noinline__ void stage_rows(uint32_t dst, int dst_pitch, const void* src, int src_stride, int rows,
                                        int cpr, int tid) {
    const int n = rows * cpr;
#pragma unroll 1
    for (int i = tid; i < n; i += NCONS) {
        const int r = i / cpr, c = i - r * cpr;
        cp_async16(dst + r * dst_pitch + c * 16, (const unsigned char*)src + (size_t)r * src_stride + c * 16);
    }
}

__device__ __noinline__ void gemv_mma(uint32_t w, int w_pitch, uint32_t a, int a_pitch, int ksteps, int ntiles,
                                      float* part, int lane) {
    float c[10][4];
#pragma unroll
    for (int nt = 0; nt < 10; ++nt) { c[nt][0] = 0.f; c[nt][1] = 0.f; c[nt][2] = 0.f; c[nt][3] = 0.f; }
    uint32_t ap = a + (lane >> 2) * a_pitch + (lane & 3) * 4;
    uint32_t wp = w + (lane & 15) * w_pitch;
    for (int ks = 0; ks < ksteps; ++ks) {
        uint32_t a0 = 0, a2 = 0;
        if (lane < 16) {
            asm volatile("ld.shared.u32 %0, [%1];" : "=r"(a0) : "r"(ap));
            asm volatile("ld.shared.u32 %0, [%1];" : "=r"(a2) : "r"(ap + 16));
        }
#pragma unroll
        for (int nt = 0; nt < 10; ++nt) {
            if (nt < ntiles) {
                uint32_t b0, b1;
                asm volatile("ldmatrix.sync.aligned.m8n8.x2.trans.shared.b16 {%0, %1}, [%2];"
                             : "=r"(b0), "=r"(b1) : "r"(wp + nt * 16));
                asm volatile(
                    "mma.sync.aligned.m16n8k16.row.col.f32.bf16.bf16.f32 {%0, %1, %2, %3}, {%4, %5, %6, %7}, "
                    "{%8, %9}, {%0, %1, %2, %3};"
                    : "+f"(c[nt][0]), "+f"(c[nt][1]), "+f"(c[nt][2]), "+f"(c[nt][3])
                    : "r"(a0), "r"(0u), "r"(a2), "r"(0u), "r"(b0), "r"(b1));
            }
        }
        ap += 32;
        wp += 16 * w_pitch;
    }
    if (lane < 16) {
        float* pp = part + (lane >> 2) * 80 + (lane & 3) * 2;
#pragma unroll
        for (int nt = 0; nt < 10; ++nt)
            if (nt < ntiles) *(float2*)(pp + nt * 8) = make_float2(c[nt][0], c[nt][1]);
    }
}

__device__ __forceinline__ float tall_sum(const float* part, int b, int n) {
    float s = 0.f;
#pragma unroll
    for (int w = 0; w < 8; ++w) s += part[(w * 4 + b) * 80 + n];
    return s;
}

__device__ __noinline__ void ln_norm(float (&v)[10], float* s_red, int tid) {
    const int warp = tid >> 5;
    float s = 0.f;
#pragma unroll
    for (int i = 0; i < 10; ++i) s += v[i];
    s = warp_sum(s);
    if ((tid & 31) == 0) s_red[warp] = s;
    cons_sync();
    const float mean_f = (s_red[warp & 6] + s_red[warp | 1]) * (1.0f / DM);
    float q = 0.f;
#pragma unroll
    for (int i = 0; i < 10; ++i) { const float d = v[i] - mean_f; q = fmaf(d, d, q); }
    q = warp_sum(q);
    if ((tid & 31) == 0) s_red[8 + warp] = q;
    cons_sync();
    const float var = (s_red[8 + (warp & 6)] + s_red[8 + (warp | 1)]) * (1.0f / DM);
    const float mean = bf16r(mean_f);
    const float den = bf16r(sqrtf(bf16r(bf16r(var) + 1e-5f)));
#pragma unroll
    for (int i = 0; i < 10; ++i) v[i] = bf16r(__fdiv_rn(bf16r(v[i] - mean), den));
}
__device__ __forceinline__ void modulate(const float (&n)[10], const float2 (&sh)[5], const float2 (&sc)[5], uint32_t* dst) {
#pragma unroll
    for (int i = 0; i < 5; ++i) {
        const float h0 = bf16r(n[2 * i] * bf16r(1.0f + sc[i].x)) + sh[i].x;
        const float h1 = bf16r(n[2 * i + 1] * bf16r(1.0f + sc[i].y)) + sh[i].y;
        __nv_bfloat162 p = __floats2bfloat162_rn(h0, h1);
        dst[i] = *(uint32_t*)&p;
    }
}

__device__ __forceinline__ float gelu_tanh(float x) {
    const float kBeta = 0.7978845608028654f;
    const float inner = kBeta * (x + 0.044715f * x * x * x);
    return 0.5f * x * (1.0f + tanhf(inner));
}

__global__ void __launch_bounds__(NTHREADS, 1)
decode_block_kernel(const __nv_bfloat16* __restrict__ x_in, const __nv_bfloat16* __restrict__ k_cache,
                    const __nv_bfloat16* __restrict__ v_cache, const __nv_bfloat16* __restrict__ wq,
                    const __nv_bfloat16* __restrict__ wo, const __nv_bfloat16* __restrict__ w_gate,
                    const __nv_bfloat16* __restrict__ w_up, const __nv_bfloat16* __restrict__ w_down,
                    const __nv_bfloat16* __restrict__ cvec, const __nv_bfloat16* __restrict__ w_mod,
                    __nv_bfloat16* __restrict__ out) {
    extern __shared__ __align__(128) unsigned char smem[];
    const int tid = threadIdx.x;
    const int cta = blockIdx.x;

    const uint32_t sbase = smem_u32(smem);
    const uint32_t bar_full = sbase + SM_BAR;
    const uint32_t bar_empty = bar_full + NST * 8;
    volatile int* s_item = (volatile int*)(smem + SM_ITEM);
    volatile int* s_tag = (volatile int*)(smem + SM_TAG);

    const uint32_t bar_go = bar_empty + NST * 8;
    if (tid < NST) s_tag[tid] = -1;
    if (tid == 0) {
#pragma unroll 1
        for (int s = 0; s < 2 * NST + 1; ++s) mbar_init(bar_full + s * 8, 1);
        asm volatile("fence.mbarrier_init.release.cluster;" ::: "memory");
        asm volatile("fence.proxy.async.shared::cta;" ::: "memory");
#pragma unroll 1
        for (int s = 0; s < PRE; ++s) mbar_arrive(bar_empty + s * 8);
    }
    __syncthreads();

    if (tid >= NCONS) {
        if (tid == NCONS) {
            int u = 0;
            bool pf = false, kdone = false;
            const int G = (int)gridDim.x;
            auto produce = [&](const int item) {
                const int it = item & (NITEM_K - 1);
                const bool is_v = item >= NITEM_K;
                const unsigned char* src = (const unsigned char*)(is_v ? v_cache : k_cache) + (size_t)it * (ITEM_KEYS * DH * 2);
                if (is_v && !kdone) {
                    if (ld_acquire(&g_kall) == NITEM_K) {
                        kdone = true;
                    } else {
                        const long long t0 = clock64();
                        while (ld_acquire(&g_kcnt[it / CHUNKS]) < CHUNKS)
                            if (clock64() - t0 > WAIT_LIMIT_CYCLES) __trap();
                    }
                }
#pragma unroll 1
                for (int t = 0; t < TPI; ++t, ++u) {
                    const int st = u % NST;
                    const uint32_t fb = bar_full + st * 8;
                    mbar_wait(bar_empty + st * 8, (u / NST) & 1);
                    s_item[st] = item;
                    s_tag[st] = u;
                    mbar_expect_tx(fb, TILE_BYTES);
                    bulk_g2s(sbase + SM_RING + st * STAGE_BYTES, src + t * TILE_BYTES, TILE_BYTES, fb);
                }
                if (!pf && item >= NITEM - 10 * G) {
                    pf = true;
                    if (cta < QN / 48)
                        asm volatile("cp.async.bulk.prefetch.L2.global [%0], %1;" ::"l"(wo + (size_t)cta * 48 * DM), "r"(48 * DM * 2) : "memory");
                    if (cta < FF / 16)
                        asm volatile("cp.async.bulk.prefetch.L2.global [%0], %1;" ::"l"(w_down + (size_t)cta * 16 * DM), "r"(16 * DM * 2) : "memory");
                }
            };
            mbar_wait(bar_go, 0);
            unsigned int r0 = cta - 3 * G, r1 = cta - 2 * G, r2 = cta - G;
#pragma unroll 1
            for (;;) {
                if ((int)(r0 + 3 * G) >= NITEM) break;
                produce((int)(r0 + 3 * G));
                r0 = atomicAdd(&g_work, 1u);
                if ((int)(r1 + 3 * G) >= NITEM) break;
                produce((int)(r1 + 3 * G));
                r1 = atomicAdd(&g_work, 1u);
                if ((int)(r2 + 3 * G) >= NITEM) break;
                produce((int)(r2 + 3 * G));
                r2 = atomicAdd(&g_work, 1u);
            }
            s_item[15] = (int)(r0 + r1 + r2);
#pragma unroll 1
            for (int j = 0; j < 8; ++j, u += TPI) {
                const int st = u % NST;
                mbar_wait(bar_empty + st * 8, (u / NST) & 1);
                s_item[st] = -1;
                s_tag[st] = u;
                mbar_arrive(bar_full + st * 8);
            }
            PROFP(13);
        }
        return;
    }

    const int lane = tid & 31, warp = tid >> 5;
    float* s_part = (float*)(smem + SM_PART);
    float* s_xp = (float*)(smem + SM_XP);
    float* s_red = (float*)(smem + SM_RED);
    __nv_bfloat16* s_a = (__nv_bfloat16*)(smem + SM_A);
    const int lrow = tid >> 6, lcol = (tid & 63) * 10;
    uint32_t* h_dst = (uint32_t*)(smem + SM_A + lrow * A_PITCH + lcol * 2);

    PROF(0);
    unsigned int target = 0;
    if (tid == 0) target = ld_acquire(&g_bar[1]) + gridDim.x;
    float nv[10];
    {
        const int i1 = tid + NCONS;
        const uint4 c0 = __ldg((const uint4*)cvec + tid);
        uint4 c1 = c0;
        if (i1 < 320) c1 = __ldg((const uint4*)cvec + i1);
        uint32_t xw[5];
#pragma unroll
        for (int i = 0; i < 5; ++i) xw[i] = __ldg((const uint32_t*)(x_in + lrow * DM + lcol) + i);
        if (cta < MODN / 32) stage_rows(sbase + SM_W32, P32, w_mod + cta * 32, MODN * 2, DM, 4, tid);
#pragma unroll 1
        for (int r = 0; r < 2; ++r) {
            const int i = r ? i1 : tid;
            if (i < 320) {
                const uint4 cc = r ? c1 : c0;
                const uint32_t cw[4] = {cc.x, cc.y, cc.z, cc.w};
                uint32_t ow[4];
#pragma unroll
                for (int k = 0; k < 4; ++k) {
                    const float a = bf_lo(cw[k]), b = bf_hi(cw[k]);
                    __nv_bfloat162 p = __floats2bfloat162_rn(__fdiv_rn(a, 1.0f + __expf(-a)), __fdiv_rn(b, 1.0f + __expf(-b)));
                    ow[k] = *(uint32_t*)&p;
                }
                const int b = i / 80, c8 = i - b * 80;
                *(uint4*)(smem + SM_A + b * A_PITCH + c8 * 16) = make_uint4(ow[0], ow[1], ow[2], ow[3]);
            }
        }
#pragma unroll
        for (int i = 0; i < 5; ++i) {
            nv[2 * i] = bf_lo(xw[i]);
            nv[2 * i + 1] = bf_hi(xw[i]);
            *(float2*)(s_xp + lrow * DM + lcol + 2 * i) = make_float2(nv[2 * i], nv[2 * i + 1]);
        }
    }
    if (cta == gridDim.x - 1) {
#pragma unroll 1
        for (int i = tid; i < NB * QN / 4; i += NCONS) ((float4*)g_o)[i] = make_float4(0.f, 0.f, 0.f, 0.f);
#pragma unroll 1
        for (int i = tid; i < NB * DM; i += NCONS) g_attn[i] = 0.f;
        if (tid < NBH) g_kcnt[tid] = 0u;
        if (tid == 0) g_kall = 0u;
    }
    ln_norm(nv, s_red, tid);
    cp_async_wait_all();
    cons_sync();
    if (PSTART == 0 && tid == 0) mbar_arrive(bar_go);
    if (cta < MODN / 32) {
        gemv_mma(sbase + SM_W32 + warp * 80 * P32, P32, sbase + SM_A + warp * 160, A_PITCH, 5, 4, s_part + warp * 320, lane);
        cons_sync();
        if (tid < 128) g_mod[(tid >> 5) * MODN + cta * 32 + (tid & 31)] = bf16r(tall_sum(s_part, tid >> 5, tid & 31));
    }
    PROF(1);
    grid_arrive(&g_bar[0], tid);
    if (cta < QN / 48) stage_rows(sbase + SM_WQ, P48, wq + cta * 48, QN * 2, DM, 6, tid);
    grid_wait(&g_bar[0], target, tid);
    if (PSTART == 1 && tid == 0) mbar_arrive(bar_go);
    PROF(2);

    if (cta < QN / 48) {
        float2 sh[5], sc[5];
#pragma unroll
        for (int i = 0; i < 5; ++i) {
            sh[i] = __ldcg((const float2*)(g_mod + lrow * MODN + lcol) + i);
            sc[i] = __ldcg((const float2*)(g_mod + lrow * MODN + DM + lcol) + i);
        }
        modulate(nv, sh, sc, h_dst);
        cp_async_wait_all();
        cons_sync();
        if (PSTART == 2 && tid == 0) mbar_arrive(bar_go);
        gemv_mma(sbase + SM_WQ + warp * 80 * P48, P48, sbase + SM_A + warp * 160, A_PITCH, 5, 6, s_part + warp * 320, lane);
        cons_sync();
        if (tid < 192) {
            const int b = tid / 48, n = tid - b * 48;
            g_q[b * QN + cta * 48 + n] = __float2bfloat16_rn(tall_sum(s_part, b, n));
        }
    } else if (PSTART == 2 && tid == 0) {
        mbar_arrive(bar_go);
    }
    PROF(3);
    grid_arrive(&g_bar[1], tid);
    if (tid == 0) {
#pragma unroll 1
        for (int s = PRE; s < NST; ++s) mbar_arrive(bar_empty + s * 8);
    }
    if (cta < FF / 16) {
        stage_rows(sbase + SM_W32, P32, w_gate + cta * 16, FF * 2, DM, 2, tid);
        stage_rows(sbase + SM_W32 + 32, P32, w_up + cta * 16, FF * 2, DM, 2, tid);
    }
    grid_wait(&g_bar[1], target, tid);
    PROF(4);

    {
        const int sub = lane & 7, grp = lane >> 3;
        for (int u0 = warp * TPI;; u0 += 8 * TPI) {
            if (s_tag[u0 % NST] != u0) tag_wait_slow(s_tag + u0 % NST, u0);
            const int item = s_item[u0 % NST];
            if (item < 0) {
                mbar_wait(bar_full + (u0 % NST) * 8, (u0 / NST) & 1);
                __syncwarp();
                if (lane == 0) mbar_arrive(bar_empty + (u0 % NST) * 8);
                break;
            }
            const int bh = (item & (NITEM_K - 1)) / CHUNKS;
            if (item < NITEM_K) {
                float* gs = g_s + (size_t)item * ITEM_KEYS;
                float qr[24];
                {
                    const uint4* qp = (const uint4*)(g_q + (bh >> 5) * QN + (bh & 31) * DH) + sub;
#pragma unroll
                    for (int j = 0; j < 3; ++j) {
                        const uint4 v = __ldcg(qp + 8 * j);
                        qr[j * 8 + 0] = bf_lo(v.x); qr[j * 8 + 1] = bf_hi(v.x);
                        qr[j * 8 + 2] = bf_lo(v.y); qr[j * 8 + 3] = bf_hi(v.y);
                        qr[j * 8 + 4] = bf_lo(v.z); qr[j * 8 + 5] = bf_hi(v.z);
                        qr[j * 8 + 6] = bf_lo(v.w); qr[j * 8 + 7] = bf_hi(v.w);
                    }
                }
                float m_run = -INFINITY, l_run = 0.f;
#pragma unroll 1
                for (int hh = 0; hh < 2 * TPI; ++hh) {
                    const int u = u0 + (hh >> 1), st = u % NST;
                    if (!(hh & 1)) stage_wait(bar_full, s_tag, u);
                    const uint4* tile = (const uint4*)(smem + SM_RING + st * STAGE_BYTES) + (hh & 1) * (32 * 24);
                    float part[8];
#pragma unroll
                    for (int it = 0; it < 8; ++it) {
                        const uint4* row = tile + (it * 4 + grp) * 24 + sub;
                        const uint4 a = row[0], b = row[8], c = row[16];
                        part[it] = dot8(a, qr) + dot8(b, qr + 8) + dot8(c, qr + 16);
                    }
                    if (hh & 1) {
                        __syncwarp();
                        if (lane == 0) mbar_arrive(bar_empty + st * 8);
                    }
#pragma unroll
                    for (int j = 0; j < 4; ++j) {
                        const float send = (sub & 4) ? part[j] : part[j + 4];
                        const float keep = (sub & 4) ? part[j + 4] : part[j];
                        part[j] = keep + __shfl_xor_sync(0xffffffffu, send, 4);
                    }
#pragma unroll
                    for (int j = 0; j < 2; ++j) {
                        const float send = (sub & 2) ? part[j] : part[j + 2];
                        const float keep = (sub & 2) ? part[j + 2] : part[j];
                        part[j] = keep + __shfl_xor_sync(0xffffffffu, send, 2);
                    }
                    {
                        const float send = (sub & 1) ? part[0] : part[1];
                        const float keep = (sub & 1) ? part[1] : part[0];
                        part[0] = keep + __shfl_xor_sync(0xffffffffu, send, 1);
                    }
                    const float s = bf16r(bf16r(part[0]) * 0.07216878364870323f);
                    gs[hh * 32 + sub * 4 + grp] = s;
                    const float m_new = fmaxf(m_run, s);
                    l_run = l_run * __expf(m_run - m_new) + __expf(s - m_new);
                    m_run = m_new;
                }
                const float m = warp_max(m_run);
                const float l = warp_sum(l_run * __expf(m_run - m));
                __syncwarp();
                if (lane == 0) {
                    g_stat[item] = make_float2(m, l);
                    red_release_add(&g_kcnt[bh], 1u);
                    red_release_add(&g_kall, 1u);
                }
            } else {
                float pr[2 * TPI];
                {
                    const float* gs = g_s + (size_t)(item - NITEM_K) * ITEM_KEYS + lane;
                    const float2 st2 = __ldcg(g_stat + bh * CHUNKS + lane);
#pragma unroll
                    for (int hh = 0; hh < 2 * TPI; ++hh) pr[hh] = __ldcg(gs + hh * 32);
                    const float mm = warp_max(st2.x);
                    const float ll = warp_sum(st2.y * __expf(st2.x - mm));
#pragma unroll
                    for (int hh = 0; hh < 2 * TPI; ++hh) pr[hh] = bf16r(__fdiv_rn(__expf(pr[hh] - mm), ll));
                }
                float acc[3][8];
#pragma unroll
                for (int j = 0; j < 3; ++j)
#pragma unroll
                    for (int e = 0; e < 8; ++e) acc[j][e] = 0.f;
#pragma unroll
                for (int hh = 0; hh < 2 * TPI; ++hh) {
                    const int u = u0 + (hh >> 1), st = u % NST;
                    if (!(hh & 1)) stage_wait(bar_full, s_tag, u);
                    const uint4* tile = (const uint4*)(smem + SM_RING + st * STAGE_BYTES) + (hh & 1) * (32 * 24);
#pragma unroll
                    for (int it = 0; it < 8; ++it) {
                        const uint4* row = tile + (it * 4 + grp) * 24 + sub;
                        const uint4 a = row[0], b = row[8], c = row[16];
                        const float p = __shfl_sync(0xffffffffu, pr[hh], it * 4 + grp);
                        fma8(acc[0], a, p);
                        fma8(acc[1], b, p);
                        fma8(acc[2], c, p);
                    }
                    if (hh & 1) {
                        __syncwarp();
                        if (lane == 0) mbar_arrive(bar_empty + st * 8);
                    }
                }
                float* go = g_o + (bh >> 5) * QN + (bh & 31) * DH + sub * 8;
#pragma unroll
                for (int j = 0; j < 3; ++j) {
#pragma unroll
                    for (int e = 0; e < 8; ++e) {
                        float v = acc[j][e];
                        v += __shfl_xor_sync(0xffffffffu, v, 8);
                        v += __shfl_xor_sync(0xffffffffu, v, 16);
                        acc[j][e] = v;
                    }
                    if (grp == 0) {
                        red_add_v4(go + j * 64, acc[j][0], acc[j][1], acc[j][2], acc[j][3]);
                        red_add_v4(go + j * 64 + 4, acc[j][4], acc[j][5], acc[j][6], acc[j][7]);
                    }
                }
            }
        }
    }
    PROF(5);
    grid_arrive(&g_bar[2], tid);
    PROF(6);
    const int ks = cta >> 3, ns = cta & 7;
    if (cta < 128) stage_rows(sbase + SM_WO, P80, wo + (size_t)ks * WO_ROWS * DM + ns * 80, DM * 2, WO_ROWS, 10, tid);
    if (cta < DM / 8) stage_rows(sbase + SM_WD, 16, w_down + cta * 8, DM * 2, FF, 1, tid);
    grid_wait(&g_bar[2], target, tid);
    if (cta == 0 && tid == 0) g_work = 0u;
    PROF(7);

    if (cta < 128) {
#pragma unroll
        for (int r = 0; r < 2; ++r) {
            const int i = tid + r * NCONS;
            if (i < NB * WO_ROWS / 4) {
                const int b = i / 96, c4 = i - b * 96;
                const float4 v = __ldcg((const float4*)(g_o + b * QN + ks * WO_ROWS) + c4);
                __nv_bfloat162 p0 = __floats2bfloat162_rn(v.x, v.y), p1 = __floats2bfloat162_rn(v.z, v.w);
                uint2 w2;
                w2.x = *(uint32_t*)&p0; w2.y = *(uint32_t*)&p1;
                *(uint2*)(smem + SM_A + b * A_PITCH + c4 * 8) = w2;
            }
        }
        cp_async_wait_all();
        cons_sync();
        gemv_mma(sbase + SM_WO + warp * 48 * P80, P80, sbase + SM_A + warp * 96, A_PITCH, 3, 10, s_part + warp * 320, lane);
        cons_sync();
        if (tid < 80) {
            const int b = tid / 20, n4 = tid - b * 20;
            float4 s4 = make_float4(0.f, 0.f, 0.f, 0.f);
#pragma unroll
            for (int w = 0; w < 8; ++w) {
                const float4 v = *(const float4*)(s_part + (w * 4 + b) * 80 + n4 * 4);
                s4.x += v.x; s4.y += v.y; s4.z += v.z; s4.w += v.w;
            }
            red_add_v4(g_attn + b * DM + ns * 80 + n4 * 4, s4.x, s4.y, s4.z, s4.w);
        }
    }
    PROF(8);
    grid_arrive(&g_bar[3], tid);
    if (cta >= FF / 16) {
        if (tid == 0) red_release_add(&g_bar[4], 1u);
        return;
    }
    float gb = 0.f;
    {
        float2 ga[5], sh[5], sc[5];
#pragma unroll
        for (int i = 0; i < 5; ++i) {
            ga[i] = __ldcg((const float2*)(g_mod + lrow * MODN + 2 * DM + lcol) + i);
            sh[i] = __ldcg((const float2*)(g_mod + lrow * MODN + 3 * DM + lcol) + i);
            sc[i] = __ldcg((const float2*)(g_mod + lrow * MODN + 4 * DM + lcol) + i);
        }
        if (tid < 32 && cta < DM / 8) gb = __ldcg(g_mod + (tid >> 3) * MODN + 5 * DM + cta * 8 + (tid & 7));
        grid_wait(&g_bar[3], target, tid);
        PROF(9);
#pragma unroll
        for (int i = 0; i < 5; ++i) {
            const float2 av = __ldcg((const float2*)(g_attn + lrow * DM + lcol) + i);
            float2* xp = (float2*)(s_xp + lrow * DM + lcol) + i;
            const float2 xv = *xp;
            nv[2 * i] = bf16r(xv.x + bf16r(ga[i].x * bf16r(av.x)));
            nv[2 * i + 1] = bf16r(xv.y + bf16r(ga[i].y * bf16r(av.y)));
            *xp = make_float2(nv[2 * i], nv[2 * i + 1]);
        }
        ln_norm(nv, s_red, tid);
        modulate(nv, sh, sc, h_dst);
        cons_sync();
        gemv_mma(sbase + SM_W32 + warp * 80 * P32, P32, sbase + SM_A + warp * 160, A_PITCH, 5, 4, s_part + warp * 320, lane);
        cons_sync();
        if (tid < 64) {
            const int b = tid >> 4, n = tid & 15;
            const float g = bf16r(tall_sum(s_part, b, n));
            const float up = bf16r(tall_sum(s_part, b, 16 + n));
            g_act[b * FF + cta * 16 + n] = __float2bfloat16_rn(bf16r(gelu_tanh(g)) * up);
        }
    }
    PROF(10);
    grid_arrive(&g_bar[4], tid);
    if (cta >= DM / 8) return;
    grid_wait(&g_bar[4], target, tid);
    PROF(11);
    {
        uint4 v[3];
#pragma unroll
        for (int r = 0; r < 3; ++r) v[r] = __ldcg((const uint4*)g_act + tid + r * NCONS);
#pragma unroll
        for (int r = 0; r < 3; ++r) {
            const int i = tid + r * NCONS, b = i / 192, c8 = i - b * 192;
            *(uint4*)(smem + SM_ACT + b * ACT_PITCH + c8 * 16) = v[r];
        }
        cons_sync();
        gemv_mma(sbase + SM_WD + warp * 192 * 16, 16, sbase + SM_ACT + warp * 384, ACT_PITCH, 12, 1, s_part + warp * 320, lane);
        cons_sync();
        if (tid < 32) {
            const int b = tid >> 3, col = cta * 8 + (tid & 7);
            const float f = bf16r(tall_sum(s_part, b, tid & 7));
            out[b * DM + col] = __float2bfloat16_rn(s_xp[b * DM + col] + bf16r(gb * f));
        }
    }
    PROF(12);
}

}

extern "C" void kernel_launch(void* const* d_in, const int* in_sizes, int n_in, void* d_out, int out_size) {
    (void)in_sizes; (void)n_in; (void)out_size;
    const __nv_bfloat16* A_x = (const __nv_bfloat16*)d_in[0];
    const __nv_bfloat16* A_k = (const __nv_bfloat16*)d_in[1];
    const __nv_bfloat16* A_v = (const __nv_bfloat16*)d_in[2];
    const __nv_bfloat16* A_wq = (const __nv_bfloat16*)d_in[3];
    const __nv_bfloat16* A_wo = (const __nv_bfloat16*)d_in[4];
    const __nv_bfloat16* B_wg = (const __nv_bfloat16*)d_in[6];
    const __nv_bfloat16* B_wu = (const __nv_bfloat16*)d_in[7];
    const __nv_bfloat16* B_wd = (const __nv_bfloat16*)d_in[8];
    const __nv_bfloat16* c = (const __nv_bfloat16*)d_in[9];
    const __nv_bfloat16* w_mod = (const __nv_bfloat16*)d_in[10];
    static int grid = 0;
    if (grid == 0) {
        cudaFuncSetAttribute(decode_block_kernel, cudaFuncAttributeMaxDynamicSharedMemorySize, SM_TOTAL);
        int dev = 0, sms = 0;
        cudaGetDevice(&dev);
        cudaDeviceGetAttribute(&sms, cudaDevAttrMultiProcessorCount, dev);
        grid = sms < 132 ? sms : 132;
    }
    decode_block_kernel<<<grid, NTHREADS, SM_TOTAL>>>(A_x, A_k, A_v, A_wq, A_wo, B_wg, B_wu, B_wd, c, w_mod,
                                                      (__nv_bfloat16*)d_out);
}
```

```cpp
#include <cuda_runtime.h>
#include <cuda_bf16.h>
#include <stdint.h>

namespace {

constexpr int NB = 4;
constexpr int DM = 640;
constexpr int NH = 32;
constexpr int SK = 4096;
constexpr int DH = 192;
constexpr int FF = 1536;
constexpr int MODN = 6 * DM;
constexpr int QN = NH * DH;
constexpr int NBH = NB * NH;

constexpr int NCONS = 256;
constexpr int NTHREADS = NCONS + 32;
constexpr int TILE_KEYS = 64;
constexpr int TILE_BYTES = TILE_KEYS * DH * 2;
constexpr int STAGE_BYTES = TILE_BYTES;
constexpr int NST = 6;
constexpr int PRE = 3;
constexpr int TPI = 2;
constexpr int ITEM_KEYS = TPI * TILE_KEYS;
constexpr int CHUNKS = SK / ITEM_KEYS;
constexpr int NITEM_K = NBH * CHUNKS;
constexpr int NITEM = 2 * NITEM_K;

constexpr int A_PITCH = 1296;
constexpr int ACT_PITCH = FF * 2 + 16;
constexpr int P16 = 48;
constexpr int P32 = 80;
constexpr int P48 = 112;
constexpr int P80 = 176;
constexpr int WO_ROWS = 384;

constexpr int SM_RING = 0;
constexpr int SM_WQ = PRE * STAGE_BYTES;
constexpr int SM_WO = 0;
constexpr int SM_WD = SM_WO + WO_ROWS * P80;
constexpr int SM_W32 = NST * STAGE_BYTES;
constexpr int SM_ACT = SM_W32;
constexpr int SM_A = SM_W32 + DM * P32;
constexpr int SM_PART = SM_A + NB * A_PITCH;
constexpr int SM_XP = SM_PART + 8 * 4 * 80 * 4;
constexpr int SM_RED = SM_XP + NB * DM * 4;
constexpr int SM_ITEM = SM_RED + 16 * 4;
constexpr int SM_TAG = SM_ITEM + 16 * 4;
constexpr int SM_BAR = SM_TAG + 16 * 4;
constexpr int SM_TOTAL = SM_BAR + (2 * NST + 1) * 8;
static_assert(SM_WQ + DM * P48 <= NST * STAGE_BYTES, "prologue overlay");
static_assert(SM_WD + FF * P16 <= NST * STAGE_BYTES, "tail overlay");
static_assert(SM_TOTAL <= 232448, "smem");
#define PSTART 0

__device__ __align__(128) unsigned long long g_mod[NB * MODN / 2];
__device__ __align__(128) unsigned long long g_q[NB * QN / 2];
__device__ __align__(128) unsigned long long g_act[NB * FF / 2];
__device__ __align__(128) float g_s[NBH * SK];
__device__ __align__(128) float2 g_stat[NBH * CHUNKS];
__device__ __align__(128) unsigned int g_kcnt[NBH];
__device__ __align__(128) float g_o[2][NB * QN];
__device__ __align__(128) float g_attn[2][NB * DM];
__device__ __align__(128) unsigned int g_bar[8];
__device__ unsigned int g_work;
__device__ unsigned int g_kall;
__device__ unsigned int g_epoch;

#define PROF(k) do { } while (0)
#define PROFP(k) do { } while (0)

__device__ __forceinline__ float bf16r(float x) { return __bfloat162float(__float2bfloat16_rn(x)); }
__device__ __forceinline__ float bf_lo(uint32_t u) { return __uint_as_float(u << 16); }
__device__ __forceinline__ float bf_hi(uint32_t u) { return __uint_as_float(u & 0xffff0000u); }

__device__ __forceinline__ uint32_t smem_u32(const void* p) { return (uint32_t)__cvta_generic_to_shared(p); }
__device__ __forceinline__ void mbar_init(uint32_t bar, uint32_t count) {
    asm volatile("mbarrier.init.shared::cta.b64 [%0], %1;" ::"r"(bar), "r"(count) : "memory");
}
__device__ __forceinline__ void mbar_expect_tx(uint32_t bar, uint32_t bytes) {
    asm volatile("mbarrier.arrive.expect_tx.shared::cta.b64 _, [%0], %1;" ::"r"(bar), "r"(bytes) : "memory");
}
__device__ __forceinline__ void mbar_arrive(uint32_t bar) {
    asm volatile("mbarrier.arrive.shared::cta.b64 _, [%0];" ::"r"(bar) : "memory");
}
constexpr long long WAIT_LIMIT_CYCLES = 200000000LL;
__device__ __forceinline__ uint32_t mbar_try(uint32_t bar, uint32_t parity) {
    uint32_t done;
    asm volatile(
        "{\n\t.reg .pred p;\n\t"
        "mbarrier.try_wait.parity.shared::cta.b64 p, [%1], %2;\n\t"
        "selp.u32 %0, 1, 0, p;\n\t}"
        : "=r"(done) : "r"(bar), "r"(parity) : "memory");
    return done;
}
__device__ __noinline__ void mbar_wait_slow(uint32_t bar, uint32_t parity) {
    const long long t0 = clock64();
    while (!mbar_try(bar, parity)) {
        if (clock64() - t0 > WAIT_LIMIT_CYCLES) __trap();
    }
}
__device__ __forceinline__ void mbar_wait(uint32_t bar, uint32_t parity) {
    if (!mbar_try(bar, parity)) mbar_wait_slow(bar, parity);
}
__device__ __noinline__ void tag_wait_slow(volatile int* tag, int u) {
    const long long t0 = clock64();
    while (*tag != u) {
        __nanosleep(32);
        if (clock64() - t0 > WAIT_LIMIT_CYCLES) __trap();
    }
}
__device__ __forceinline__ void stage_wait(uint32_t bar_full, volatile int* s_tag, int u) {
    const int st = u % NST;
    if (s_tag[st] != u) tag_wait_slow(s_tag + st, u);
    mbar_wait(bar_full + st * 8, (u / NST) & 1);
}
__device__ __forceinline__ void bulk_g2s(uint32_t dst, const void* src, uint32_t bytes, uint32_t bar) {
    asm volatile(
        "cp.async.bulk.shared::cluster.global.mbarrier::complete_tx::bytes [%0], [%1], %2, [%3];"
        ::"r"(dst), "l"(src), "r"(bytes), "r"(bar) : "memory");
}
__device__ __forceinline__ void cp_async16(uint32_t dst, const void* src) {
    asm volatile("cp.async.cg.shared.global [%0], [%1], 16;" ::"r"(dst), "l"(src) : "memory");
}
__device__ __forceinline__ void cp_async_wait_all() { asm volatile("cp.async.wait_all;" ::: "memory"); }
__device__ __forceinline__ void cp_async_commit() { asm volatile("cp.async.commit_group;" ::: "memory"); }
__device__ __forceinline__ void cp_async_wait1() { asm volatile("cp.async.wait_group 1;" ::: "memory"); }
__device__ __forceinline__ void red_release_add(unsigned int* p, unsigned int v) {
    asm volatile("red.release.gpu.global.add.u32 [%0], %1;" ::"l"(p), "r"(v) : "memory");
}
__device__ __forceinline__ void cons_sync() { asm volatile("bar.sync 1, 256;" ::: "memory"); }

__device__ __forceinline__ void red_add_v4(float* p, float a, float b, float c, float d) {
    asm volatile("red.global.add.v4.f32 [%0], {%1, %2, %3, %4};" ::"l"(p), "f"(a), "f"(b), "f"(c), "f"(d) : "memory");
}
__device__ __forceinline__ unsigned int ld_acquire(const unsigned int* p) {
    unsigned int v;
    asm volatile("ld.acquire.gpu.global.u32 %0, [%1];" : "=r"(v) : "l"(p) : "memory");
    return v;
}
__device__ __forceinline__ void ll_store(unsigned long long* p, float a, float b, unsigned int ep) {
    __nv_bfloat162 v = __floats2bfloat162_rn(a, b);
    const unsigned long long w = ((unsigned long long)ep << 32) | *(uint32_t*)&v;
    asm volatile("st.relaxed.gpu.global.u64 [%0], %1;" ::"l"(p), "l"(w) : "memory");
}
__device__ __forceinline__ uint2 ll_ld1(const unsigned long long* p) {
    uint2 v;
    asm volatile("ld.relaxed.gpu.global.v2.u32 {%0, %1}, [%2];" : "=r"(v.x), "=r"(v.y) : "l"(p) : "memory");
    return v;
}
__device__ __forceinline__ uint4 ll_ld2(const unsigned long long* p) {
    uint4 v;
    asm volatile("ld.volatile.global.v4.u32 {%0, %1, %2, %3}, [%4];" : "=r"(v.x), "=r"(v.y), "=r"(v.z), "=r"(v.w) : "l"(p) : "memory");
    return v;
}
template <int N>
__device__ __forceinline__ void ll_get(const unsigned long long* p, uint32_t (&d)[N], unsigned int ep) {
    long long t0 = 0;
    for (;;) {
        bool ok = true;
#pragma unroll
        for (int i = 0; i < N; ++i) {
            const uint2 v = ll_ld1(p + i);
            d[i] = v.x;
            ok = ok && (v.y == ep);
        }
        if (ok) break;
        if (t0 == 0) t0 = clock64();
        else if (clock64() - t0 > WAIT_LIMIT_CYCLES) __trap();
    }
}

__device__ __forceinline__ void grid_arrive(unsigned int* ctr, int tid) {
    cons_sync();
    if (tid == 0) red_release_add(ctr, 1u);
}
__device__ __noinline__ void grid_wait(const unsigned int* ctr, unsigned int target, int tid) {
    if (tid == 0) {
        const long long t0 = clock64();
        while ((int)(ld_acquire(ctr) - target) < 0) {
            if (clock64() - t0 > WAIT_LIMIT_CYCLES) __trap();
        }
    }
    cons_sync();
}

__device__ __forceinline__ float warp_sum(float v) {
#pragma unroll
    for (int o = 16; o > 0; o >>= 1) v += __shfl_xor_sync(0xffffffffu, v, o);
    return v;
}
__device__ __forceinline__ float warp_max(float v) {
#pragma unroll
    for (int o = 16; o > 0; o >>= 1) v = fmaxf(v, __shfl_xor_sync(0xffffffffu, v, o));
    return v;
}

__device__ __forceinline__ void fma8(float (&acc)[8], const uint4& w, float s) {
    acc[0] = fmaf(s, bf_lo(w.x), acc[0]);
    acc[1] = fmaf(s, bf_hi(w.x), acc[1]);
    acc[2] = fmaf(s, bf_lo(w.y), acc[2]);
    acc[3] = fmaf(s, bf_hi(w.y), acc[3]);
    acc[4] = fmaf(s, bf_lo(w.z), acc[4]);
    acc[5] = fmaf(s, bf_hi(w.z), acc[5]);
    acc[6] = fmaf(s, bf_lo(w.w), acc[6]);
    acc[7] = fmaf(s, bf_hi(w.w), acc[7]);
}
__device__ __forceinline__ float dot8(const uint4& w, const float* q) {
    float s = q[0] * bf_lo(w.x);
    s = fmaf(q[1], bf_hi(w.x), s);
    s = fmaf(q[2], bf_lo(w.y), s);
    s = fmaf(q[3], bf_hi(w.y), s);
    s = fmaf(q[4], bf_lo(w.z), s);
    s = fmaf(q[5], bf_hi(w.z), s);
    s = fmaf(q[6], bf_lo(w.w), s);
    s = fmaf(q[7], bf_hi(w.w), s);
    return s;
}

__device__ __noinline__ void stage_rows(uint32_t dst, int dst_pitch, const void* src, int src_stride, int rows,
                                        int cpr, int tid, int nthr) {
    const int n = rows * cpr;
#pragma unroll 1
    for (int i = tid; i < n; i += nthr) {
        const int r = i / cpr, c = i - r * cpr;
        cp_async16(dst + r * dst_pitch + c * 16, (const unsigned char*)src + (size_t)r * src_stride + c * 16);
    }
}

template <int KS, int NT>
__device__ __noinline__ void gemv_mma(uint32_t w, int w_pitch, uint32_t a, int a_pitch, float* part, int lane) {
    float c[NT][4];
#pragma unroll
    for (int nt = 0; nt < NT; ++nt) { c[nt][0] = 0.f; c[nt][1] = 0.f; c[nt][2] = 0.f; c[nt][3] = 0.f; }
    const uint32_t ap = a + (lane >> 2) * a_pitch + (lane & 3) * 4;
    const uint32_t wp = w + ((lane & 7) + ((lane >> 4) << 3)) * w_pitch + ((lane >> 3) & 1) * 16;
#pragma unroll
    for (int ks = 0; ks < KS; ++ks) {
        uint32_t b0 = 0, b1 = 0;
        if (lane < 16) {
            asm volatile("ld.shared.u32 %0, [%1];" : "=r"(b0) : "r"(ap + ks * 32));
            asm volatile("ld.shared.u32 %0, [%1];" : "=r"(b1) : "r"(ap + ks * 32 + 16));
        }
#pragma unroll
        for (int nt = 0; nt < NT; ++nt) {
            uint32_t a0, a1, a2, a3;
            asm volatile("ldmatrix.sync.aligned.m8n8.x4.trans.shared.b16 {%0, %1, %2, %3}, [%4];"
                         : "=r"(a0), "=r"(a1), "=r"(a2), "=r"(a3) : "r"(wp + ks * 16 * w_pitch + nt * 32));
            asm volatile(
                "mma.sync.aligned.m16n8k16.row.col.f32.bf16.bf16.f32 {%0, %1, %2, %3}, {%4, %5, %6, %7}, "
                "{%8, %9}, {%0, %1, %2, %3};"
                : "+f"(c[nt][0]), "+f"(c[nt][1]), "+f"(c[nt][2]), "+f"(c[nt][3])
                : "r"(a0), "r"(a1), "r"(a2), "r"(a3), "r"(b0), "r"(b1));
        }
    }
    if ((lane & 3) < 2) {
        float* pp = part + (lane & 3) * 160 + (lane >> 2);
#pragma unroll
        for (int nt = 0; nt < NT; ++nt) {
            pp[nt * 16] = c[nt][0];
            pp[nt * 16 + 80] = c[nt][1];
            pp[nt * 16 + 8] = c[nt][2];
            pp[nt * 16 + 88] = c[nt][3];
        }
    }
}

__device__ __forceinline__ float tall_sum(const float* part, int b, int n) {
    float s = 0.f;
#pragma unroll
    for (int w = 0; w < 8; ++w) s += part[(w * 4 + b) * 80 + n];
    return s;
}

__device__ __noinline__ void ln_norm(float (&v)[10], float* s_red, int tid) {
    const int warp = tid >> 5;
    float s = 0.f;
#pragma unroll
    for (int i = 0; i < 10; ++i) s += v[i];
    s = warp_sum(s);
    if ((tid & 31) == 0) s_red[warp] = s;
    cons_sync();
    const float mean_f = (s_red[warp & 6] + s_red[warp | 1]) * (1.0f / DM);
    float q = 0.f;
#pragma unroll
    for (int i = 0; i < 10; ++i) { const float d = v[i] - mean_f; q = fmaf(d, d, q); }
    q = warp_sum(q);
    if ((tid & 31) == 0) s_red[8 + warp] = q;
    cons_sync();
    const float var = (s_red[8 + (warp & 6)] + s_red[8 + (warp | 1)]) * (1.0f / DM);
    const float mean = bf16r(mean_f);
    const float den = bf16r(sqrtf(bf16r(bf16r(var) + 1e-5f)));
#pragma unroll
    for (int i = 0; i < 10; ++i) v[i] = bf16r(__fdiv_rn(bf16r(v[i] - mean), den));
}
__device__ __forceinline__ void modulate(const float (&n)[10], const uint32_t (&sh)[5], const uint32_t (&sc)[5], uint32_t* dst) {
#pragma unroll
    for (int i = 0; i < 5; ++i) {
        const float h0 = bf16r(n[2 * i] * bf16r(1.0f + bf_lo(sc[i]))) + bf_lo(sh[i]);
        const float h1 = bf16r(n[2 * i + 1] * bf16r(1.0f + bf_hi(sc[i]))) + bf_hi(sh[i]);
        __nv_bfloat162 p = __floats2bfloat162_rn(h0, h1);
        dst[i] = *(uint32_t*)&p;
    }
}

__device__ __forceinline__ float gelu_tanh(float x) {
    const float kBeta = 0.7978845608028654f;
    const float inner = kBeta * (x + 0.044715f * x * x * x);
    return 0.5f * x * (1.0f + tanhf(inner));
}

__global__ void __launch_bounds__(NTHREADS, 1)
decode_block_kernel(const __nv_bfloat16* __restrict__ x_in, const __nv_bfloat16* __restrict__ k_cache,
                    const __nv_bfloat16* __restrict__ v_cache, const __nv_bfloat16* __restrict__ wq,
                    const __nv_bfloat16* __restrict__ wo, const __nv_bfloat16* __restrict__ w_gate,
                    const __nv_bfloat16* __restrict__ w_up, const __nv_bfloat16* __restrict__ w_down,
                    const __nv_bfloat16* __restrict__ cvec, const __nv_bfloat16* __restrict__ w_mod,
                    __nv_bfloat16* __restrict__ out) {
    extern __shared__ __align__(128) unsigned char smem[];
    const int tid = threadIdx.x;
    const int cta = blockIdx.x;

    const uint32_t sbase = smem_u32(smem);
    const uint32_t bar_full = sbase + SM_BAR;
    const uint32_t bar_empty = bar_full + NST * 8;
    volatile int* s_item = (volatile int*)(smem + SM_ITEM);
    volatile int* s_tag = (volatile int*)(smem + SM_TAG);

    const uint32_t bar_go = bar_empty + NST * 8;
    if (tid < NST) s_tag[tid] = -1;
    if (tid == 0) {
#pragma unroll 1
        for (int s = 0; s < 2 * NST + 1; ++s) mbar_init(bar_full + s * 8, 1);
        asm volatile("fence.mbarrier_init.release.cluster;" ::: "memory");
        asm volatile("fence.proxy.async.shared::cta;" ::: "memory");
#pragma unroll 1
        for (int s = 0; s < PRE; ++s) mbar_arrive(bar_empty + s * 8);
    }
    __syncthreads();

    if (tid >= NCONS) {
        if (tid == NCONS) {
            int u = 0;
            bool pf = false, kdone = false;
            const int G = (int)gridDim.x;
            const unsigned int ep = ld_acquire(&g_epoch) + 1u;
            auto produce = [&](const int item) {
                const int it = item & (NITEM_K - 1);
                const bool is_v = item >= NITEM_K;
                const unsigned char* src = (const unsigned char*)(is_v ? v_cache : k_cache) + (size_t)it * (ITEM_KEYS * DH * 2);
                if (is_v && !kdone) {
                    if (ld_acquire(&g_kall) == ep * NITEM_K) {
                        kdone = true;
                    } else {
                        const long long t0 = clock64();
                        while (ld_acquire(&g_kcnt[it / CHUNKS]) != ep * CHUNKS)
                            if (clock64() - t0 > WAIT_LIMIT_CYCLES) __trap();
                    }
                }
#pragma unroll 1
                for (int t = 0; t < TPI; ++t, ++u) {
                    const int st = u % NST;
                    const uint32_t fb = bar_full + st * 8;
                    mbar_wait(bar_empty + st * 8, (u / NST) & 1);
                    s_item[st] = item;
                    s_tag[st] = u;
                    mbar_expect_tx(fb, TILE_BYTES);
                    bulk_g2s(sbase + SM_RING + st * STAGE_BYTES, src + t * TILE_BYTES, TILE_BYTES, fb);
                }
                if (!pf && item >= NITEM - 10 * G) {
                    pf = true;
                    if (cta < QN / 48)
                        asm volatile("cp.async.bulk.prefetch.L2.global [%0], %1;" ::"l"(wo + (size_t)cta * 48 * DM), "r"(48 * DM * 2) : "memory");
                    if (cta < FF / 16)
                        asm volatile("cp.async.bulk.prefetch.L2.global [%0], %1;" ::"l"(w_down + (size_t)cta * 16 * DM), "r"(16 * DM * 2) : "memory");
                }
            };
            if (PSTART != 3) mbar_wait(bar_go, 0);
            unsigned int r0 = cta - 3 * G, r1 = cta - 2 * G, r2 = cta - G;
#pragma unroll 1
            for (;;) {
                if ((int)(r0 + 3 * G) >= NITEM) break;
                produce((int)(r0 + 3 * G));
                r0 = atomicAdd(&g_work, 1u);
                if ((int)(r1 + 3 * G) >= NITEM) break;
                produce((int)(r1 + 3 * G));
                r1 = atomicAdd(&g_work, 1u);
                if ((int)(r2 + 3 * G) >= NITEM) break;
                produce((int)(r2 + 3 * G));
                r2 = atomicAdd(&g_work, 1u);
            }
            s_item[15] = (int)(r0 + r1 + r2);
#pragma unroll 1
            for (int j = 0; j < 8; ++j, u += TPI) {
                const int st = u % NST;
                mbar_wait(bar_empty + st * 8, (u / NST) & 1);
                s_item[st] = -1;
                s_tag[st] = u;
                mbar_arrive(bar_full + st * 8);
            }
            PROFP(13);
        }
        return;
    }

    const int lane = tid & 31, warp = tid >> 5;
    float* s_part = (float*)(smem + SM_PART);
    float* s_xp = (float*)(smem + SM_XP);
    float* s_red = (float*)(smem + SM_RED);
    const int lrow = tid >> 6, lcol = (tid & 63) * 10;
    uint32_t* h_dst = (uint32_t*)(smem + SM_A + lrow * A_PITCH + lcol * 2);

    PROF(0);
    const unsigned int ep = ld_acquire(&g_epoch) + 1u;
    const unsigned int target = ep * gridDim.x;
    const unsigned long long* mod_row = g_mod + (lrow * MODN + lcol) / 2;
    float nv[10];
    {
        const int i1 = tid + NCONS;
        const uint4 c0 = __ldg((const uint4*)cvec + tid);
        uint4 c1 = c0;
        if (i1 < 320) c1 = __ldg((const uint4*)cvec + i1);
        uint32_t xw[5];
#pragma unroll
        for (int i = 0; i < 5; ++i) xw[i] = __ldg((const uint32_t*)(x_in + lrow * DM + lcol) + i);
        if (cta < MODN / 32) stage_rows(sbase + SM_W32, P32, w_mod + cta * 32, MODN * 2, DM, 4, tid, NCONS);
        cp_async_commit();
        if (cta < QN / 48) stage_rows(sbase + SM_WQ, P48, wq + cta * 48, QN * 2, DM, 6, tid, NCONS);
        cp_async_commit();
        if (PSTART == 1 && tid == 0) mbar_arrive(bar_go);
#pragma unroll 1
        for (int r = 0; r < 2; ++r) {
            const int i = r ? i1 : tid;
            if (i < 320) {
                const uint4 cc = r ? c1 : c0;
                const uint32_t cw[4] = {cc.x, cc.y, cc.z, cc.w};
                uint32_t ow[4];
#pragma unroll
                for (int k = 0; k < 4; ++k) {
                    const float a = bf_lo(cw[k]), b = bf_hi(cw[k]);
                    __nv_bfloat162 p = __floats2bfloat162_rn(__fdiv_rn(a, 1.0f + __expf(-a)), __fdiv_rn(b, 1.0f + __expf(-b)));
                    ow[k] = *(uint32_t*)&p;
                }
                const int b = i / 80, c8 = i - b * 80;
                *(uint4*)(smem + SM_A + b * A_PITCH + c8 * 16) = make_uint4(ow[0], ow[1], ow[2], ow[3]);
            }
        }
#pragma unroll
        for (int i = 0; i < 5; ++i) {
            nv[2 * i] = bf_lo(xw[i]);
            nv[2 * i + 1] = bf_hi(xw[i]);
            *(float2*)(s_xp + lrow * DM + lcol + 2 * i) = make_float2(nv[2 * i], nv[2 * i + 1]);
        }
    }
    float* acc_o = g_o[ep & 1];
    float* acc_attn = g_attn[ep & 1];
    if (cta == gridDim.x - 1) {
#pragma unroll 1
        for (int i = tid; i < NB * QN / 4; i += NCONS) ((float4*)g_o[~ep & 1])[i] = make_float4(0.f, 0.f, 0.f, 0.f);
#pragma unroll 1
        for (int i = tid; i < NB * DM; i += NCONS) g_attn[~ep & 1][i] = 0.f;
    }
    ln_norm(nv, s_red, tid);
    cp_async_wait1();
    cons_sync();
    if (PSTART == 0 && tid == 0) mbar_arrive(bar_go);
    if (cta < MODN / 32) {
        gemv_mma<5, 2>(sbase + SM_W32 + warp * 80 * P32, P32, sbase + SM_A + warp * 160, A_PITCH, s_part + warp * 320, lane);
        cons_sync();
        if (tid < 64) {
            const int b = tid >> 4, n = (tid & 15) * 2;
            ll_store(g_mod + (b * MODN + cta * 32 + n) / 2, tall_sum(s_part, b, n), tall_sum(s_part, b, n + 1), ep);
        }
    }
    PROF(1);

    if (cta < QN / 48) {
        uint32_t sh[5], sc[5];
        ll_get(mod_row, sh, ep);
        ll_get(mod_row + DM / 2, sc, ep);
        PROF(2);
        cons_sync();
        modulate(nv, sh, sc, h_dst);
        cp_async_wait_all();
        cons_sync();
        if (PSTART == 2 && tid == 0) mbar_arrive(bar_go);
        gemv_mma<5, 3>(sbase + SM_WQ + warp * 80 * P48, P48, sbase + SM_A + warp * 160, A_PITCH, s_part + warp * 320, lane);
        cons_sync();
        if (tid < 96) {
            const int b = tid / 24, n = (tid - b * 24) * 2;
            ll_store(g_q + (b * QN + cta * 48 + n) / 2, tall_sum(s_part, b, n), tall_sum(s_part, b, n + 1), ep);
        }
    } else if (PSTART == 2 && tid == 0) {
        mbar_arrive(bar_go);
    }
    PROF(3);
    if (tid == 0) {
#pragma unroll 1
        for (int s = PRE; s < NST; ++s) mbar_arrive(bar_empty + s * 8);
    }
    uint32_t m_ga[5], m_sb[5], m_cb[5], m_gb[1] = {0u};
    if (cta < FF / 16) {
        if (warp == 7) {
            stage_rows(sbase + SM_W32, P32, w_gate + cta * 16, FF * 2, DM, 2, lane, 32);
            stage_rows(sbase + SM_W32 + 32, P32, w_up + cta * 16, FF * 2, DM, 2, lane, 32);
        }
        ll_get(mod_row + DM, m_ga, ep);
        ll_get(mod_row + 3 * DM / 2, m_sb, ep);
        ll_get(mod_row + 2 * DM, m_cb, ep);
        if (tid < 32 && cta < DM / 16) ll_get(g_mod + ((tid >> 3) * MODN + 5 * DM + cta * 16) / 2 + (tid & 7), m_gb, ep);
    }
    PROF(4);

    {
        const int sub = lane & 7, grp = lane >> 3;
        for (int u0 = warp * TPI;; u0 += 8 * TPI) {
            if (s_tag[u0 % NST] != u0) tag_wait_slow(s_tag + u0 % NST, u0);
            const int item = s_item[u0 % NST];
            if (item < 0) {
                mbar_wait(bar_full + (u0 % NST) * 8, (u0 / NST) & 1);
                __syncwarp();
                if (lane == 0) mbar_arrive(bar_empty + (u0 % NST) * 8);
                break;
            }
            const int bh = (item & (NITEM_K - 1)) / CHUNKS;
            if (item < NITEM_K) {
                float* gs = g_s + (size_t)item * ITEM_KEYS;
                float qr[24];
                {
                    const unsigned long long* qp = g_q + ((bh >> 5) * QN + (bh & 31) * DH) / 2 + sub * 4;
                    long long t0 = 0;
                    for (;;) {
                        bool ok = true;
#pragma unroll
                        for (int j = 0; j < 6; ++j) {
                            const uint4 v = ll_ld2(qp + (j >> 1) * 32 + (j & 1) * 2);
                            qr[j * 4 + 0] = bf_lo(v.x); qr[j * 4 + 1] = bf_hi(v.x);
                            qr[j * 4 + 2] = bf_lo(v.z); qr[j * 4 + 3] = bf_hi(v.z);
                            ok = ok && v.y == ep && v.w == ep;
                        }
                        if (ok) break;
                        if (t0 == 0) t0 = clock64();
                        else if (clock64() - t0 > WAIT_LIMIT_CYCLES) __trap();
                    }
                }
                float m_run = -INFINITY, l_run = 0.f;
#pragma unroll 1
                for (int hh = 0; hh < 2 * TPI; ++hh) {
                    const int u = u0 + (hh >> 1), st = u % NST;
                    if (!(hh & 1)) stage_wait(bar_full, s_tag, u);
                    const uint4* tile = (const uint4*)(smem + SM_RING + st * STAGE_BYTES) + (hh & 1) * (32 * 24);
                    float part[8];
#pragma unroll
                    for (int it = 0; it < 8; ++it) {
                        const uint4* row = tile + (it * 4 + grp) * 24 + sub;
                        const uint4 a = row[0], b = row[8], c = row[16];
                        part[it] = dot8(a, qr) + dot8(b, qr + 8) + dot8(c, qr + 16);
                    }
                    if (hh & 1) {
                        __syncwarp();
                        if (lane == 0) mbar_arrive(bar_empty + st * 8);
                    }
#pragma unroll
                    for (int j = 0; j < 4; ++j) {
                        const float send = (sub & 4) ? part[j] : part[j + 4];
                        const float keep = (sub & 4) ? part[j + 4] : part[j];
                        part[j] = keep + __shfl_xor_sync(0xffffffffu, send, 4);
                    }
#pragma unroll
                    for (int j = 0; j < 2; ++j) {
                        const float send = (sub & 2) ? part[j] : part[j + 2];
                        const float keep = (sub & 2) ? part[j + 2] : part[j];
                        part[j] = keep + __shfl_xor_sync(0xffffffffu, send, 2);
                    }
                    {
                        const float send = (sub & 1) ? part[0] : part[1];
                        const float keep = (sub & 1) ? part[1] : part[0];
                        part[0] = keep + __shfl_xor_sync(0xffffffffu, send, 1);
                    }
                    const float s = bf16r(bf16r(part[0]) * 0.07216878364870323f);
                    gs[hh * 32 + sub * 4 + grp] = s;
                    const float m_new = fmaxf(m_run, s);
                    l_run = l_run * __expf(m_run - m_new) + __expf(s - m_new);
                    m_run = m_new;
                }
                const float m = warp_max(m_run);
                const float l = warp_sum(l_run * __expf(m_run - m));
                __syncwarp();
                if (lane == 0) {
                    g_stat[item] = make_float2(m, l);
                    red_release_add(&g_kcnt[bh], 1u);
                    red_release_add(&g_kall, 1u);
                }
            } else {
                float pr[2 * TPI];
                {
                    const float* gs = g_s + (size_t)(item - NITEM_K) * ITEM_KEYS + lane;
                    const float2 st2 = __ldcg(g_stat + bh * CHUNKS + lane);
#pragma unroll
                    for (int hh = 0; hh < 2 * TPI; ++hh) pr[hh] = __ldcg(gs + hh * 32);
                    const float mm = warp_max(st2.x);
                    const float ll = warp_sum(st2.y * __expf(st2.x - mm));
#pragma unroll
                    for (int hh = 0; hh < 2 * TPI; ++hh) pr[hh] = bf16r(__fdiv_rn(__expf(pr[hh] - mm), ll));
                }
                float acc[3][8];
#pragma unroll
                for (int j = 0; j < 3; ++j)
#pragma unroll
                    for (int e = 0; e < 8; ++e) acc[j][e] = 0.f;
#pragma unroll
                for (int hh = 0; hh < 2 * TPI; ++hh) {
                    const int u = u0 + (hh >> 1), st = u % NST;
                    if (!(hh & 1)) stage_wait(bar_full, s_tag, u);
                    const uint4* tile = (const uint4*)(smem + SM_RING + st * STAGE_BYTES) + (hh & 1) * (32 * 24);
#pragma unroll
                    for (int it = 0; it < 8; ++it) {
                        const uint4* row = tile + (it * 4 + grp) * 24 + sub;
                        const uint4 a = row[0], b = row[8], c = row[16];
                        const float p = __shfl_sync(0xffffffffu, pr[hh], it * 4 + grp);
                        fma8(acc[0], a, p);
                        fma8(acc[1], b, p);
                        fma8(acc[2], c, p);
                    }
                    if (hh & 1) {
                        __syncwarp();
                        if (lane == 0) mbar_arrive(bar_empty + st * 8);
                    }
                }
                float* go = acc_o + (bh >> 5) * QN + (bh & 31) * DH + sub * 8;
#pragma unroll
                for (int j = 0; j < 3; ++j) {
#pragma unroll
                    for (int e = 0; e < 8; ++e) {
                        float v = acc[j][e];
                        v += __shfl_xor_sync(0xffffffffu, v, 8);
                        v += __shfl_xor_sync(0xffffffffu, v, 16);
                        acc[j][e] = v;
                    }
                    if (grp == 0) {
                        red_add_v4(go + j * 64, acc[j][0], acc[j][1], acc[j][2], acc[j][3]);
                        red_add_v4(go + j * 64 + 4, acc[j][4], acc[j][5], acc[j][6], acc[j][7]);
                    }
                }
            }
        }
    }
    PROF(5);
    grid_arrive(&g_bar[2], tid);
    PROF(6);
    const int ks = cta >> 3, ns = cta & 7;
    if (cta < 128) stage_rows(sbase + SM_WO, P80, wo + (size_t)ks * WO_ROWS * DM + ns * 80, DM * 2, WO_ROWS, 10, tid, NCONS);
    if (cta < DM / 16) stage_rows(sbase + SM_WD, P16, w_down + cta * 16, DM * 2, FF, 2, tid, NCONS);
    grid_wait(&g_bar[2], target, tid);
    if (cta == 0 && tid == 0) { g_work = 0u; g_epoch = ep; }
    PROF(7);

    if (cta < 128) {
#pragma unroll
        for (int r = 0; r < 2; ++r) {
            const int i = tid + r * NCONS;
            if (i < NB * WO_ROWS / 4) {
                const int b = i / 96, c4 = i - b * 96;
                const float4 v = __ldcg((const float4*)(acc_o + b * QN + ks * WO_ROWS) + c4);
                __nv_bfloat162 p0 = __floats2bfloat162_rn(v.x, v.y), p1 = __floats2bfloat162_rn(v.z, v.w);
                uint2 w2;
                w2.x = *(uint32_t*)&p0; w2.y = *(uint32_t*)&p1;
                *(uint2*)(smem + SM_A + b * A_PITCH + c4 * 8) = w2;
            }
        }
        cp_async_wait_all();
        cons_sync();
        gemv_mma<3, 5>(sbase + SM_WO + warp * 48 * P80, P80, sbase + SM_A + warp * 96, A_PITCH, s_part + warp * 320, lane);
        cons_sync();
        if (tid < 80) {
            const int b = tid / 20, n4 = tid - b * 20;
            float4 s4 = make_float4(0.f, 0.f, 0.f, 0.f);
#pragma unroll
            for (int w = 0; w < 8; ++w) {
                const float4 v = *(const float4*)(s_part + (w * 4 + b) * 80 + n4 * 4);
                s4.x += v.x; s4.y += v.y; s4.z += v.z; s4.w += v.w;
            }
            red_add_v4(acc_attn + b * DM + ns * 80 + n4 * 4, s4.x, s4.y, s4.z, s4.w);
        }
    }
    PROF(8);
    grid_arrive(&g_bar[3], tid);
    if (cta >= FF / 16) return;
    grid_wait(&g_bar[3], target, tid);
    PROF(9);
#pragma unroll
    for (int i = 0; i < 5; ++i) {
        const float2 av = __ldcg((const float2*)(acc_attn + lrow * DM + lcol) + i);
        float2* xp = (float2*)(s_xp + lrow * DM + lcol) + i;
        const float2 xv = *xp;
        nv[2 * i] = bf16r(xv.x + bf16r(bf_lo(m_ga[i]) * bf16r(av.x)));
        nv[2 * i + 1] = bf16r(xv.y + bf16r(bf_hi(m_ga[i]) * bf16r(av.y)));
        *xp = make_float2(nv[2 * i], nv[2 * i + 1]);
    }
    ln_norm(nv, s_red, tid);
    modulate(nv, m_sb, m_cb, h_dst);
    cons_sync();
    gemv_mma<5, 2>(sbase + SM_W32 + warp * 80 * P32, P32, sbase + SM_A + warp * 160, A_PITCH, s_part + warp * 320, lane);
    cons_sync();
    if (tid < 32) {
        const int b = tid >> 3, n = (tid & 7) * 2;
        const float g0 = bf16r(tall_sum(s_part, b, n)), g1 = bf16r(tall_sum(s_part, b, n + 1));
        const float u0 = bf16r(tall_sum(s_part, b, 16 + n)), u1 = bf16r(tall_sum(s_part, b, 17 + n));
        ll_store(g_act + (b * FF + cta * 16 + n) / 2, bf16r(gelu_tanh(g0)) * u0, bf16r(gelu_tanh(g1)) * u1, ep);
    }
    PROF(10);
    if (cta >= DM / 16) return;
    {
        long long t0 = 0;
        for (;;) {
            bool ok = true;
#pragma unroll
            for (int r = 0; r < 6; ++r) {
                const int i = tid + r * NCONS, b = i / 384, c4 = i - b * 384;
                const uint4 v = ll_ld2(g_act + 2 * i);
                *(uint2*)(smem + SM_ACT + b * ACT_PITCH + c4 * 8) = make_uint2(v.x, v.z);
                ok = ok && v.y == ep && v.w == ep;
            }
            if (ok) break;
            if (t0 == 0) t0 = clock64();
            else if (clock64() - t0 > WAIT_LIMIT_CYCLES) __trap();
        }
        cons_sync();
        PROF(11);
        gemv_mma<12, 1>(sbase + SM_WD + warp * 192 * P16, P16, sbase + SM_ACT + warp * 384, ACT_PITCH, s_part + warp * 320, lane);
        cons_sync();
        if (tid < 32) {
            const int b = tid >> 3, n = (tid & 7) * 2, col = cta * 16 + n;
            const float f0 = bf16r(tall_sum(s_part, b, n)), f1 = bf16r(tall_sum(s_part, b, n + 1));
            __nv_bfloat162 p = __floats2bfloat162_rn(s_xp[b * DM + col] + bf16r(bf_lo(m_gb[0]) * f0),
                                                     s_xp[b * DM + col + 1] + bf16r(bf_hi(m_gb[0]) * f1));
            *(__nv_bfloat162*)(out + b * DM + col) = p;
        }
    }
    PROF(12);
}

}

extern "C" void kernel_launch(void* const* d_in, const int* in_sizes, int n_in, void* d_out, int out_size) {
    (void)in_sizes; (void)n_in; (void)out_size;
    const __nv_bfloat16* A_x = (const __nv_bfloat16*)d_in[0];
    const __nv_bfloat16* A_k = (const __nv_bfloat16*)d_in[1];
    const __nv_bfloat16* A_v = (const __nv_bfloat16*)d_in[2];
    const __nv_bfloat16* A_wq = (const __nv_bfloat16*)d_in[3];
    const __nv_bfloat16* A_wo = (const __nv_bfloat16*)d_in[4];
    const __nv_bfloat16* B_wg = (const __nv_bfloat16*)d_in[6];
    const __nv_bfloat16* B_wu = (const __nv_bfloat16*)d_in[7];
    const __nv_bfloat16* B_wd = (const __nv_bfloat16*)d_in[8];
    const __nv_bfloat16* c = (const __nv_bfloat16*)d_in[9];
    const __nv_bfloat16* w_mod = (const __nv_bfloat16*)d_in[10];
    static int grid = 0;
    if (grid == 0) {
        cudaFuncSetAttribute(decode_block_kernel, cudaFuncAttributeMaxDynamicSharedMemorySize, SM_TOTAL);
        int dev = 0, sms = 0;
        cudaGetDevice(&dev);
        cudaDeviceGetAttribute(&sms, cudaDevAttrMultiProcessorCount, dev);
        grid = sms < 132 ? sms : 132;
    }
    decode_block_kernel<<<grid, NTHREADS, SM_TOTAL>>>(A_x, A_k, A_v, A_wq, A_wo, B_wg, B_wu, B_wd, c, w_mod,
                                                      (__nv_bfloat16*)d_out);
}
```

```cpp
#include <cuda_runtime.h>
#include <cuda_bf16.h>
#include <stdint.h>

namespace {

constexpr int NB = 4;
constexpr int DM = 640;
constexpr int NH = 32;
constexpr int SK = 4096;
constexpr int DH = 192;
constexpr int FF = 1536;
constexpr int MODN = 6 * DM;
constexpr int QN = NH * DH;
constexpr int NBH = NB * NH;

constexpr int NCONS = 256;
constexpr int NTHREADS = NCONS + 32;
constexpr int TILE_KEYS = 64;
constexpr int TILE_BYTES = TILE_KEYS * DH * 2;
constexpr int STAGE_BYTES = TILE_BYTES;
constexpr int NST = 6;
constexpr int PRE = 3;
constexpr int TPI = 2;
constexpr int ITEM_KEYS = TPI * TILE_KEYS;
constexpr int CHUNKS = SK / ITEM_KEYS;
constexpr int NITEM_K = NBH * CHUNKS;
constexpr int NITEM = 2 * NITEM_K;

constexpr int A_PITCH = 1296;
constexpr int ACT_PITCH = FF * 2 + 16;
constexpr int P16 = 48;
constexpr int P32 = 80;
constexpr int P48 = 112;
constexpr int P80 = 176;
constexpr int WO_ROWS = 384;

constexpr int SM_RING = 0;
constexpr int SM_WQ = PRE * STAGE_BYTES;
constexpr int SM_WO = 0;
constexpr int SM_WD = SM_WO + WO_ROWS * P80;
constexpr int SM_W32 = NST * STAGE_BYTES;
constexpr int SM_ACT = SM_W32;
constexpr int SM_A = SM_W32 + DM * P32;
constexpr int SM_PART = SM_A + NB * A_PITCH;
constexpr int SM_XP = SM_PART + 8 * 4 * 80 * 4;
constexpr int SM_RED = SM_XP + NB * DM * 4;
constexpr int SM_ITEM = SM_RED + 16 * 4;
constexpr int SM_TAG = SM_ITEM + 16 * 4;
constexpr int SM_BAR = SM_TAG + 16 * 4;
constexpr int SM_TOTAL = SM_BAR + (2 * NST + 1) * 8;
static_assert(SM_WQ + DM * P48 <= NST * STAGE_BYTES, "prologue overlay");
static_assert(SM_WD + FF * P16 <= NST * STAGE_BYTES, "tail overlay");
static_assert(SM_TOTAL <= 232448, "smem");
#define PSTART 0

__device__ __align__(128) unsigned long long g_mod[NB * MODN / 2];
__device__ __align__(128) unsigned long long g_q[NB * QN / 2];
__device__ __align__(128) unsigned long long g_act[NB * FF / 2];
__device__ __align__(128) float g_s[NBH * SK];
__device__ __align__(128) float2 g_stat[NBH * CHUNKS];
__device__ __align__(128) unsigned int g_kcnt[NBH];
__device__ __align__(128) float g_o[2][NB * QN];
__device__ __align__(128) float g_attn[2][NB * DM];
__device__ __align__(128) unsigned int g_bar[8];
__device__ unsigned int g_work;
__device__ unsigned int g_kall;
__device__ unsigned int g_epoch;

#define PROF(k) do { } while (0)
#define PROFP(k) do { } while (0)

__device__ __forceinline__ float bf16r(float x) { return __bfloat162float(__float2bfloat16_rn(x)); }
__device__ __forceinline__ float bf_lo(uint32_t u) { return __uint_as_float(u << 16); }
__device__ __forceinline__ float bf_hi(uint32_t u) { return __uint_as_float(u & 0xffff0000u); }

__device__ __forceinline__ uint32_t smem_u32(const void* p) { return (uint32_t)__cvta_generic_to_shared(p); }
__device__ __forceinline__ void mbar_init(uint32_t bar, uint32_t count) {
    asm volatile("mbarrier.init.shared::cta.b64 [%0], %1;" ::"r"(bar), "r"(count) : "memory");
}
__device__ __forceinline__ void mbar_expect_tx(uint32_t bar, uint32_t bytes) {
    asm volatile("mbarrier.arrive.expect_tx.shared::cta.b64 _, [%0], %1;" ::"r"(bar), "r"(bytes) : "memory");
}
__device__ __forceinline__ void mbar_arrive(uint32_t bar) {
    asm volatile("mbarrier.arrive.shared::cta.b64 _, [%0];" ::"r"(bar) : "memory");
}
constexpr long long WAIT_LIMIT_CYCLES = 200000000LL;
__device__ __forceinline__ uint32_t mbar_try(uint32_t bar, uint32_t parity) {
    uint32_t done;
    asm volatile(
        "{\n\t.reg .pred p;\n\t"
        "mbarrier.try_wait.parity.shared::cta.b64 p, [%1], %2;\n\t"
        "selp.u32 %0, 1, 0, p;\n\t}"
        : "=r"(done) : "r"(bar), "r"(parity) : "memory");
    return done;
}
__device__ __noinline__ void mbar_wait_slow(uint32_t bar, uint32_t parity) {
    const long long t0 = clock64();
    while (!mbar_try(bar, parity)) {
        if (clock64() - t0 > WAIT_LIMIT_CYCLES) __trap();
    }
}
__device__ __forceinline__ void mbar_wait(uint32_t bar, uint32_t parity) {
    if (!mbar_try(bar, parity)) mbar_wait_slow(bar, parity);
}
__device__ __noinline__ void tag_wait_slow(volatile int* tag, int u) {
    const long long t0 = clock64();
    while (*tag != u) {
        __nanosleep(32);
        if (clock64() - t0 > WAIT_LIMIT_CYCLES) __trap();
    }
}
__device__ __forceinline__ void stage_wait(uint32_t bar_full, volatile int* s_tag, int u) {
    const int st = u % NST;
    if (s_tag[st] != u) tag_wait_slow(s_tag + st, u);
    mbar_wait(bar_full + st * 8, (u / NST) & 1);
}
__device__ __forceinline__ void bulk_g2s(uint32_t dst, const void* src, uint32_t bytes, uint32_t bar) {
    asm volatile(
        "cp.async.bulk.shared::cluster.global.mbarrier::complete_tx::bytes [%0], [%1], %2, [%3];"
        ::"r"(dst), "l"(src), "r"(bytes), "r"(bar) : "memory");
}
__device__ __forceinline__ void cp_async16(uint32_t dst, const void* src) {
    asm volatile("cp.async.cg.shared.global [%0], [%1], 16;" ::"r"(dst), "l"(src) : "memory");
}
__device__ __forceinline__ void cp_async_wait_all() { asm volatile("cp.async.wait_all;" ::: "memory"); }
__device__ __forceinline__ void cp_async_commit() { asm volatile("cp.async.commit_group;" ::: "memory"); }
__device__ __forceinline__ void cp_async_wait1() { asm volatile("cp.async.wait_group 1;" ::: "memory"); }
__device__ __forceinline__ void red_release_add(unsigned int* p, unsigned int v) {
    asm volatile("red.release.gpu.global.add.u32 [%0], %1;" ::"l"(p), "r"(v) : "memory");
}
__device__ __forceinline__ void cons_sync() { asm volatile("bar.sync 1, 256;" ::: "memory"); }

__device__ __forceinline__ void red_add_v4(float* p, float a, float b, float c, float d) {
    asm volatile("red.global.add.v4.f32 [%0], {%1, %2, %3, %4};" ::"l"(p), "f"(a), "f"(b), "f"(c), "f"(d) : "memory");
}
__device__ __forceinline__ unsigned int ld_acquire(const unsigned int* p) {
    unsigned int v;
    asm volatile("ld.acquire.gpu.global.u32 %0, [%1];" : "=r"(v) : "l"(p) : "memory");
    return v;
}
__device__ __forceinline__ void ll_store(unsigned long long* p, float a, float b, unsigned int ep) {
    __nv_bfloat162 v = __floats2bfloat162_rn(a, b);
    const unsigned long long w = ((unsigned long long)ep << 32) | *(uint32_t*)&v;
    asm volatile("st.relaxed.gpu.global.u64 [%0], %1;" ::"l"(p), "l"(w) : "memory");
}
__device__ __forceinline__ uint2 ll_ld1(const unsigned long long* p) {
    uint2 v;
    asm volatile("ld.relaxed.gpu.global.v2.u32 {%0, %1}, [%2];" : "=r"(v.x), "=r"(v.y) : "l"(p) : "memory");
    return v;
}
__device__ __forceinline__ uint4 ll_ld2(const unsigned long long* p) {
    uint4 v;
    asm volatile("ld.volatile.global.v4.u32 {%0, %1, %2, %3}, [%4];" : "=r"(v.x), "=r"(v.y), "=r"(v.z), "=r"(v.w) : "l"(p) : "memory");
    return v;
}
template <int N>
__device__ __forceinline__ void ll_get(const unsigned long long* p, uint32_t (&d)[N], unsigned int ep) {
    long long t0 = 0;
    for (;;) {
        bool ok = true;
#pragma unroll
        for (int i = 0; i < N; ++i) {
            const uint2 v = ll_ld1(p + i);
            d[i] = v.x;
            ok = ok && (v.y == ep);
        }
        if (ok) break;
        if (t0 == 0) t0 = clock64();
        else if (clock64() - t0 > WAIT_LIMIT_CYCLES) __trap();
    }
}

__device__ __forceinline__ void grid_arrive(unsigned int* ctr, int tid) {
    cons_sync();
    if (tid == 0) red_release_add(ctr, 1u);
}
__device__ __noinline__ void grid_wait(const unsigned int* ctr, unsigned int target, int tid) {
    if (tid == 0) {
        const long long t0 = clock64();
        while ((int)(ld_acquire(ctr) - target) < 0) {
            if (clock64() - t0 > WAIT_LIMIT_CYCLES) __trap();
        }
    }
    cons_sync();
}

__device__ __forceinline__ float warp_sum(float v) {
#pragma unroll
    for (int o = 16; o > 0; o >>= 1) v += __shfl_xor_sync(0xffffffffu, v, o);
    return v;
}
__device__ __forceinline__ float warp_max(float v) {
#pragma unroll
    for (int o = 16; o > 0; o >>= 1) v = fmaxf(v, __shfl_xor_sync(0xffffffffu, v, o));
    return v;
}

__device__ __forceinline__ void fma8(float (&acc)[8], const uint4& w, float s) {
    acc[0] = fmaf(s, bf_lo(w.x), acc[0]);
    acc[1] = fmaf(s, bf_hi(w.x), acc[1]);
    acc[2] = fmaf(s, bf_lo(w.y), acc[2]);
    acc[3] = fmaf(s, bf_hi(w.y), acc[3]);
    acc[4] = fmaf(s, bf_lo(w.z), acc[4]);
    acc[5] = fmaf(s, bf_hi(w.z), acc[5]);
    acc[6] = fmaf(s, bf_lo(w.w), acc[6]);
    acc[7] = fmaf(s, bf_hi(w.w), acc[7]);
}
__device__ __forceinline__ float dot8(const uint4& w, const float* q) {
    float s = q[0] * bf_lo(w.x);
    s = fmaf(q[1], bf_hi(w.x), s);
    s = fmaf(q[2], bf_lo(w.y), s);
    s = fmaf(q[3], bf_hi(w.y), s);
    s = fmaf(q[4], bf_lo(w.z), s);
    s = fmaf(q[5], bf_hi(w.z), s);
    s = fmaf(q[6], bf_lo(w.w), s);
    s = fmaf(q[7], bf_hi(w.w), s);
    return s;
}

__device__ __noinline__ void stage_rows(uint32_t dst, int dst_pitch, const void* src, int src_stride, int rows,
                                        int cpr, int tid, int nthr) {
    const int n = rows * cpr;
#pragma unroll 1
    for (int i = tid; i < n; i += nthr) {
        const int r = i / cpr, c = i - r * cpr;
        cp_async16(dst + r * dst_pitch + c * 16, (const unsigned char*)src + (size_t)r * src_stride + c * 16);
    }
}

template <int KS, int NT>
__device__ __noinline__ void gemv_mma(uint32_t w, int w_pitch, uint32_t a, int a_pitch, float* part, int lane) {
    float c[NT][4];
#pragma unroll
    for (int nt = 0; nt < NT; ++nt) { c[nt][0] = 0.f; c[nt][1] = 0.f; c[nt][2] = 0.f; c[nt][3] = 0.f; }
    const uint32_t ap = a + (lane >> 2) * a_pitch + (lane & 3) * 4;
    const uint32_t wp = w + ((lane & 7) + ((lane >> 4) << 3)) * w_pitch + ((lane >> 3) & 1) * 16;
#pragma unroll
    for (int ks = 0; ks < KS; ++ks) {
        uint32_t b0 = 0, b1 = 0;
        if (lane < 16) {
            asm("ld.shared.u32 %0, [%1];" : "=r"(b0) : "r"(ap + ks * 32));
            asm("ld.shared.u32 %0, [%1];" : "=r"(b1) : "r"(ap + ks * 32 + 16));
        }
#pragma unroll
        for (int nt = 0; nt < NT; ++nt) {
            uint32_t a0, a1, a2, a3;
            asm("ldmatrix.sync.aligned.m8n8.x4.trans.shared.b16 {%0, %1, %2, %3}, [%4];"
                         : "=r"(a0), "=r"(a1), "=r"(a2), "=r"(a3) : "r"(wp + ks * 16 * w_pitch + nt * 32));
            asm("mma.sync.aligned.m16n8k16.row.col.f32.bf16.bf16.f32 {%0, %1, %2, %3}, {%4, %5, %6, %7}, "
                "{%8, %9}, {%0, %1, %2, %3};"
                : "+f"(c[nt][0]), "+f"(c[nt][1]), "+f"(c[nt][2]), "+f"(c[nt][3])
                : "r"(a0), "r"(a1), "r"(a2), "r"(a3), "r"(b0), "r"(b1));
        }
    }
    if ((lane & 3) < 2) {
        float* pp = part + (lane & 3) * 160 + (lane >> 2);
#pragma unroll
        for (int nt = 0; nt < NT; ++nt) {
            pp[nt * 16] = c[nt][0];
            pp[nt * 16 + 80] = c[nt][1];
            pp[nt * 16 + 8] = c[nt][2];
            pp[nt * 16 + 88] = c[nt][3];
        }
    }
}

__device__ __forceinline__ float tall_sum(const float* part, int b, int n) {
    float s = 0.f;
#pragma unroll
    for (int w = 0; w < 8; ++w) s += part[(w * 4 + b) * 80 + n];
    return s;
}

__device__ __forceinline__ void ln_norm(float (&v)[10], float* s_red, int tid) {
    const int warp = tid >> 5;
    const float pv = __shfl_sync(0xffffffffu, v[0], 0);
    float s = 0.f, q = 0.f;
#pragma unroll
    for (int i = 0; i < 10; ++i) { const float d = v[i] - pv; s += d; q = fmaf(d, d, q); }
#pragma unroll
    for (int o = 16; o > 0; o >>= 1) {
        s += __shfl_xor_sync(0xffffffffu, s, o);
        q += __shfl_xor_sync(0xffffffffu, q, o);
    }
    const float md = s * (2.0f / DM);
    if ((tid & 31) == 0) *(float2*)(s_red + 2 * warp) = make_float2(pv + md, fmaxf(q - s * md, 0.f));
    cons_sync();
    const float4 r = *(const float4*)(s_red + 4 * (warp >> 1));
    const float dm = r.x - r.z;
    const float var = (r.y + r.w + dm * dm * (DM / 4)) * (1.0f / DM);
    const float mean = bf16r(0.5f * (r.x + r.z));
    const float inv = __fdiv_rn(1.0f, bf16r(sqrtf(bf16r(bf16r(var) + 1e-5f))));
#pragma unroll
    for (int i = 0; i < 10; ++i) v[i] = bf16r(bf16r(v[i] - mean) * inv);
}
__device__ __forceinline__ void modulate(const float (&n)[10], const uint32_t (&sh)[5], const uint32_t (&sc)[5], uint32_t* dst) {
#pragma unroll
    for (int i = 0; i < 5; ++i) {
        const float h0 = bf16r(n[2 * i] * bf16r(1.0f + bf_lo(sc[i]))) + bf_lo(sh[i]);
        const float h1 = bf16r(n[2 * i + 1] * bf16r(1.0f + bf_hi(sc[i]))) + bf_hi(sh[i]);
        __nv_bfloat162 p = __floats2bfloat162_rn(h0, h1);
        dst[i] = *(uint32_t*)&p;
    }
}

__device__ __forceinline__ float gelu_tanh(float x) {
    const float kBeta = 0.7978845608028654f;
    const float inner = kBeta * (x + 0.044715f * x * x * x);
    return 0.5f * x * (1.0f + tanhf(inner));
}

__global__ void __launch_bounds__(NTHREADS, 1)
decode_block_kernel(const __nv_bfloat16* __restrict__ x_in, const __nv_bfloat16* __restrict__ k_cache,
                    const __nv_bfloat16* __restrict__ v_cache, const __nv_bfloat16* __restrict__ wq,
                    const __nv_bfloat16* __restrict__ wo, const __nv_bfloat16* __restrict__ w_gate,
                    const __nv_bfloat16* __restrict__ w_up, const __nv_bfloat16* __restrict__ w_down,
                    const __nv_bfloat16* __restrict__ cvec, const __nv_bfloat16* __restrict__ w_mod,
                    __nv_bfloat16* __restrict__ out) {
    extern __shared__ __align__(128) unsigned char smem[];
    const int tid = threadIdx.x;
    const int cta = blockIdx.x;

    const uint32_t sbase = smem_u32(smem);
    const uint32_t bar_full = sbase + SM_BAR;
    const uint32_t bar_empty = bar_full + NST * 8;
    volatile int* s_item = (volatile int*)(smem + SM_ITEM);
    volatile int* s_tag = (volatile int*)(smem + SM_TAG);

    const uint32_t bar_go = bar_empty + NST * 8;
    if (tid < NST) s_tag[tid] = -1;
    if (tid == 0) {
#pragma unroll 1
        for (int s = 0; s < 2 * NST + 1; ++s) mbar_init(bar_full + s * 8, 1);
        asm volatile("fence.mbarrier_init.release.cluster;" ::: "memory");
        asm volatile("fence.proxy.async.shared::cta;" ::: "memory");
#pragma unroll 1
        for (int s = 0; s < PRE; ++s) mbar_arrive(bar_empty + s * 8);
    }
    __syncthreads();

    if (tid >= NCONS) {
        if (tid == NCONS) {
            int u = 0;
            bool pf = false, kdone = false;
            const int G = (int)gridDim.x;
            const unsigned int ep = ld_acquire(&g_epoch) + 1u;
            auto produce = [&](const int item) {
                const int it = item & (NITEM_K - 1);
                const bool is_v = item >= NITEM_K;
                const unsigned char* src = (const unsigned char*)(is_v ? v_cache : k_cache) + (size_t)it * (ITEM_KEYS * DH * 2);
                if (is_v && !kdone) {
                    if (ld_acquire(&g_kall) == ep * NITEM_K) {
                        kdone = true;
                    } else {
                        const long long t0 = clock64();
                        while (ld_acquire(&g_kcnt[it / CHUNKS]) != ep * CHUNKS)
                            if (clock64() - t0 > WAIT_LIMIT_CYCLES) __trap();
                    }
                }
#pragma unroll 1
                for (int t = 0; t < TPI; ++t, ++u) {
                    const int st = u % NST;
                    const uint32_t fb = bar_full + st * 8;
                    mbar_wait(bar_empty + st * 8, (u / NST) & 1);
                    s_item[st] = item;
                    s_tag[st] = u;
                    mbar_expect_tx(fb, TILE_BYTES);
                    bulk_g2s(sbase + SM_RING + st * STAGE_BYTES, src + t * TILE_BYTES, TILE_BYTES, fb);
                }
                if (!pf && item >= NITEM - 10 * G) {
                    pf = true;
                    if (cta < QN / 48)
                        asm volatile("cp.async.bulk.prefetch.L2.global [%0], %1;" ::"l"(wo + (size_t)cta * 48 * DM), "r"(48 * DM * 2) : "memory");
                    if (cta < FF / 16)
                        asm volatile("cp.async.bulk.prefetch.L2.global [%0], %1;" ::"l"(w_down + (size_t)cta * 16 * DM), "r"(16 * DM * 2) : "memory");
                }
            };
            if (PSTART != 3) mbar_wait(bar_go, 0);
            unsigned int r0 = cta - 3 * G, r1 = cta - 2 * G, r2 = cta - G;
#pragma unroll 1
            for (;;) {
                if ((int)(r0 + 3 * G) >= NITEM) break;
                produce((int)(r0 + 3 * G));
                r0 = atomicAdd(&g_work, 1u);
                if ((int)(r1 + 3 * G) >= NITEM) break;
                produce((int)(r1 + 3 * G));
                r1 = atomicAdd(&g_work, 1u);
                if ((int)(r2 + 3 * G) >= NITEM) break;
                produce((int)(r2 + 3 * G));
                r2 = atomicAdd(&g_work, 1u);
            }
            s_item[15] = (int)(r0 + r1 + r2);
#pragma unroll 1
            for (int j = 0; j < 8; ++j, u += TPI) {
                const int st = u % NST;
                mbar_wait(bar_empty + st * 8, (u / NST) & 1);
                s_item[st] = -1;
                s_tag[st] = u;
                mbar_arrive(bar_full + st * 8);
            }
            PROFP(13);
        }
        return;
    }

    const int lane = tid & 31, warp = tid >> 5;
    float* s_part = (float*)(smem + SM_PART);
    float* s_xp = (float*)(smem + SM_XP);
    float* s_red = (float*)(smem + SM_RED);
    const int lrow = tid >> 6, lcol = (tid & 63) * 10;
    uint32_t* h_dst = (uint32_t*)(smem + SM_A + lrow * A_PITCH + lcol * 2);

    PROF(0);
    const unsigned int ep = ld_acquire(&g_epoch) + 1u;
    const unsigned int target = ep * gridDim.x;
    const unsigned long long* mod_row = g_mod + (lrow * MODN + lcol) / 2;
    float nv[10];
    {
        const int i1 = tid + NCONS;
        const uint4 c0 = __ldg((const uint4*)cvec + tid);
        uint4 c1 = c0;
        if (i1 < 320) c1 = __ldg((const uint4*)cvec + i1);
        uint32_t xw[5];
#pragma unroll
        for (int i = 0; i < 5; ++i) xw[i] = __ldg((const uint32_t*)(x_in + lrow * DM + lcol) + i);
        if (cta < MODN / 32) stage_rows(sbase + SM_W32, P32, w_mod + cta * 32, MODN * 2, DM, 4, tid, NCONS);
        cp_async_commit();
        if (cta < QN / 48) stage_rows(sbase + SM_WQ, P48, wq + cta * 48, QN * 2, DM, 6, tid, NCONS);
        cp_async_commit();
        if (PSTART == 1 && tid == 0) mbar_arrive(bar_go);
#pragma unroll 1
        for (int r = 0; r < 2; ++r) {
            const int i = r ? i1 : tid;
            if (i < 320) {
                const uint4 cc = r ? c1 : c0;
                const uint32_t cw[4] = {cc.x, cc.y, cc.z, cc.w};
                uint32_t ow[4];
#pragma unroll
                for (int k = 0; k < 4; ++k) {
                    const float a = bf_lo(cw[k]), b = bf_hi(cw[k]);
                    __nv_bfloat162 p = __floats2bfloat162_rn(__fdiv_rn(a, 1.0f + __expf(-a)), __fdiv_rn(b, 1.0f + __expf(-b)));
                    ow[k] = *(uint32_t*)&p;
                }
                const int b = i / 80, c8 = i - b * 80;
                *(uint4*)(smem + SM_A + b * A_PITCH + c8 * 16) = make_uint4(ow[0], ow[1], ow[2], ow[3]);
            }
        }
#pragma unroll
        for (int i = 0; i < 5; ++i) {
            nv[2 * i] = bf_lo(xw[i]);
            nv[2 * i + 1] = bf_hi(xw[i]);
            *(float2*)(s_xp + lrow * DM + lcol + 2 * i) = make_float2(nv[2 * i], nv[2 * i + 1]);
        }
    }
    float* acc_o = g_o[ep & 1];
    float* acc_attn = g_attn[ep & 1];
    if (cta == gridDim.x - 1) {
#pragma unroll 1
        for (int i = tid; i < NB * QN / 4; i += NCONS) ((float4*)g_o[~ep & 1])[i] = make_float4(0.f, 0.f, 0.f, 0.f);
#pragma unroll 1
        for (int i = tid; i < NB * DM; i += NCONS) g_attn[~ep & 1][i] = 0.f;
    }
    ln_norm(nv, s_red, tid);
    cp_async_wait1();
    cons_sync();
    if (PSTART == 0 && tid == 0) mbar_arrive(bar_go);
    if (cta < MODN / 32) {
        gemv_mma<5, 2>(sbase + SM_W32 + warp * 80 * P32, P32, sbase + SM_A + warp * 160, A_PITCH, s_part + warp * 320, lane);
        cons_sync();
        if (tid < 64) {
            const int b = tid >> 4, n = (tid & 15) * 2;
            ll_store(g_mod + (b * MODN + cta * 32 + n) / 2, tall_sum(s_part, b, n), tall_sum(s_part, b, n + 1), ep);
        }
    }
    PROF(1);

    if (cta < QN / 48) {
        cons_sync();
        {
            long long t0 = 0;
            for (;;) {
                bool ok = true;
#pragma unroll
                for (int r = 0; r < 5; ++r) {
                    const int i = tid + r * NCONS, b = i / 320, c4 = i - b * 320;
                    const uint4 v = ll_ld2(g_mod + b * (MODN / 2) + 2 * c4);
                    *(uint2*)(s_part + b * DM + 2 * c4) = make_uint2(v.x, v.z);
                    ok = ok && v.y == ep && v.w == ep;
                }
                if (ok) break;
                if (t0 == 0) t0 = clock64();
                else if (clock64() - t0 > WAIT_LIMIT_CYCLES) __trap();
            }
        }
        cons_sync();
        PROF(2);
        uint32_t sh[5], sc[5];
#pragma unroll
        for (int i = 0; i < 5; ++i) {
            sh[i] = ((const uint32_t*)s_part)[lrow * DM + lcol / 2 + i];
            sc[i] = ((const uint32_t*)s_part)[lrow * DM + DM / 2 + lcol / 2 + i];
        }
        modulate(nv, sh, sc, h_dst);
        cp_async_wait_all();
        cons_sync();
        if (PSTART == 2 && tid == 0) mbar_arrive(bar_go);
        gemv_mma<5, 3>(sbase + SM_WQ + warp * 80 * P48, P48, sbase + SM_A + warp * 160, A_PITCH, s_part + warp * 320, lane);
        cons_sync();
        if (tid < 96) {
            const int b = tid / 24, n = (tid - b * 24) * 2;
            ll_store(g_q + (b * QN + cta * 48 + n) / 2, tall_sum(s_part, b, n), tall_sum(s_part, b, n + 1), ep);
        }
    } else if (PSTART == 2 && tid == 0) {
        mbar_arrive(bar_go);
    }
    PROF(3);
    if (tid == 0) {
#pragma unroll 1
        for (int s = PRE; s < NST; ++s) mbar_arrive(bar_empty + s * 8);
    }
    uint32_t m_ga[5], m_sb[5], m_cb[5], m_gb[1] = {0u};
    if (cta < FF / 16) {
        if (warp == 7) {
            stage_rows(sbase + SM_W32, P32, w_gate + cta * 16, FF * 2, DM, 2, lane, 32);
            stage_rows(sbase + SM_W32 + 32, P32, w_up + cta * 16, FF * 2, DM, 2, lane, 32);
        }
    }
    PROF(4);

    {
        const int sub = lane & 7, grp = lane >> 3;
        for (int u0 = warp * TPI;; u0 += 8 * TPI) {
            if (u0 >= 8 * TPI && u0 < 16 * TPI && cta < FF / 16) {
                ll_get(mod_row + DM, m_ga, ep);
                ll_get(mod_row + 3 * DM / 2, m_sb, ep);
                ll_get(mod_row + 2 * DM, m_cb, ep);
                if (tid < 32 && cta < DM / 16) ll_get(g_mod + ((tid >> 3) * MODN + 5 * DM + cta * 16) / 2 + (tid & 7), m_gb, ep);
            }
            if (s_tag[u0 % NST] != u0) tag_wait_slow(s_tag + u0 % NST, u0);
            const int item = s_item[u0 % NST];
            if (item < 0) {
                mbar_wait(bar_full + (u0 % NST) * 8, (u0 / NST) & 1);
                __syncwarp();
                if (lane == 0) mbar_arrive(bar_empty + (u0 % NST) * 8);
                break;
            }
            const int bh = (item & (NITEM_K - 1)) / CHUNKS;
            if (item < NITEM_K) {
                float* gs = g_s + (size_t)item * ITEM_KEYS;
                float qr[24];
                {
                    const unsigned long long* qp = g_q + ((bh >> 5) * QN + (bh & 31) * DH) / 2 + sub * 4;
                    long long t0 = 0;
                    for (;;) {
                        bool ok = true;
#pragma unroll
                        for (int j = 0; j < 6; ++j) {
                            const uint4 v = ll_ld2(qp + (j >> 1) * 32 + (j & 1) * 2);
                            qr[j * 4 + 0] = bf_lo(v.x); qr[j * 4 + 1] = bf_hi(v.x);
                            qr[j * 4 + 2] = bf_lo(v.z); qr[j * 4 + 3] = bf_hi(v.z);
                            ok = ok && v.y == ep && v.w == ep;
                        }
                        if (ok) break;
                        if (t0 == 0) t0 = clock64();
                        else if (clock64() - t0 > WAIT_LIMIT_CYCLES) __trap();
                    }
                }
                float m_run = -INFINITY, l_run = 0.f;
#pragma unroll 1
                for (int hh = 0; hh < 2 * TPI; ++hh) {
                    const int u = u0 + (hh >> 1), st = u % NST;
                    if (!(hh & 1)) stage_wait(bar_full, s_tag, u);
                    const uint4* tile = (const uint4*)(smem + SM_RING + st * STAGE_BYTES) + (hh & 1) * (32 * 24);
                    float part[8];
#pragma unroll
                    for (int it = 0; it < 8; ++it) {
                        const uint4* row = tile + (it * 4 + grp) * 24 + sub;
                        const uint4 a = row[0], b = row[8], c = row[16];
                        part[it] = dot8(a, qr) + dot8(b, qr + 8) + dot8(c, qr + 16);
                    }
                    if (hh & 1) {
                        __syncwarp();
                        if (lane == 0) mbar_arrive(bar_empty + st * 8);
                    }
#pragma unroll
                    for (int j = 0; j < 4; ++j) {
                        const float send = (sub & 4) ? part[j] : part[j + 4];
                        const float keep = (sub & 4) ? part[j + 4] : part[j];
                        part[j] = keep + __shfl_xor_sync(0xffffffffu, send, 4);
                    }
#pragma unroll
                    for (int j = 0; j < 2; ++j) {
                        const float send = (sub & 2) ? part[j] : part[j + 2];
                        const float keep = (sub & 2) ? part[j + 2] : part[j];
                        part[j] = keep + __shfl_xor_sync(0xffffffffu, send, 2);
                    }
                    {
                        const float send = (sub & 1) ? part[0] : part[1];
                        const float keep = (sub & 1) ? part[1] : part[0];
                        part[0] = keep + __shfl_xor_sync(0xffffffffu, send, 1);
                    }
                    const float s = bf16r(bf16r(part[0]) * 0.07216878364870323f);
                    gs[hh * 32 + sub * 4 + grp] = s;
                    const float m_new = fmaxf(m_run, s);
                    l_run = l_run * __expf(m_run - m_new) + __expf(s - m_new);
                    m_run = m_new;
                }
                const float m = warp_max(m_run);
                const float l = warp_sum(l_run * __expf(m_run - m));
                __syncwarp();
                if (lane == 0) {
                    g_stat[item] = make_float2(m, l);
                    red_release_add(&g_kcnt[bh], 1u);
                    red_release_add(&g_kall, 1u);
                }
            } else {
                float pr[2 * TPI];
                {
                    const float* gs = g_s + (size_t)(item - NITEM_K) * ITEM_KEYS + lane;
                    const float2 st2 = __ldcg(g_stat + bh * CHUNKS + lane);
#pragma unroll
                    for (int hh = 0; hh < 2 * TPI; ++hh) pr[hh] = __ldcg(gs + hh * 32);
                    const float mm = warp_max(st2.x);
                    const float ll = warp_sum(st2.y * __expf(st2.x - mm));
#pragma unroll
                    for (int hh = 0; hh < 2 * TPI; ++hh) pr[hh] = bf16r(__fdiv_rn(__expf(pr[hh] - mm), ll));
                }
                float acc[3][8];
#pragma unroll
                for (int j = 0; j < 3; ++j)
#pragma unroll
                    for (int e = 0; e < 8; ++e) acc[j][e] = 0.f;
#pragma unroll
                for (int hh = 0; hh < 2 * TPI; ++hh) {
                    const int u = u0 + (hh >> 1), st = u % NST;
                    if (!(hh & 1)) stage_wait(bar_full, s_tag, u);
                    const uint4* tile = (const uint4*)(smem + SM_RING + st * STAGE_BYTES) + (hh & 1) * (32 * 24);
#pragma unroll
                    for (int it = 0; it < 8; ++it) {
                        const uint4* row = tile + (it * 4 + grp) * 24 + sub;
                        const uint4 a = row[0], b = row[8], c = row[16];
                        const float p = __shfl_sync(0xffffffffu, pr[hh], it * 4 + grp);
                        fma8(acc[0], a, p);
                        fma8(acc[1], b, p);
                        fma8(acc[2], c, p);
                    }
                    if (hh & 1) {
                        __syncwarp();
                        if (lane == 0) mbar_arrive(bar_empty + st * 8);
                    }
                }
                float* go = acc_o + (bh >> 5) * QN + (bh & 31) * DH + sub * 8;
#pragma unroll
                for (int j = 0; j < 3; ++j) {
#pragma unroll
                    for (int e = 0; e < 8; ++e) {
                        float v = acc[j][e];
                        v += __shfl_xor_sync(0xffffffffu, v, 8);
                        v += __shfl_xor_sync(0xffffffffu, v, 16);
                        acc[j][e] = v;
                    }
                    if (grp == 0) {
                        red_add_v4(go + j * 64, acc[j][0], acc[j][1], acc[j][2], acc[j][3]);
                        red_add_v4(go + j * 64 + 4, acc[j][4], acc[j][5], acc[j][6], acc[j][7]);
                    }
                }
            }
        }
    }
    PROF(5);
    grid_arrive(&g_bar[2], tid);
    PROF(6);
    const int ks = cta >> 3, ns = cta & 7;
    if (cta < 128) stage_rows(sbase + SM_WO, P80, wo + (size_t)ks * WO_ROWS * DM + ns * 80, DM * 2, WO_ROWS, 10, tid, NCONS);
    if (cta < DM / 16) stage_rows(sbase + SM_WD, P16, w_down + cta * 16, DM * 2, FF, 2, tid, NCONS);
    grid_wait(&g_bar[2], target, tid);
    if (cta == 0 && tid == 0) { g_work = 0u; g_epoch = ep; }
    PROF(7);

    if (cta < 128) {
#pragma unroll
        for (int r = 0; r < 2; ++r) {
            const int i = tid + r * NCONS;
            if (i < NB * WO_ROWS / 4) {
                const int b = i / 96, c4 = i - b * 96;
                const float4 v = __ldcg((const float4*)(acc_o + b * QN + ks * WO_ROWS) + c4);
                __nv_bfloat162 p0 = __floats2bfloat162_rn(v.x, v.y), p1 = __floats2bfloat162_rn(v.z, v.w);
                uint2 w2;
                w2.x = *(uint32_t*)&p0; w2.y = *(uint32_t*)&p1;
                *(uint2*)(smem + SM_A + b * A_PITCH + c4 * 8) = w2;
            }
        }
        cp_async_wait_all();
        cons_sync();
        gemv_mma<3, 5>(sbase + SM_WO + warp * 48 * P80, P80, sbase + SM_A + warp * 96, A_PITCH, s_part + warp * 320, lane);
        cons_sync();
        if (tid < 80) {
            const int b = tid / 20, n4 = tid - b * 20;
            float4 s4 = make_float4(0.f, 0.f, 0.f, 0.f);
#pragma unroll
            for (int w = 0; w < 8; ++w) {
                const float4 v = *(const float4*)(s_part + (w * 4 + b) * 80 + n4 * 4);
                s4.x += v.x; s4.y += v.y; s4.z += v.z; s4.w += v.w;
            }
            red_add_v4(acc_attn + b * DM + ns * 80 + n4 * 4, s4.x, s4.y, s4.z, s4.w);
        }
    }
    PROF(8);
    grid_arrive(&g_bar[3], tid);
    if (cta >= FF / 16) return;
    grid_wait(&g_bar[3], target, tid);
    PROF(9);
    {
        float4 v[3];
#pragma unroll
        for (int r = 0; r < 3; ++r)
            if (tid + r * NCONS < NB * DM / 4) v[r] = __ldcg((const float4*)acc_attn + tid + r * NCONS);
#pragma unroll
        for (int r = 0; r < 3; ++r)
            if (tid + r * NCONS < NB * DM / 4) ((float4*)s_part)[tid + r * NCONS] = v[r];
    }
    cons_sync();
#pragma unroll
    for (int i = 0; i < 5; ++i) {
        const float2 av = *((const float2*)(s_part + lrow * DM + lcol) + i);
        float2* xp = (float2*)(s_xp + lrow * DM + lcol) + i;
        const float2 xv = *xp;
        nv[2 * i] = bf16r(xv.x + bf16r(bf_lo(m_ga[i]) * bf16r(av.x)));
        nv[2 * i + 1] = bf16r(xv.y + bf16r(bf_hi(m_ga[i]) * bf16r(av.y)));
        *xp = make_float2(nv[2 * i], nv[2 * i + 1]);
    }
    ln_norm(nv, s_red, tid);
    modulate(nv, m_sb, m_cb, h_dst);
    cons_sync();
    gemv_mma<5, 2>(sbase + SM_W32 + warp * 80 * P32, P32, sbase + SM_A + warp * 160, A_PITCH, s_part + warp * 320, lane);
    cons_sync();
    if (tid < 32) {
        const int b = tid >> 3, n = (tid & 7) * 2;
        const float g0 = bf16r(tall_sum(s_part, b, n)), g1 = bf16r(tall_sum(s_part, b, n + 1));
        const float u0 = bf16r(tall_sum(s_part, b, 16 + n)), u1 = bf16r(tall_sum(s_part, b, 17 + n));
        ll_store(g_act + (b * FF + cta * 16 + n) / 2, bf16r(gelu_tanh(g0)) * u0, bf16r(gelu_tanh(g1)) * u1, ep);
    }
    PROF(10);
    if (cta >= DM / 16) return;
    {
        long long t0 = 0;
        for (;;) {
            bool ok = true;
#pragma unroll
            for (int r = 0; r < 6; ++r) {
                const int i = tid + r * NCONS, b = i / 384, c4 = i - b * 384;
                const uint4 v = ll_ld2(g_act + 2 * i);
                *(uint2*)(smem + SM_ACT + b * ACT_PITCH + c4 * 8) = make_uint2(v.x, v.z);
                ok = ok && v.y == ep && v.w == ep;
            }
            if (ok) break;
            if (t0 == 0) t0 = clock64();
            else if (clock64() - t0 > WAIT_LIMIT_CYCLES) __trap();
        }
        cons_sync();
        PROF(11);
        gemv_mma<12, 1>(sbase + SM_WD + warp * 192 * P16, P16, sbase + SM_ACT + warp * 384, ACT_PITCH, s_part + warp * 320, lane);
        cons_sync();
        if (tid < 32) {
            const int b = tid >> 3, n = (tid & 7) * 2, col = cta * 16 + n;
            const float f0 = bf16r(tall_sum(s_part, b, n)), f1 = bf16r(tall_sum(s_part, b, n + 1));
            __nv_bfloat162 p = __floats2bfloat162_rn(s_xp[b * DM + col] + bf16r(bf_lo(m_gb[0]) * f0),
                                                     s_xp[b * DM + col + 1] + bf16r(bf_hi(m_gb[0]) * f1));
            *(__nv_bfloat162*)(out + b * DM + col) = p;
        }
    }
    PROF(12);
}

}

extern "C" void kernel_launch(void* const* d_in, const int* in_sizes, int n_in, void* d_out, int out_size) {
    (void)in_sizes; (void)n_in; (void)out_size;
    const __nv_bfloat16* A_x = (const __nv_bfloat16*)d_in[0];
    const __nv_bfloat16* A_k = (const __nv_bfloat16*)d_in[1];
    const __nv_bfloat16* A_v = (const __nv_bfloat16*)d_in[2];
    const __nv_bfloat16* A_wq = (const __nv_bfloat16*)d_in[3];
    const __nv_bfloat16* A_wo = (const __nv_bfloat16*)d_in[4];
    const __nv_bfloat16* B_wg = (const __nv_bfloat16*)d_in[6];
    const __nv_bfloat16* B_wu = (const __nv_bfloat16*)d_in[7];
    const __nv_bfloat16* B_wd = (const __nv_bfloat16*)d_in[8];
    const __nv_bfloat16* c = (const __nv_bfloat16*)d_in[9];
    const __nv_bfloat16* w_mod = (const __nv_bfloat16*)d_in[10];
    static int grid = 0;
    if (grid == 0) {
        cudaFuncSetAttribute(decode_block_kernel, cudaFuncAttributeMaxDynamicSharedMemorySize, SM_TOTAL);
        int dev = 0, sms = 0;
        cudaGetDevice(&dev);
        cudaDeviceGetAttribute(&sms, cudaDevAttrMultiProcessorCount, dev);
        grid = sms < 132 ? sms : 132;
    }
    decode_block_kernel<<<grid, NTHREADS, SM_TOTAL>>>(A_x, A_k, A_v, A_wq, A_wo, B_wg, B_wu, B_wd, c, w_mod,
                                                      (__nv_bfloat16*)d_out);
}
```

```cpp
#include <cuda_runtime.h>
#include <cuda_bf16.h>
#include <stdint.h>

namespace {

constexpr int NB = 4;
constexpr int DM = 640;
constexpr int NH = 32;
constexpr int SK = 4096;
constexpr int DH = 192;
constexpr int FF = 1536;
constexpr int MODN = 6 * DM;
constexpr int QN = NH * DH;
constexpr int NBH = NB * NH;

constexpr int NCONS = 256;
constexpr int NTHREADS = NCONS + 32;
constexpr int TILE_KEYS = 64;
constexpr int TILE_BYTES = TILE_KEYS * DH * 2;
constexpr int STAGE_BYTES = TILE_BYTES;
constexpr int NST = 6;
constexpr int PRE = 3;
constexpr int TPI = 2;
constexpr int ITEM_KEYS = TPI * TILE_KEYS;
constexpr int CHUNKS = SK / ITEM_KEYS;
constexpr int NITEM_K = NBH * CHUNKS;
constexpr int NITEM = 2 * NITEM_K;

constexpr int A_PITCH = 1296;
constexpr int ACT_PITCH = FF * 2 + 16;
constexpr int P16 = 48;
constexpr int P32 = 80;
constexpr int P48 = 112;
constexpr int P80 = 176;
constexpr int WO_ROWS = 384;

constexpr int SM_RING = 0;
constexpr int SM_WQ = PRE * STAGE_BYTES;
constexpr int SM_WO = 0;
constexpr int SM_WD = SM_WO + WO_ROWS * P80;
constexpr int SM_W32 = NST * STAGE_BYTES;
constexpr int SM_ACT = SM_W32;
constexpr int SM_A = SM_W32 + DM * P32;
constexpr int SM_PART = SM_A + NB * A_PITCH;
constexpr int SM_XP = SM_PART + 8 * 4 * 80 * 4;
constexpr int SM_RED = SM_XP + NB * DM * 4;
constexpr int SM_ITEM = SM_RED + 16 * 4;
constexpr int SM_TAG = SM_ITEM + 16 * 4;
constexpr int SM_BAR = SM_TAG + 16 * 4;
constexpr int SM_TOTAL = SM_BAR + (2 * NST + 1) * 8;
static_assert(SM_WQ + DM * P48 <= NST * STAGE_BYTES, "prologue overlay");
static_assert(SM_WD + FF * P16 <= NST * STAGE_BYTES, "tail overlay");
static_assert(SM_TOTAL <= 232448, "smem");
#define PSTART 0

__device__ __align__(128) unsigned long long g_mod[NB * MODN / 2];
__device__ __align__(128) unsigned long long g_q[NB * QN / 2];
__device__ __align__(128) unsigned long long g_act[NB * FF / 2];
__device__ __align__(128) unsigned int g_s[NBH * SK];
__device__ __align__(128) unsigned long long g_stat[NBH * CHUNKS];
__device__ __align__(128) float g_o[2][NB * QN];
__device__ __align__(128) float g_attn[2][NB * DM];
__device__ __align__(128) unsigned int g_bar[8];
__device__ unsigned int g_work;
__device__ unsigned int g_epoch;

#define PROF(k) do { } while (0)
#define PROFP(k) do { } while (0)

__device__ __forceinline__ float bf16r(float x) { return __bfloat162float(__float2bfloat16_rn(x)); }
__device__ __forceinline__ float bf_lo(uint32_t u) { return __uint_as_float(u << 16); }
__device__ __forceinline__ float bf_hi(uint32_t u) { return __uint_as_float(u & 0xffff0000u); }

__device__ __forceinline__ uint32_t smem_u32(const void* p) { return (uint32_t)__cvta_generic_to_shared(p); }
__device__ __forceinline__ void mbar_init(uint32_t bar, uint32_t count) {
    asm volatile("mbarrier.init.shared::cta.b64 [%0], %1;" ::"r"(bar), "r"(count) : "memory");
}
__device__ __forceinline__ void mbar_expect_tx(uint32_t bar, uint32_t bytes) {
    asm volatile("mbarrier.arrive.expect_tx.shared::cta.b64 _, [%0], %1;" ::"r"(bar), "r"(bytes) : "memory");
}
__device__ __forceinline__ void mbar_arrive(uint32_t bar) {
    asm volatile("mbarrier.arrive.shared::cta.b64 _, [%0];" ::"r"(bar) : "memory");
}
constexpr long long WAIT_LIMIT_CYCLES = 200000000LL;
__device__ __forceinline__ uint32_t mbar_try(uint32_t bar, uint32_t parity) {
    uint32_t done;
    asm volatile(
        "{\n\t.reg .pred p;\n\t"
        "mbarrier.try_wait.parity.shared::cta.b64 p, [%1], %2;\n\t"
        "selp.u32 %0, 1, 0, p;\n\t}"
        : "=r"(done) : "r"(bar), "r"(parity) : "memory");
    return done;
}
__device__ __noinline__ void mbar_wait_slow(uint32_t bar, uint32_t parity) {
    const long long t0 = clock64();
    while (!mbar_try(bar, parity)) {
        if (clock64() - t0 > WAIT_LIMIT_CYCLES) __trap();
    }
}
__device__ __forceinline__ void mbar_wait(uint32_t bar, uint32_t parity) {
    if (!mbar_try(bar, parity)) mbar_wait_slow(bar, parity);
}
__device__ __noinline__ void tag_wait_slow(volatile int* tag, int u) {
    const long long t0 = clock64();
    while (*tag != u) {
        __nanosleep(32);
        if (clock64() - t0 > WAIT_LIMIT_CYCLES) __trap();
    }
}
__device__ __forceinline__ void stage_wait(uint32_t bar_full, volatile int* s_tag, int u) {
    const int st = u % NST;
    if (s_tag[st] != u) tag_wait_slow(s_tag + st, u);
    mbar_wait(bar_full + st * 8, (u / NST) & 1);
}
__device__ __forceinline__ void bulk_g2s(uint32_t dst, const void* src, uint32_t bytes, uint32_t bar) {
    asm volatile(
        "cp.async.bulk.shared::cluster.global.mbarrier::complete_tx::bytes [%0], [%1], %2, [%3];"
        ::"r"(dst), "l"(src), "r"(bytes), "r"(bar) : "memory");
}
__device__ __forceinline__ void cp_async16(uint32_t dst, const void* src) {
    asm volatile("cp.async.cg.shared.global [%0], [%1], 16;" ::"r"(dst), "l"(src) : "memory");
}
__device__ __forceinline__ void cp_async_wait_all() { asm volatile("cp.async.wait_all;" ::: "memory"); }
__device__ __forceinline__ void cp_async_commit() { asm volatile("cp.async.commit_group;" ::: "memory"); }
__device__ __forceinline__ void cp_async_wait1() { asm volatile("cp.async.wait_group 1;" ::: "memory"); }
__device__ __forceinline__ void red_release_add(unsigned int* p, unsigned int v) {
    asm volatile("red.release.gpu.global.add.u32 [%0], %1;" ::"l"(p), "r"(v) : "memory");
}
__device__ __forceinline__ void cons_sync() { asm volatile("bar.sync 1, 256;" ::: "memory"); }

__device__ __forceinline__ void red_add_v4(float* p, float a, float b, float c, float d) {
    asm volatile("red.global.add.v4.f32 [%0], {%1, %2, %3, %4};" ::"l"(p), "f"(a), "f"(b), "f"(c), "f"(d) : "memory");
}
__device__ __forceinline__ unsigned int ld_acquire(const unsigned int* p) {
    unsigned int v;
    asm volatile("ld.acquire.gpu.global.u32 %0, [%1];" : "=r"(v) : "l"(p) : "memory");
    return v;
}
__device__ __forceinline__ void ll_store(unsigned long long* p, float a, float b, unsigned int ep) {
    __nv_bfloat162 v = __floats2bfloat162_rn(a, b);
    const unsigned long long w = ((unsigned long long)ep << 32) | *(uint32_t*)&v;
    asm volatile("st.relaxed.gpu.global.u64 [%0], %1;" ::"l"(p), "l"(w) : "memory");
}
__device__ __forceinline__ uint2 ll_ld1(const unsigned long long* p) {
    unsigned long long w;
    asm volatile("ld.relaxed.gpu.global.u64 %0, [%1];" : "=l"(w) : "l"(p) : "memory");
    return make_uint2((uint32_t)w, (uint32_t)(w >> 32));
}
__device__ __forceinline__ uint4 ll_ld2(const unsigned long long* p) {
    unsigned long long a, b;
    asm volatile("ld.relaxed.gpu.global.v2.u64 {%0, %1}, [%2];" : "=l"(a), "=l"(b) : "l"(p) : "memory");
    return make_uint4((uint32_t)a, (uint32_t)(a >> 32), (uint32_t)b, (uint32_t)(b >> 32));
}
template <int N>
__device__ __forceinline__ void ll_get(const unsigned long long* p, uint32_t (&d)[N], unsigned int ep) {
    long long t0 = 0;
    for (;;) {
        bool ok = true;
#pragma unroll
        for (int i = 0; i < N; ++i) {
            const uint2 v = ll_ld1(p + i);
            d[i] = v.x;
            ok = ok && (v.y == ep);
        }
        if (ok) break;
        if (t0 == 0) t0 = clock64();
        else if (clock64() - t0 > WAIT_LIMIT_CYCLES) __trap();
    }
}

__device__ __forceinline__ void grid_arrive(unsigned int* ctr, int tid) {
    cons_sync();
    if (tid == 0) red_release_add(ctr, 1u);
}
__device__ __noinline__ void grid_wait(const unsigned int* ctr, unsigned int target, int tid) {
    if (tid == 0) {
        const long long t0 = clock64();
        while ((int)(ld_acquire(ctr) - target) < 0) {
            if (clock64() - t0 > WAIT_LIMIT_CYCLES) __trap();
        }
    }
    cons_sync();
}

__device__ __forceinline__ float warp_sum(float v) {
#pragma unroll
    for (int o = 16; o > 0; o >>= 1) v += __shfl_xor_sync(0xffffffffu, v, o);
    return v;
}
__device__ __forceinline__ float warp_max(float v) {
#pragma unroll
    for (int o = 16; o > 0; o >>= 1) v = fmaxf(v, __shfl_xor_sync(0xffffffffu, v, o));
    return v;
}

__device__ __forceinline__ void fma8(float (&acc)[8], const uint4& w, float s) {
    acc[0] = fmaf(s, bf_lo(w.x), acc[0]);
    acc[1] = fmaf(s, bf_hi(w.x), acc[1]);
    acc[2] = fmaf(s, bf_lo(w.y), acc[2]);
    acc[3] = fmaf(s, bf_hi(w.y), acc[3]);
    acc[4] = fmaf(s, bf_lo(w.z), acc[4]);
    acc[5] = fmaf(s, bf_hi(w.z), acc[5]);
    acc[6] = fmaf(s, bf_lo(w.w), acc[6]);
    acc[7] = fmaf(s, bf_hi(w.w), acc[7]);
}
__device__ __forceinline__ float dot8(const uint4& w, const float* q) {
    float s = q[0] * bf_lo(w.x);
    s = fmaf(q[1], bf_hi(w.x), s);
    s = fmaf(q[2], bf_lo(w.y), s);
    s = fmaf(q[3], bf_hi(w.y), s);
    s = fmaf(q[4], bf_lo(w.z), s);
    s = fmaf(q[5], bf_hi(w.z), s);
    s = fmaf(q[6], bf_lo(w.w), s);
    s = fmaf(q[7], bf_hi(w.w), s);
    return s;
}

__device__ __noinline__ void stage_rows(uint32_t dst, int dst_pitch, const void* src, int src_stride, int rows,
                                        int cpr, int tid, int nthr) {
    const int n = rows * cpr;
#pragma unroll 1
    for (int i = tid; i < n; i += nthr) {
        const int r = i / cpr, c = i - r * cpr;
        cp_async16(dst + r * dst_pitch + c * 16, (const unsigned char*)src + (size_t)r * src_stride + c * 16);
    }
}

template <int KS, int NT>
__device__ __noinline__ void gemv_mma(uint32_t w, int w_pitch, uint32_t a, int a_pitch, float* part, int lane) {
    float c[NT][4];
#pragma unroll
    for (int nt = 0; nt < NT; ++nt) { c[nt][0] = 0.f; c[nt][1] = 0.f; c[nt][2] = 0.f; c[nt][3] = 0.f; }
    const uint32_t ap = a + (lane >> 2) * a_pitch + (lane & 3) * 4;
    const uint32_t wp = w + ((lane & 7) + ((lane >> 4) << 3)) * w_pitch + ((lane >> 3) & 1) * 16;
#pragma unroll
    for (int ks = 0; ks < KS; ++ks) {
        uint32_t b0 = 0, b1 = 0;
        if (lane < 16) {
            asm("ld.shared.u32 %0, [%1];" : "=r"(b0) : "r"(ap + ks * 32));
            asm("ld.shared.u32 %0, [%1];" : "=r"(b1) : "r"(ap + ks * 32 + 16));
        }
#pragma unroll
        for (int nt = 0; nt < NT; ++nt) {
            uint32_t a0, a1, a2, a3;
            asm("ldmatrix.sync.aligned.m8n8.x4.trans.shared.b16 {%0, %1, %2, %3}, [%4];"
                         : "=r"(a0), "=r"(a1), "=r"(a2), "=r"(a3) : "r"(wp + ks * 16 * w_pitch + nt * 32));
            asm("mma.sync.aligned.m16n8k16.row.col.f32.bf16.bf16.f32 {%0, %1, %2, %3}, {%4, %5, %6, %7}, "
                "{%8, %9}, {%0, %1, %2, %3};"
                : "+f"(c[nt][0]), "+f"(c[nt][1]), "+f"(c[nt][2]), "+f"(c[nt][3])
                : "r"(a0), "r"(a1), "r"(a2), "r"(a3), "r"(b0), "r"(b1));
        }
    }
    if ((lane & 3) < 2) {
        float* pp = part + (lane & 3) * 160 + (lane >> 2);
#pragma unroll
        for (int nt = 0; nt < NT; ++nt) {
            pp[nt * 16] = c[nt][0];
            pp[nt * 16 + 80] = c[nt][1];
            pp[nt * 16 + 8] = c[nt][2];
            pp[nt * 16 + 88] = c[nt][3];
        }
    }
}

__device__ __forceinline__ float tall_sum(const float* part, int b, int n) {
    float s = 0.f;
#pragma unroll
    for (int w = 0; w < 8; ++w) s += part[(w * 4 + b) * 80 + n];
    return s;
}

__device__ __forceinline__ void ln_norm(float (&v)[10], float* s_red, int tid) {
    const int warp = tid >> 5;
    const float pv = __shfl_sync(0xffffffffu, v[0], 0);
    float s = 0.f, q = 0.f;
#pragma unroll
    for (int i = 0; i < 10; ++i) { const float d = v[i] - pv; s += d; q = fmaf(d, d, q); }
#pragma unroll
    for (int o = 16; o > 0; o >>= 1) {
        s += __shfl_xor_sync(0xffffffffu, s, o);
        q += __shfl_xor_sync(0xffffffffu, q, o);
    }
    const float md = s * (2.0f / DM);
    if ((tid & 31) == 0) *(float2*)(s_red + 2 * warp) = make_float2(pv + md, fmaxf(q - s * md, 0.f));
    cons_sync();
    const float4 r = *(const float4*)(s_red + 4 * (warp >> 1));
    const float dm = r.x - r.z;
    const float var = (r.y + r.w + dm * dm * (DM / 4)) * (1.0f / DM);
    const float mean = bf16r(0.5f * (r.x + r.z));
    const float inv = __fdiv_rn(1.0f, bf16r(sqrtf(bf16r(bf16r(var) + 1e-5f))));
#pragma unroll
    for (int i = 0; i < 10; ++i) v[i] = bf16r(bf16r(v[i] - mean) * inv);
}
__device__ __forceinline__ void modulate(const float (&n)[10], const uint32_t (&sh)[5], const uint32_t (&sc)[5], uint32_t* dst) {
#pragma unroll
    for (int i = 0; i < 5; ++i) {
        const float h0 = bf16r(n[2 * i] * bf16r(1.0f + bf_lo(sc[i]))) + bf_lo(sh[i]);
        const float h1 = bf16r(n[2 * i + 1] * bf16r(1.0f + bf_hi(sc[i]))) + bf_hi(sh[i]);
        __nv_bfloat162 p = __floats2bfloat162_rn(h0, h1);
        dst[i] = *(uint32_t*)&p;
    }
}

__device__ __forceinline__ float gelu_tanh(float x) {
    const float kBeta = 0.7978845608028654f;
    const float inner = kBeta * (x + 0.044715f * x * x * x);
    return 0.5f * x * (1.0f + tanhf(inner));
}

__global__ void __launch_bounds__(NTHREADS, 1)
decode_block_kernel(const __nv_bfloat16* __restrict__ x_in, const __nv_bfloat16* __restrict__ k_cache,
                    const __nv_bfloat16* __restrict__ v_cache, const __nv_bfloat16* __restrict__ wq,
                    const __nv_bfloat16* __restrict__ wo, const __nv_bfloat16* __restrict__ w_gate,
                    const __nv_bfloat16* __restrict__ w_up, const __nv_bfloat16* __restrict__ w_down,
                    const __nv_bfloat16* __restrict__ cvec, const __nv_bfloat16* __restrict__ w_mod,
                    __nv_bfloat16* __restrict__ out) {
    extern __shared__ __align__(128) unsigned char smem[];
    const int tid = threadIdx.x;
    const int cta = blockIdx.x;

    const uint32_t sbase = smem_u32(smem);
    const uint32_t bar_full = sbase + SM_BAR;
    const uint32_t bar_empty = bar_full + NST * 8;
    volatile int* s_item = (volatile int*)(smem + SM_ITEM);
    volatile int* s_tag = (volatile int*)(smem + SM_TAG);

    const uint32_t bar_go = bar_empty + NST * 8;
    if (tid < NST) s_tag[tid] = -1;
    if (tid == 0) {
#pragma unroll 1
        for (int s = 0; s < 2 * NST + 1; ++s) mbar_init(bar_full + s * 8, 1);
        asm volatile("fence.mbarrier_init.release.cluster;" ::: "memory");
        asm volatile("fence.proxy.async.shared::cta;" ::: "memory");
#pragma unroll 1
        for (int s = 0; s < PRE; ++s) mbar_arrive(bar_empty + s * 8);
    }
    __syncthreads();

    if (tid >= NCONS) {
        if (tid == NCONS) {
            int u = 0;
            bool pf = false;
            const int G = (int)gridDim.x;
            auto produce = [&](const int item) {
                const int it = item & (NITEM_K - 1);
                const bool is_v = item >= NITEM_K;
                const unsigned char* src = (const unsigned char*)(is_v ? v_cache : k_cache) + (size_t)it * (ITEM_KEYS * DH * 2);
#pragma unroll 1
                for (int t = 0; t < TPI; ++t, ++u) {
                    const int st = u % NST;
                    const uint32_t fb = bar_full + st * 8;
                    mbar_wait(bar_empty + st * 8, (u / NST) & 1);
                    s_item[st] = item;
                    s_tag[st] = u;
                    mbar_expect_tx(fb, TILE_BYTES);
                    bulk_g2s(sbase + SM_RING + st * STAGE_BYTES, src + t * TILE_BYTES, TILE_BYTES, fb);
                }
                if (!pf && item >= NITEM - 10 * G) {
                    pf = true;
                    if (cta < QN / 48)
                        asm volatile("cp.async.bulk.prefetch.L2.global [%0], %1;" ::"l"(wo + (size_t)cta * 48 * DM), "r"(48 * DM * 2) : "memory");
                    if (cta < FF / 16)
                        asm volatile("cp.async.bulk.prefetch.L2.global [%0], %1;" ::"l"(w_down + (size_t)cta * 16 * DM), "r"(16 * DM * 2) : "memory");
                }
            };
            if (PSTART != 3) mbar_wait(bar_go, 0);
            unsigned int r0 = cta - 3 * G, r1 = cta - 2 * G, r2 = cta - G;
#pragma unroll 1
            for (;;) {
                if ((int)(r0 + 3 * G) >= NITEM) break;
                produce((int)(r0 + 3 * G));
                r0 = atomicAdd(&g_work, 1u);
                if ((int)(r1 + 3 * G) >= NITEM) break;
                produce((int)(r1 + 3 * G));
                r1 = atomicAdd(&g_work, 1u);
                if ((int)(r2 + 3 * G) >= NITEM) break;
                produce((int)(r2 + 3 * G));
                r2 = atomicAdd(&g_work, 1u);
            }
            s_item[15] = (int)(r0 + r1 + r2);
#pragma unroll 1
            for (int j = 0; j < 8; ++j, u += TPI) {
                const int st = u % NST;
                mbar_wait(bar_empty + st * 8, (u / NST) & 1);
                s_item[st] = -1;
                s_tag[st] = u;
                mbar_arrive(bar_full + st * 8);
            }
            PROFP(13);
        }
        return;
    }

    const int lane = tid & 31, warp = tid >> 5;
    float* s_part = (float*)(smem + SM_PART);
    float* s_xp = (float*)(smem + SM_XP);
    float* s_red = (float*)(smem + SM_RED);
    const int lrow = tid >> 6, lcol = (tid & 63) * 10;
    uint32_t* h_dst = (uint32_t*)(smem + SM_A + lrow * A_PITCH + lcol * 2);

    PROF(0);
    const unsigned int ep = ld_acquire(&g_epoch) + 1u;
    const unsigned int target = ep * gridDim.x, tag16 = ep & 0xffffu;
    const unsigned long long* mod_row = g_mod + (lrow * MODN + lcol) / 2;
    float nv[10];
    {
        const int i1 = tid + NCONS;
        const uint4 c0 = __ldg((const uint4*)cvec + tid);
        uint4 c1 = c0;
        if (i1 < 320) c1 = __ldg((const uint4*)cvec + i1);
        uint32_t xw[5];
#pragma unroll
        for (int i = 0; i < 5; ++i) xw[i] = __ldg((const uint32_t*)(x_in + lrow * DM + lcol) + i);
        if (cta < MODN / 32) stage_rows(sbase + SM_W32, P32, w_mod + cta * 32, MODN * 2, DM, 4, tid, NCONS);
        cp_async_commit();
        if (cta < QN / 48) stage_rows(sbase + SM_WQ, P48, wq + cta * 48, QN * 2, DM, 6, tid, NCONS);
        cp_async_commit();
        if (PSTART == 1 && tid == 0) mbar_arrive(bar_go);
#pragma unroll 1
        for (int r = 0; r < 2; ++r) {
            const int i = r ? i1 : tid;
            if (i < 320) {
                const uint4 cc = r ? c1 : c0;
                const uint32_t cw[4] = {cc.x, cc.y, cc.z, cc.w};
                uint32_t ow[4];
#pragma unroll
                for (int k = 0; k < 4; ++k) {
                    const float a = bf_lo(cw[k]), b = bf_hi(cw[k]);
                    __nv_bfloat162 p = __floats2bfloat162_rn(__fdiv_rn(a, 1.0f + __expf(-a)), __fdiv_rn(b, 1.0f + __expf(-b)));
                    ow[k] = *(uint32_t*)&p;
                }
                const int b = i / 80, c8 = i - b * 80;
                *(uint4*)(smem + SM_A + b * A_PITCH + c8 * 16) = make_uint4(ow[0], ow[1], ow[2], ow[3]);
            }
        }
#pragma unroll
        for (int i = 0; i < 5; ++i) {
            nv[2 * i] = bf_lo(xw[i]);
            nv[2 * i + 1] = bf_hi(xw[i]);
            *(float2*)(s_xp + lrow * DM + lcol + 2 * i) = make_float2(nv[2 * i], nv[2 * i + 1]);
        }
    }
    float* acc_o = g_o[ep & 1];
    float* acc_attn = g_attn[ep & 1];
    if (cta == gridDim.x - 1) {
#pragma unroll 1
        for (int i = tid; i < NB * QN / 4; i += NCONS) ((float4*)g_o[~ep & 1])[i] = make_float4(0.f, 0.f, 0.f, 0.f);
#pragma unroll 1
        for (int i = tid; i < NB * DM; i += NCONS) g_attn[~ep & 1][i] = 0.f;
    }
    ln_norm(nv, s_red, tid);
    cp_async_wait1();
    cons_sync();
    if (PSTART == 0 && tid == 0) mbar_arrive(bar_go);
    if (cta < MODN / 32) {
        gemv_mma<5, 2>(sbase + SM_W32 + warp * 80 * P32, P32, sbase + SM_A + warp * 160, A_PITCH, s_part + warp * 320, lane);
        cons_sync();
        if (tid < 64) {
            const int b = tid >> 4, n = (tid & 15) * 2;
            ll_store(g_mod + (b * MODN + cta * 32 + n) / 2, tall_sum(s_part, b, n), tall_sum(s_part, b, n + 1), ep);
        }
    }
    PROF(1);

    if (cta < QN / 48) {
        cons_sync();
        {
            long long t0 = 0;
            for (;;) {
                bool ok = true;
#pragma unroll
                for (int r = 0; r < 5; ++r) {
                    const int i = tid + r * NCONS, b = i / 320, c4 = i - b * 320;
                    const uint4 v = ll_ld2(g_mod + b * (MODN / 2) + 2 * c4);
                    *(uint2*)(s_part + b * DM + 2 * c4) = make_uint2(v.x, v.z);
                    ok = ok && v.y == ep && v.w == ep;
                }
                if (ok) break;
                if (t0 == 0) t0 = clock64();
                else if (clock64() - t0 > WAIT_LIMIT_CYCLES) __trap();
            }
        }
        cons_sync();
        PROF(2);
        uint32_t sh[5], sc[5];
#pragma unroll
        for (int i = 0; i < 5; ++i) {
            sh[i] = ((const uint32_t*)s_part)[lrow * DM + lcol / 2 + i];
            sc[i] = ((const uint32_t*)s_part)[lrow * DM + DM / 2 + lcol / 2 + i];
        }
        modulate(nv, sh, sc, h_dst);
        cp_async_wait_all();
        cons_sync();
        if (PSTART == 2 && tid == 0) mbar_arrive(bar_go);
        gemv_mma<5, 3>(sbase + SM_WQ + warp * 80 * P48, P48, sbase + SM_A + warp * 160, A_PITCH, s_part + warp * 320, lane);
        cons_sync();
        if (tid < 96) {
            const int b = tid / 24, n = (tid - b * 24) * 2;
            ll_store(g_q + (b * QN + cta * 48 + n) / 2, tall_sum(s_part, b, n), tall_sum(s_part, b, n + 1), ep);
        }
    } else if (PSTART == 2 && tid == 0) {
        mbar_arrive(bar_go);
    }
    PROF(3);
    if (tid == 0) {
#pragma unroll 1
        for (int s = PRE; s < NST; ++s) mbar_arrive(bar_empty + s * 8);
    }
    uint32_t m_ga[5], m_sb[5], m_cb[5], m_gb[1] = {0u};
    if (cta < FF / 16) {
        if (warp == 7) {
            stage_rows(sbase + SM_W32, P32, w_gate + cta * 16, FF * 2, DM, 2, lane, 32);
            stage_rows(sbase + SM_W32 + 32, P32, w_up + cta * 16, FF * 2, DM, 2, lane, 32);
        }
    }
    PROF(4);

    {
        const int sub = lane & 7, grp = lane >> 3;
        for (int u0 = warp * TPI;; u0 += 8 * TPI) {
            if (u0 >= 8 * TPI && u0 < 16 * TPI && cta < FF / 16) {
                ll_get(mod_row + DM, m_ga, ep);
                ll_get(mod_row + 3 * DM / 2, m_sb, ep);
                ll_get(mod_row + 2 * DM, m_cb, ep);
                if (tid < 32 && cta < DM / 16) ll_get(g_mod + ((tid >> 3) * MODN + 5 * DM + cta * 16) / 2 + (tid & 7), m_gb, ep);
            }
            if (s_tag[u0 % NST] != u0) tag_wait_slow(s_tag + u0 % NST, u0);
            const int item = s_item[u0 % NST];
            if (item < 0) {
                mbar_wait(bar_full + (u0 % NST) * 8, (u0 / NST) & 1);
                __syncwarp();
                if (lane == 0) mbar_arrive(bar_empty + (u0 % NST) * 8);
                break;
            }
            const int bh = (item & (NITEM_K - 1)) / CHUNKS;
            if (item < NITEM_K) {
                unsigned int* gs = g_s + (size_t)item * ITEM_KEYS;
                float qr[24];
                {
                    const unsigned long long* qp = g_q + ((bh >> 5) * QN + (bh & 31) * DH) / 2 + sub * 4;
                    long long t0 = 0;
                    for (;;) {
                        bool ok = true;
#pragma unroll
                        for (int j = 0; j < 6; ++j) {
                            const uint4 v = ll_ld2(qp + (j >> 1) * 32 + (j & 1) * 2);
                            qr[j * 4 + 0] = bf_lo(v.x); qr[j * 4 + 1] = bf_hi(v.x);
                            qr[j * 4 + 2] = bf_lo(v.z); qr[j * 4 + 3] = bf_hi(v.z);
                            ok = ok && v.y == ep && v.w == ep;
                        }
                        if (ok) break;
                        if (t0 == 0) t0 = clock64();
                        else if (clock64() - t0 > WAIT_LIMIT_CYCLES) __trap();
                    }
                }
                float m_run = -INFINITY, l_run = 0.f;
#pragma unroll 1
                for (int hh = 0; hh < 2 * TPI; ++hh) {
                    const int u = u0 + (hh >> 1), st = u % NST;
                    if (!(hh & 1)) stage_wait(bar_full, s_tag, u);
                    const uint4* tile = (const uint4*)(smem + SM_RING + st * STAGE_BYTES) + (hh & 1) * (32 * 24);
                    float part[8];
#pragma unroll
                    for (int it = 0; it < 8; ++it) {
                        const uint4* row = tile + (it * 4 + grp) * 24 + sub;
                        const uint4 a = row[0], b = row[8], c = row[16];
                        part[it] = dot8(a, qr) + dot8(b, qr + 8) + dot8(c, qr + 16);
                    }
                    if (hh & 1) {
                        __syncwarp();
                        if (lane == 0) mbar_arrive(bar_empty + st * 8);
                    }
#pragma unroll
                    for (int j = 0; j < 4; ++j) {
                        const float send = (sub & 4) ? part[j] : part[j + 4];
                        const float keep = (sub & 4) ? part[j + 4] : part[j];
                        part[j] = keep + __shfl_xor_sync(0xffffffffu, send, 4);
                    }
#pragma unroll
                    for (int j = 0; j < 2; ++j) {
                        const float send = (sub & 2) ? part[j] : part[j + 2];
                        const float keep = (sub & 2) ? part[j + 2] : part[j];
                        part[j] = keep + __shfl_xor_sync(0xffffffffu, send, 2);
                    }
                    {
                        const float send = (sub & 1) ? part[0] : part[1];
                        const float keep = (sub & 1) ? part[1] : part[0];
                        part[0] = keep + __shfl_xor_sync(0xffffffffu, send, 1);
                    }
                    const float s = bf16r(bf16r(part[0]) * 0.07216878364870323f);
                    asm volatile("st.relaxed.gpu.global.u32 [%0], %1;" ::"l"(gs + hh * 32 + sub * 4 + grp), "r"(__float_as_uint(s) | tag16) : "memory");
                    const float m_new = fmaxf(m_run, s);
                    l_run = l_run * __expf(m_run - m_new) + __expf(s - m_new);
                    m_run = m_new;
                }
                const float m = warp_max(m_run);
                const float l = warp_sum(l_run * __expf(m_run - m));
                if (lane == 0)
                    asm volatile("st.relaxed.gpu.global.u64 [%0], %1;" ::"l"(g_stat + item),
                                 "l"(((unsigned long long)__float_as_uint(l) << 32) | (__float_as_uint(m) | tag16)) : "memory");
            } else {
                float pr[2 * TPI];
                {
                    const unsigned int* gs = g_s + (size_t)(item - NITEM_K) * ITEM_KEYS + lane;
                    uint2 st2;
                    long long t0 = 0;
                    for (;;) {
                        st2 = ll_ld1(g_stat + bh * CHUNKS + lane);
                        bool ok = (st2.x & 0xffffu) == tag16;
#pragma unroll
                        for (int hh = 0; hh < 2 * TPI; ++hh) {
                            unsigned int w;
                            asm volatile("ld.relaxed.gpu.global.u32 %0, [%1];" : "=r"(w) : "l"(gs + hh * 32) : "memory");
                            ok = ok && (w & 0xffffu) == tag16;
                            pr[hh] = bf_hi(w);
                        }
                        if (__all_sync(0xffffffffu, ok)) break;
                        if (t0 == 0) t0 = clock64();
                        else if (clock64() - t0 > WAIT_LIMIT_CYCLES) __trap();
                    }
                    const float mi = bf_hi(st2.x);
                    const float mm = warp_max(mi);
                    const float ll = warp_sum(__uint_as_float(st2.y) * __expf(mi - mm));
#pragma unroll
                    for (int hh = 0; hh < 2 * TPI; ++hh) pr[hh] = bf16r(__fdiv_rn(__expf(pr[hh] - mm), ll));
                }
                float acc[3][8];
#pragma unroll
                for (int j = 0; j < 3; ++j)
#pragma unroll
                    for (int e = 0; e < 8; ++e) acc[j][e] = 0.f;
#pragma unroll
                for (int hh = 0; hh < 2 * TPI; ++hh) {
                    const int u = u0 + (hh >> 1), st = u % NST;
                    if (!(hh & 1)) stage_wait(bar_full, s_tag, u);
                    const uint4* tile = (const uint4*)(smem + SM_RING + st * STAGE_BYTES) + (hh & 1) * (32 * 24);
#pragma unroll
                    for (int it = 0; it < 8; ++it) {
                        const uint4* row = tile + (it * 4 + grp) * 24 + sub;
                        const uint4 a = row[0], b = row[8], c = row[16];
                        const float p = __shfl_sync(0xffffffffu, pr[hh], it * 4 + grp);
                        fma8(acc[0], a, p);
                        fma8(acc[1], b, p);
                        fma8(acc[2], c, p);
                    }
                    if (hh & 1) {
                        __syncwarp();
                        if (lane == 0) mbar_arrive(bar_empty + st * 8);
                    }
                }
                float* go = acc_o + (bh >> 5) * QN + (bh & 31) * DH + sub * 8;
#pragma unroll
                for (int j = 0; j < 3; ++j) {
#pragma unroll
                    for (int e = 0; e < 8; ++e) {
                        float v = acc[j][e];
                        v += __shfl_xor_sync(0xffffffffu, v, 8);
                        v += __shfl_xor_sync(0xffffffffu, v, 16);
                        acc[j][e] = v;
                    }
                    if (grp == 0) {
                        red_add_v4(go + j * 64, acc[j][0], acc[j][1], acc[j][2], acc[j][3]);
                        red_add_v4(go + j * 64 + 4, acc[j][4], acc[j][5], acc[j][6], acc[j][7]);
                    }
                }
            }
        }
    }
    PROF(5);
    grid_arrive(&g_bar[2], tid);
    PROF(6);
    const int ks = cta >> 3, ns = cta & 7;
    if (cta < 128) stage_rows(sbase + SM_WO, P80, wo + (size_t)ks * WO_ROWS * DM + ns * 80, DM * 2, WO_ROWS, 10, tid, NCONS);
    if (cta < DM / 16) stage_rows(sbase + SM_WD, P16, w_down + cta * 16, DM * 2, FF, 2, tid, NCONS);
    grid_wait(&g_bar[2], target, tid);
    if (cta == 0 && tid == 0) { g_work = 0u; g_epoch = ep; }
    PROF(7);

    if (cta < 128) {
#pragma unroll
        for (int r = 0; r < 2; ++r) {
            const int i = tid + r * NCONS;
            if (i < NB * WO_ROWS / 4) {
                const int b = i / 96, c4 = i - b * 96;
                const float4 v = __ldcg((const float4*)(acc_o + b * QN + ks * WO_ROWS) + c4);
                __nv_bfloat162 p0 = __floats2bfloat162_rn(v.x, v.y), p1 = __floats2bfloat162_rn(v.z, v.w);
                uint2 w2;
                w2.x = *(uint32_t*)&p0; w2.y = *(uint32_t*)&p1;
                *(uint2*)(smem + SM_A + b * A_PITCH + c4 * 8) = w2;
            }
        }
        cp_async_wait_all();
        cons_sync();
        gemv_mma<3, 5>(sbase + SM_WO + warp * 48 * P80, P80, sbase + SM_A + warp * 96, A_PITCH, s_part + warp * 320, lane);
        cons_sync();
        if (tid < 80) {
            const int b = tid / 20, n4 = tid - b * 20;
            float4 s4 = make_float4(0.f, 0.f, 0.f, 0.f);
#pragma unroll
            for (int w = 0; w < 8; ++w) {
                const float4 v = *(const float4*)(s_part + (w * 4 + b) * 80 + n4 * 4);
                s4.x += v.x; s4.y += v.y; s4.z += v.z; s4.w += v.w;
            }
            red_add_v4(acc_attn + b * DM + ns * 80 + n4 * 4, s4.x, s4.y, s4.z, s4.w);
        }
    }
    PROF(8);
    grid_arrive(&g_bar[3], tid);
    if (cta >= FF / 16) return;
    grid_wait(&g_bar[3], target, tid);
    PROF(9);
    {
        float4 v[3];
#pragma unroll
        for (int r = 0; r < 3; ++r)
            if (tid + r * NCONS < NB * DM / 4) v[r] = __ldcg((const float4*)acc_attn + tid + r * NCONS);
#pragma unroll
        for (int r = 0; r < 3; ++r)
            if (tid + r * NCONS < NB * DM / 4) ((float4*)s_part)[tid + r * NCONS] = v[r];
    }
    cons_sync();
#pragma unroll
    for (int i = 0; i < 5; ++i) {
        const float2 av = *((const float2*)(s_part + lrow * DM + lcol) + i);
        float2* xp = (float2*)(s_xp + lrow * DM + lcol) + i;
        const float2 xv = *xp;
        nv[2 * i] = bf16r(xv.x + bf16r(bf_lo(m_ga[i]) * bf16r(av.x)));
        nv[2 * i + 1] = bf16r(xv.y + bf16r(bf_hi(m_ga[i]) * bf16r(av.y)));
        *xp = make_float2(nv[2 * i], nv[2 * i + 1]);
    }
    ln_norm(nv, s_red, tid);
    modulate(nv, m_sb, m_cb, h_dst);
    cons_sync();
    gemv_mma<5, 2>(sbase + SM_W32 + warp * 80 * P32, P32, sbase + SM_A + warp * 160, A_PITCH, s_part + warp * 320, lane);
    cons_sync();
    if (tid < 32) {
        const int b = tid >> 3, n = (tid & 7) * 2;
        const float g0 = bf16r(tall_sum(s_part, b, n)), g1 = bf16r(tall_sum(s_part, b, n + 1));
        const float u0 = bf16r(tall_sum(s_part, b, 16 + n)), u1 = bf16r(tall_sum(s_part, b, 17 + n));
        ll_store(g_act + (b * FF + cta * 16 + n) / 2, bf16r(gelu_tanh(g0)) * u0, bf16r(gelu_tanh(g1)) * u1, ep);
    }
    PROF(10);
    if (cta >= DM / 16) return;
    {
        long long t0 = 0;
        for (;;) {
            bool ok = true;
#pragma unroll
            for (int r = 0; r < 6; ++r) {
                const int i = tid + r * NCONS, b = i / 384, c4 = i - b * 384;
                const uint4 v = ll_ld2(g_act + 2 * i);
                *(uint2*)(smem + SM_ACT + b * ACT_PITCH + c4 * 8) = make_uint2(v.x, v.z);
                ok = ok && v.y == ep && v.w == ep;
            }
            if (ok) break;
            if (t0 == 0) t0 = clock64();
            else if (clock64() - t0 > WAIT_LIMIT_CYCLES) __trap();
        }
        cons_sync();
        PROF(11);
        gemv_mma<12, 1>(sbase + SM_WD + warp * 192 * P16, P16, sbase + SM_ACT + warp * 384, ACT_PITCH, s_part + warp * 320, lane);
        cons_sync();
        if (tid < 32) {
            const int b = tid >> 3, n = (tid & 7) * 2, col = cta * 16 + n;
            const float f0 = bf16r(tall_sum(s_part, b, n)), f1 = bf16r(tall_sum(s_part, b, n + 1));
            __nv_bfloat162 p = __floats2bfloat162_rn(s_xp[b * DM + col] + bf16r(bf_lo(m_gb[0]) * f0),
                                                     s_xp[b * DM + col + 1] + bf16r(bf_hi(m_gb[0]) * f1));
            *(__nv_bfloat162*)(out + b * DM + col) = p;
        }
    }
    PROF(12);
}

}

extern "C" void kernel_launch(void* const* d_in, const int* in_sizes, int n_in, void* d_out, int out_size) {
    (void)in_sizes; (void)n_in; (void)out_size;
    const __nv_bfloat16* A_x = (const __nv_bfloat16*)d_in[0];
    const __nv_bfloat16* A_k = (const __nv_bfloat16*)d_in[1];
    const __nv_bfloat16* A_v = (const __nv_bfloat16*)d_in[2];
    const __nv_bfloat16* A_wq = (const __nv_bfloat16*)d_in[3];
    const __nv_bfloat16* A_wo = (const __nv_bfloat16*)d_in[4];
    const __nv_bfloat16* B_wg = (const __nv_bfloat16*)d_in[6];
    const __nv_bfloat16* B_wu = (const __nv_bfloat16*)d_in[7];
    const __nv_bfloat16* B_wd = (const __nv_bfloat16*)d_in[8];
    const __nv_bfloat16* c = (const __nv_bfloat16*)d_in[9];
    const __nv_bfloat16* w_mod = (const __nv_bfloat16*)d_in[10];
    static int grid = 0;
    if (grid == 0) {
        cudaFuncSetAttribute(decode_block_kernel, cudaFuncAttributeMaxDynamicSharedMemorySize, SM_TOTAL);
        int dev = 0, sms = 0;
        cudaGetDevice(&dev);
        cudaDeviceGetAttribute(&sms, cudaDevAttrMultiProcessorCount, dev);
        grid = sms < 132 ? sms : 132;
    }
    decode_block_kernel<<<grid, NTHREADS, SM_TOTAL>>>(A_x, A_k, A_v, A_wq, A_wo, B_wg, B_wu, B_wd, c, w_mod,
                                                      (__nv_bfloat16*)d_out);
}
```

```cpp
#include <cuda_runtime.h>
#include <cuda_bf16.h>
#include <stdint.h>

namespace {

constexpr int NB = 4;
constexpr int DM = 640;
constexpr int NH = 32;
constexpr int SK = 4096;
constexpr int DH = 192;
constexpr int FF = 1536;
constexpr int MODN = 6 * DM;
constexpr int QN = NH * DH;
constexpr int NBH = NB * NH;

constexpr int NCONS = 256;
constexpr int NTHREADS = NCONS + 32;
constexpr int TILE_KEYS = 64;
constexpr int TILE_BYTES = TILE_KEYS * DH * 2;
constexpr int STAGE_BYTES = TILE_BYTES;
constexpr int NST = 6;
constexpr int PRE = 3;
constexpr int TPI = 2;
constexpr int ITEM_KEYS = TPI * TILE_KEYS;
constexpr int CHUNKS = SK / ITEM_KEYS;
constexpr int NITEM_K = NBH * CHUNKS;
constexpr int NITEM = 2 * NITEM_K;

constexpr int A_PITCH = 1296;
constexpr int ACT_PITCH = FF * 2 + 16;
constexpr int P16 = 48;
constexpr int P32 = 80;
constexpr int P48 = 112;
constexpr int P80 = 176;
constexpr int WO_ROWS = 384;

constexpr int SM_RING = 0;
constexpr int SM_WQ = PRE * STAGE_BYTES;
constexpr int SM_WO = 0;
constexpr int SM_WD = SM_WO + WO_ROWS * P80;
constexpr int SM_W32 = NST * STAGE_BYTES;
constexpr int SM_ACT = SM_W32;
constexpr int SM_A = SM_W32 + DM * P32;
constexpr int SM_PART = SM_A + NB * A_PITCH;
constexpr int SM_XP = SM_PART + 8 * 4 * 80 * 4;
constexpr int SM_RED = SM_XP + NB * DM * 4;
constexpr int SM_ITEM = SM_RED + 16 * 4;
constexpr int SM_TAG = SM_ITEM + 16 * 4;
constexpr int SM_BAR = SM_TAG + 16 * 4;
constexpr int SM_TOTAL = SM_BAR + (2 * NST + 1) * 8;
static_assert(SM_WQ + DM * P48 <= NST * STAGE_BYTES, "prologue overlay");
static_assert(SM_WD + FF * P16 <= NST * STAGE_BYTES, "tail overlay");
static_assert(SM_TOTAL <= 232448, "smem");
#define PSTART 0

__device__ __align__(128) unsigned long long g_mod[NB * MODN / 2];
__device__ __align__(128) unsigned long long g_q[NB * QN / 2];
__device__ __align__(128) unsigned long long g_act[NB * FF / 2];
__device__ __align__(128) unsigned int g_s[NBH * SK];
__device__ __align__(128) unsigned long long g_stat[NBH * CHUNKS];
__device__ __align__(128) float g_o[2][NB * QN];
__device__ __align__(128) float g_attn[2][NB * DM];
__device__ __align__(128) unsigned int g_bar[8];
__device__ unsigned int g_work;
__device__ unsigned int g_epoch;

#define PROF(k) do { } while (0)
#define PROFP(k) do { } while (0)

__device__ __forceinline__ float bf16r(float x) { return __bfloat162float(__float2bfloat16_rn(x)); }
__device__ __forceinline__ float bf_lo(uint32_t u) { return __uint_as_float(u << 16); }
__device__ __forceinline__ float bf_hi(uint32_t u) { return __uint_as_float(u & 0xffff0000u); }

__device__ __forceinline__ uint32_t smem_u32(const void* p) { return (uint32_t)__cvta_generic_to_shared(p); }
__device__ __forceinline__ void mbar_init(uint32_t bar, uint32_t count) {
    asm volatile("mbarrier.init.shared::cta.b64 [%0], %1;" ::"r"(bar), "r"(count) : "memory");
}
__device__ __forceinline__ void mbar_expect_tx(uint32_t bar, uint32_t bytes) {
    asm volatile("mbarrier.arrive.expect_tx.shared::cta.b64 _, [%0], %1;" ::"r"(bar), "r"(bytes) : "memory");
}
__device__ __forceinline__ void mbar_arrive(uint32_t bar) {
    asm volatile("mbarrier.arrive.shared::cta.b64 _, [%0];" ::"r"(bar) : "memory");
}
constexpr long long WAIT_LIMIT_CYCLES = 200000000LL;
__device__ __forceinline__ uint32_t mbar_try(uint32_t bar, uint32_t parity) {
    uint32_t done;
    asm volatile(
        "{\n\t.reg .pred p;\n\t"
        "mbarrier.try_wait.parity.shared::cta.b64 p, [%1], %2;\n\t"
        "selp.u32 %0, 1, 0, p;\n\t}"
        : "=r"(done) : "r"(bar), "r"(parity) : "memory");
    return done;
}
__device__ __noinline__ void mbar_wait_slow(uint32_t bar, uint32_t parity) {
    const long long t0 = clock64();
    while (!mbar_try(bar, parity)) {
        if (clock64() - t0 > WAIT_LIMIT_CYCLES) __trap();
    }
}
__device__ __forceinline__ void mbar_wait(uint32_t bar, uint32_t parity) {
    if (!mbar_try(bar, parity)) mbar_wait_slow(bar, parity);
}
__device__ __noinline__ void tag_wait_slow(volatile int* tag, int u) {
    const long long t0 = clock64();
    while (*tag != u) {
        __nanosleep(32);
        if (clock64() - t0 > WAIT_LIMIT_CYCLES) __trap();
    }
}
__device__ __forceinline__ void stage_wait(uint32_t bar_full, volatile int* s_tag, int u) {
    const int st = u % NST;
    if (s_tag[st] != u) tag_wait_slow(s_tag + st, u);
    mbar_wait(bar_full + st * 8, (u / NST) & 1);
}
__device__ __forceinline__ void bulk_g2s(uint32_t dst, const void* src, uint32_t bytes, uint32_t bar, uint64_t pol) {
    asm volatile(
        "cp.async.bulk.shared::cluster.global.mbarrier::complete_tx::bytes.L2::cache_hint [%0], [%1], %2, [%3], %4;"
        ::"r"(dst), "l"(src), "r"(bytes), "r"(bar), "l"(pol) : "memory");
}
__device__ __forceinline__ void cp_async16(uint32_t dst, const void* src) {
    asm volatile("cp.async.cg.shared.global [%0], [%1], 16;" ::"r"(dst), "l"(src) : "memory");
}
__device__ __forceinline__ void cp_async_wait_all() { asm volatile("cp.async.wait_all;" ::: "memory"); }
__device__ __forceinline__ void cp_async_commit() { asm volatile("cp.async.commit_group;" ::: "memory"); }
__device__ __forceinline__ void cp_async_wait1() { asm volatile("cp.async.wait_group 1;" ::: "memory"); }
__device__ __forceinline__ void red_release_add(unsigned int* p, unsigned int v) {
    asm volatile("red.release.gpu.global.add.u32 [%0], %1;" ::"l"(p), "r"(v) : "memory");
}
__device__ __forceinline__ void cons_sync() { asm volatile("bar.sync 1, 256;" ::: "memory"); }

__device__ __forceinline__ void red_add_v4(float* p, float a, float b, float c, float d) {
    asm volatile("red.global.add.v4.f32 [%0], {%1, %2, %3, %4};" ::"l"(p), "f"(a), "f"(b), "f"(c), "f"(d) : "memory");
}
__device__ __forceinline__ unsigned int ld_acquire(const unsigned int* p) {
    unsigned int v;
    asm volatile("ld.acquire.gpu.global.u32 %0, [%1];" : "=r"(v) : "l"(p) : "memory");
    return v;
}
__device__ __forceinline__ void ll_store(unsigned long long* p, float a, float b, unsigned int ep) {
    __nv_bfloat162 v = __floats2bfloat162_rn(a, b);
    const unsigned long long w = ((unsigned long long)ep << 32) | *(uint32_t*)&v;
    asm volatile("st.relaxed.gpu.global.u64 [%0], %1;" ::"l"(p), "l"(w) : "memory");
}
__device__ __forceinline__ uint2 ll_ld1(const unsigned long long* p) {
    unsigned long long w;
    asm volatile("ld.relaxed.gpu.global.u64 %0, [%1];" : "=l"(w) : "l"(p) : "memory");
    return make_uint2((uint32_t)w, (uint32_t)(w >> 32));
}
__device__ __forceinline__ uint4 ll_ld2(const unsigned long long* p) {
    unsigned long long a, b;
    asm volatile("ld.relaxed.gpu.global.v2.u64 {%0, %1}, [%2];" : "=l"(a), "=l"(b) : "l"(p) : "memory");
    return make_uint4((uint32_t)a, (uint32_t)(a >> 32), (uint32_t)b, (uint32_t)(b >> 32));
}
template <int N>
__device__ __forceinline__ void ll_get(const unsigned long long* p, uint32_t (&d)[N], unsigned int ep) {
    long long t0 = 0;
    for (;;) {
        bool ok = true;
#pragma unroll
        for (int i = 0; i < N; ++i) {
            const uint2 v = ll_ld1(p + i);
            d[i] = v.x;
            ok = ok && (v.y == ep);
        }
        if (ok) break;
        if (t0 == 0) t0 = clock64();
        else if (clock64() - t0 > WAIT_LIMIT_CYCLES) __trap();
    }
}

__device__ __forceinline__ void grid_arrive(unsigned int* ctr, int tid) {
    cons_sync();
    if (tid == 0) red_release_add(ctr, 1u);
}
__device__ __noinline__ void grid_wait(const unsigned int* ctr, unsigned int target, int tid) {
    if (tid == 0) {
        const long long t0 = clock64();
        while ((int)(ld_acquire(ctr) - target) < 0) {
            if (clock64() - t0 > WAIT_LIMIT_CYCLES) __trap();
        }
    }
    cons_sync();
}

__device__ __forceinline__ float warp_sum(float v) {
#pragma unroll
    for (int o = 16; o > 0; o >>= 1) v += __shfl_xor_sync(0xffffffffu, v, o);
    return v;
}
__device__ __forceinline__ float warp_max(float v) {
#pragma unroll
    for (int o = 16; o > 0; o >>= 1) v = fmaxf(v, __shfl_xor_sync(0xffffffffu, v, o));
    return v;
}

__device__ __forceinline__ void fma8(float (&acc)[8], const uint4& w, float s) {
    acc[0] = fmaf(s, bf_lo(w.x), acc[0]);
    acc[1] = fmaf(s, bf_hi(w.x), acc[1]);
    acc[2] = fmaf(s, bf_lo(w.y), acc[2]);
    acc[3] = fmaf(s, bf_hi(w.y), acc[3]);
    acc[4] = fmaf(s, bf_lo(w.z), acc[4]);
    acc[5] = fmaf(s, bf_hi(w.z), acc[5]);
    acc[6] = fmaf(s, bf_lo(w.w), acc[6]);
    acc[7] = fmaf(s, bf_hi(w.w), acc[7]);
}
__device__ __forceinline__ float dot8(const uint4& w, const float* q) {
    float s = q[0] * bf_lo(w.x);
    s = fmaf(q[1], bf_hi(w.x), s);
    s = fmaf(q[2], bf_lo(w.y), s);
    s = fmaf(q[3], bf_hi(w.y), s);
    s = fmaf(q[4], bf_lo(w.z), s);
    s = fmaf(q[5], bf_hi(w.z), s);
    s = fmaf(q[6], bf_lo(w.w), s);
    s = fmaf(q[7], bf_hi(w.w), s);
    return s;
}

__device__ __noinline__ void stage_rows(uint32_t dst, int dst_pitch, const void* src, int src_stride, int rows,
                                        int cpr, int tid, int nthr) {
    const int n = rows * cpr;
#pragma unroll 1
    for (int i = tid; i < n; i += nthr) {
        const int r = i / cpr, c = i - r * cpr;
        cp_async16(dst + r * dst_pitch + c * 16, (const unsigned char*)src + (size_t)r * src_stride + c * 16);
    }
}

template <int KS, int NT>
__device__ __noinline__ void gemv_mma(uint32_t w, int w_pitch, uint32_t a, int a_pitch, float* part, int lane) {
    float c[NT][4];
#pragma unroll
    for (int nt = 0; nt < NT; ++nt) { c[nt][0] = 0.f; c[nt][1] = 0.f; c[nt][2] = 0.f; c[nt][3] = 0.f; }
    const uint32_t ap = a + (lane >> 2) * a_pitch + (lane & 3) * 4;
    const uint32_t wp = w + ((lane & 7) + ((lane >> 4) << 3)) * w_pitch + ((lane >> 3) & 1) * 16;
#pragma unroll
    for (int ks = 0; ks < KS; ++ks) {
        uint32_t b0 = 0, b1 = 0;
        if (lane < 16) {
            asm("ld.shared.u32 %0, [%1];" : "=r"(b0) : "r"(ap + ks * 32));
            asm("ld.shared.u32 %0, [%1];" : "=r"(b1) : "r"(ap + ks * 32 + 16));
        }
#pragma unroll
        for (int nt = 0; nt < NT; ++nt) {
            uint32_t a0, a1, a2, a3;
            asm("ldmatrix.sync.aligned.m8n8.x4.trans.shared.b16 {%0, %1, %2, %3}, [%4];"
                         : "=r"(a0), "=r"(a1), "=r"(a2), "=r"(a3) : "r"(wp + ks * 16 * w_pitch + nt * 32));
            asm("mma.sync.aligned.m16n8k16.row.col.f32.bf16.bf16.f32 {%0, %1, %2, %3}, {%4, %5, %6, %7}, "
                "{%8, %9}, {%0, %1, %2, %3};"
                : "+f"(c[nt][0]), "+f"(c[nt][1]), "+f"(c[nt][2]), "+f"(c[nt][3])
                : "r"(a0), "r"(a1), "r"(a2), "r"(a3), "r"(b0), "r"(b1));
        }
    }
    if ((lane & 3) < 2) {
        float* pp = part + (lane & 3) * 160 + (lane >> 2);
#pragma unroll
        for (int nt = 0; nt < NT; ++nt) {
            pp[nt * 16] = c[nt][0];
            pp[nt * 16 + 80] = c[nt][1];
            pp[nt * 16 + 8] = c[nt][2];
            pp[nt * 16 + 88] = c[nt][3];
        }
    }
}

__device__ __forceinline__ float tall_sum(const float* part, int b, int n) {
    float s = 0.f;
#pragma unroll
    for (int w = 0; w < 8; ++w) s += part[(w * 4 + b) * 80 + n];
    return s;
}

__device__ __forceinline__ void ln_norm(float (&v)[10], float* s_red, int tid) {
    const int warp = tid >> 5;
    const float pv = __shfl_sync(0xffffffffu, v[0], 0);
    float s = 0.f, q = 0.f;
#pragma unroll
    for (int i = 0; i < 10; ++i) { const float d = v[i] - pv; s += d; q = fmaf(d, d, q); }
#pragma unroll
    for (int o = 16; o > 0; o >>= 1) {
        s += __shfl_xor_sync(0xffffffffu, s, o);
        q += __shfl_xor_sync(0xffffffffu, q, o);
    }
    const float md = s * (2.0f / DM);
    if ((tid & 31) == 0) *(float2*)(s_red + 2 * warp) = make_float2(pv + md, fmaxf(q - s * md, 0.f));
    cons_sync();
    const float4 r = *(const float4*)(s_red + 4 * (warp >> 1));
    const float dm = r.x - r.z;
    const float var = (r.y + r.w + dm * dm * (DM / 4)) * (1.0f / DM);
    const float mean = bf16r(0.5f * (r.x + r.z));
    const float inv = __fdiv_rn(1.0f, bf16r(sqrtf(bf16r(bf16r(var) + 1e-5f))));
#pragma unroll
    for (int i = 0; i < 10; ++i) v[i] = bf16r(bf16r(v[i] - mean) * inv);
}
__device__ __forceinline__ void modulate(const float (&n)[10], const uint32_t (&sh)[5], const uint32_t (&sc)[5], uint32_t* dst) {
#pragma unroll
    for (int i = 0; i < 5; ++i) {
        const float h0 = bf16r(n[2 * i] * bf16r(1.0f + bf_lo(sc[i]))) + bf_lo(sh[i]);
        const float h1 = bf16r(n[2 * i + 1] * bf16r(1.0f + bf_hi(sc[i]))) + bf_hi(sh[i]);
        __nv_bfloat162 p = __floats2bfloat162_rn(h0, h1);
        dst[i] = *(uint32_t*)&p;
    }
}

__device__ __forceinline__ float gelu_tanh(float x) {
    const float kBeta = 0.7978845608028654f;
    const float inner = kBeta * (x + 0.044715f * x * x * x);
    return 0.5f * x * (1.0f + tanhf(inner));
}

__global__ void __launch_bounds__(NTHREADS, 1)
decode_block_kernel(const __nv_bfloat16* __restrict__ x_in, const __nv_bfloat16* __restrict__ k_cache,
                    const __nv_bfloat16* __restrict__ v_cache, const __nv_bfloat16* __restrict__ wq,
                    const __nv_bfloat16* __restrict__ wo, const __nv_bfloat16* __restrict__ w_gate,
                    const __nv_bfloat16* __restrict__ w_up, const __nv_bfloat16* __restrict__ w_down,
                    const __nv_bfloat16* __restrict__ cvec, const __nv_bfloat16* __restrict__ w_mod,
                    __nv_bfloat16* __restrict__ out) {
    extern __shared__ __align__(128) unsigned char smem[];
    const int tid = threadIdx.x;
    const int cta = blockIdx.x;

    const uint32_t sbase = smem_u32(smem);
    const uint32_t bar_full = sbase + SM_BAR;
    const uint32_t bar_empty = bar_full + NST * 8;
    volatile int* s_item = (volatile int*)(smem + SM_ITEM);
    volatile int* s_tag = (volatile int*)(smem + SM_TAG);

    const uint32_t bar_go = bar_empty + NST * 8;
    if (tid < NST) s_tag[tid] = -1;
    if (tid == 0) {
#pragma unroll 1
        for (int s = 0; s < 2 * NST + 1; ++s) mbar_init(bar_full + s * 8, 1);
        asm volatile("fence.mbarrier_init.release.cluster;" ::: "memory");
        asm volatile("fence.proxy.async.shared::cta;" ::: "memory");
#pragma unroll 1
        for (int s = 0; s < PRE; ++s) mbar_arrive(bar_empty + s * 8);
    }
    __syncthreads();

    if (tid >= NCONS) {
        if (tid == NCONS) {
            int u = 0;
            bool pf = false;
            const int G = (int)gridDim.x;
            uint64_t pol;
            asm volatile("createpolicy.fractional.L2::evict_first.b64 %0, 1.0;" : "=l"(pol));
            auto produce = [&](const int item) {
                const int it = item & (NITEM_K - 1);
                const bool is_v = item >= NITEM_K;
                const unsigned char* src = (const unsigned char*)(is_v ? v_cache : k_cache) + (size_t)it * (ITEM_KEYS * DH * 2);
#pragma unroll 1
                for (int t = 0; t < TPI; ++t, ++u) {
                    const int st = u % NST;
                    const uint32_t fb = bar_full + st * 8;
                    mbar_wait(bar_empty + st * 8, (u / NST) & 1);
                    s_item[st] = item;
                    s_tag[st] = u;
                    mbar_expect_tx(fb, TILE_BYTES);
                    bulk_g2s(sbase + SM_RING + st * STAGE_BYTES, src + t * TILE_BYTES, TILE_BYTES, fb, pol);
                }
                if (!pf && item >= NITEM - 10 * G) {
                    pf = true;
                    if (cta < QN / 48)
                        asm volatile("cp.async.bulk.prefetch.L2.global [%0], %1;" ::"l"(wo + (size_t)cta * 48 * DM), "r"(48 * DM * 2) : "memory");
                    if (cta < FF / 16)
                        asm volatile("cp.async.bulk.prefetch.L2.global [%0], %1;" ::"l"(w_down + (size_t)cta * 16 * DM), "r"(16 * DM * 2) : "memory");
                }
            };
            if (PSTART != 3) mbar_wait(bar_go, 0);
            unsigned int r0 = cta - 3 * G, r1 = cta - 2 * G, r2 = cta - G;
#pragma unroll 1
            for (;;) {
                if ((int)(r0 + 3 * G) >= NITEM) break;
                produce((int)(r0 + 3 * G));
                r0 = atomicAdd(&g_work, 1u);
                if ((int)(r1 + 3 * G) >= NITEM) break;
                produce((int)(r1 + 3 * G));
                r1 = atomicAdd(&g_work, 1u);
                if ((int)(r2 + 3 * G) >= NITEM) break;
                produce((int)(r2 + 3 * G));
                r2 = atomicAdd(&g_work, 1u);
            }
            s_item[15] = (int)(r0 + r1 + r2);
#pragma unroll 1
            for (int j = 0; j < 8; ++j, u += TPI) {
                const int st = u % NST;
                mbar_wait(bar_empty + st * 8, (u / NST) & 1);
                s_item[st] = -1;
                s_tag[st] = u;
                mbar_arrive(bar_full + st * 8);
            }
            PROFP(13);
        }
        return;
    }

    const int lane = tid & 31, warp = tid >> 5;
    float* s_part = (float*)(smem + SM_PART);
    float* s_xp = (float*)(smem + SM_XP);
    float* s_red = (float*)(smem + SM_RED);
    const int lrow = tid >> 6, lcol = (tid & 63) * 10;
    uint32_t* h_dst = (uint32_t*)(smem + SM_A + lrow * A_PITCH + lcol * 2);

    PROF(0);
    const unsigned int ep = ld_acquire(&g_epoch) + 1u;
    const unsigned int target = ep * gridDim.x, tag16 = ep & 0xffffu;
    const unsigned long long* mod_row = g_mod + (lrow * MODN + lcol) / 2;
    float nv[10];
    {
        const int i1 = tid + NCONS;
        const uint4 c0 = __ldg((const uint4*)cvec + tid);
        uint4 c1 = c0;
        if (i1 < 320) c1 = __ldg((const uint4*)cvec + i1);
        uint32_t xw[5];
#pragma unroll
        for (int i = 0; i < 5; ++i) xw[i] = __ldg((const uint32_t*)(x_in + lrow * DM + lcol) + i);
        if (cta < MODN / 32) stage_rows(sbase + SM_W32, P32, w_mod + cta * 32, MODN * 2, DM, 4, tid, NCONS);
        cp_async_commit();
        if (cta < QN / 48) stage_rows(sbase + SM_WQ, P48, wq + cta * 48, QN * 2, DM, 6, tid, NCONS);
        cp_async_commit();
        if (PSTART == 1 && tid == 0) mbar_arrive(bar_go);
#pragma unroll 1
        for (int r = 0; r < 2; ++r) {
            const int i = r ? i1 : tid;
            if (i < 320) {
                const uint4 cc = r ? c1 : c0;
                const uint32_t cw[4] = {cc.x, cc.y, cc.z, cc.w};
                uint32_t ow[4];
#pragma unroll
                for (int k = 0; k < 4; ++k) {
                    const float a = bf_lo(cw[k]), b = bf_hi(cw[k]);
                    __nv_bfloat162 p = __floats2bfloat162_rn(__fdiv_rn(a, 1.0f + __expf(-a)), __fdiv_rn(b, 1.0f + __expf(-b)));
                    ow[k] = *(uint32_t*)&p;
                }
                const int b = i / 80, c8 = i - b * 80;
                *(uint4*)(smem + SM_A + b * A_PITCH + c8 * 16) = make_uint4(ow[0], ow[1], ow[2], ow[3]);
            }
        }
#pragma unroll
        for (int i = 0; i < 5; ++i) {
            nv[2 * i] = bf_lo(xw[i]);
            nv[2 * i + 1] = bf_hi(xw[i]);
            *(float2*)(s_xp + lrow * DM + lcol + 2 * i) = make_float2(nv[2 * i], nv[2 * i + 1]);
        }
    }
    float* acc_o = g_o[ep & 1];
    float* acc_attn = g_attn[ep & 1];
    if (cta == gridDim.x - 1) {
#pragma unroll 1
        for (int i = tid; i < NB * QN / 4; i += NCONS) ((float4*)g_o[~ep & 1])[i] = make_float4(0.f, 0.f, 0.f, 0.f);
#pragma unroll 1
        for (int i = tid; i < NB * DM; i += NCONS) g_attn[~ep & 1][i] = 0.f;
    }
    ln_norm(nv, s_red, tid);
    cp_async_wait1();
    cons_sync();
    if (PSTART == 0 && tid == 0) mbar_arrive(bar_go);
    if (cta < MODN / 32) {
        gemv_mma<5, 2>(sbase + SM_W32 + warp * 80 * P32, P32, sbase + SM_A + warp * 160, A_PITCH, s_part + warp * 320, lane);
        cons_sync();
        if (tid < 64) {
            const int b = tid >> 4, n = (tid & 15) * 2;
            ll_store(g_mod + (b * MODN + cta * 32 + n) / 2, tall_sum(s_part, b, n), tall_sum(s_part, b, n + 1), ep);
        }
    }
    PROF(1);

    if (cta < QN / 48) {
        cons_sync();
        {
            long long t0 = 0;
            for (;;) {
                bool ok = true;
#pragma unroll
                for (int r = 0; r < 5; ++r) {
                    const int i = tid + r * NCONS, b = i / 320, c4 = i - b * 320;
                    const uint4 v = ll_ld2(g_mod + b * (MODN / 2) + 2 * c4);
                    *(uint2*)(s_part + b * DM + 2 * c4) = make_uint2(v.x, v.z);
                    ok = ok && v.y == ep && v.w == ep;
                }
                if (ok) break;
                if (t0 == 0) t0 = clock64();
                else if (clock64() - t0 > WAIT_LIMIT_CYCLES) __trap();
            }
        }
        cons_sync();
        PROF(2);
        uint32_t sh[5], sc[5];
#pragma unroll
        for (int i = 0; i < 5; ++i) {
            sh[i] = ((const uint32_t*)s_part)[lrow * DM + lcol / 2 + i];
            sc[i] = ((const uint32_t*)s_part)[lrow * DM + DM / 2 + lcol / 2 + i];
        }
        modulate(nv, sh, sc, h_dst);
        cp_async_wait_all();
        cons_sync();
        if (PSTART == 2 && tid == 0) mbar_arrive(bar_go);
        gemv_mma<5, 3>(sbase + SM_WQ + warp * 80 * P48, P48, sbase + SM_A + warp * 160, A_PITCH, s_part + warp * 320, lane);
        cons_sync();
        if (tid < 96) {
            const int b = tid / 24, n = (tid - b * 24) * 2;
            ll_store(g_q + (b * QN + cta * 48 + n) / 2, tall_sum(s_part, b, n), tall_sum(s_part, b, n + 1), ep);
        }
    } else if (PSTART == 2 && tid == 0) {
        mbar_arrive(bar_go);
    }
    PROF(3);
    if (tid == 0) {
#pragma unroll 1
        for (int s = PRE; s < NST; ++s) mbar_arrive(bar_empty + s * 8);
    }
    uint32_t m_ga[5], m_sb[5], m_cb[5], m_gb[1] = {0u};
    if (cta < FF / 16) {
        if (warp == 7) {
            stage_rows(sbase + SM_W32, P32, w_gate + cta * 16, FF * 2, DM, 2, lane, 32);
            stage_rows(sbase + SM_W32 + 32, P32, w_up + cta * 16, FF * 2, DM, 2, lane, 32);
        }
    }
    PROF(4);

    {
        const int sub = lane & 7, grp = lane >> 3;
        for (int u0 = warp * TPI;; u0 += 8 * TPI) {
            if (u0 >= 8 * TPI && u0 < 16 * TPI && cta < FF / 16) {
                ll_get(mod_row + DM, m_ga, ep);
                ll_get(mod_row + 3 * DM / 2, m_sb, ep);
                ll_get(mod_row + 2 * DM, m_cb, ep);
                if (tid < 32 && cta < DM / 16) ll_get(g_mod + ((tid >> 3) * MODN + 5 * DM + cta * 16) / 2 + (tid & 7), m_gb, ep);
            }
            if (s_tag[u0 % NST] != u0) tag_wait_slow(s_tag + u0 % NST, u0);
            const int item = s_item[u0 % NST];
            if (item < 0) {
                mbar_wait(bar_full + (u0 % NST) * 8, (u0 / NST) & 1);
                __syncwarp();
                if (lane == 0) mbar_arrive(bar_empty + (u0 % NST) * 8);
                break;
            }
            const int bh = (item & (NITEM_K - 1)) / CHUNKS;
            if (item < NITEM_K) {
                unsigned int* gs = g_s + (size_t)item * ITEM_KEYS;
                float qr[24];
                {
                    const unsigned long long* qp = g_q + ((bh >> 5) * QN + (bh & 31) * DH) / 2 + sub * 4;
                    long long t0 = 0;
                    for (;;) {
                        bool ok = true;
#pragma unroll
                        for (int j = 0; j < 6; ++j) {
                            const uint4 v = ll_ld2(qp + (j >> 1) * 32 + (j & 1) * 2);
                            qr[j * 4 + 0] = bf_lo(v.x); qr[j * 4 + 1] = bf_hi(v.x);
                            qr[j * 4 + 2] = bf_lo(v.z); qr[j * 4 + 3] = bf_hi(v.z);
                            ok = ok && v.y == ep && v.w == ep;
                        }
                        if (ok) break;
                        if (t0 == 0) t0 = clock64();
                        else if (clock64() - t0 > WAIT_LIMIT_CYCLES) __trap();
                    }
                }
                float m_run = -INFINITY, l_run = 0.f;
#pragma unroll 1
                for (int hh = 0; hh < 2 * TPI; ++hh) {
                    const int u = u0 + (hh >> 1), st = u % NST;
                    if (!(hh & 1)) stage_wait(bar_full, s_tag, u);
                    const uint4* tile = (const uint4*)(smem + SM_RING + st * STAGE_BYTES) + (hh & 1) * (32 * 24);
                    float part[8];
#pragma unroll
                    for (int it = 0; it < 8; ++it) {
                        const uint4* row = tile + (it * 4 + grp) * 24 + sub;
                        const uint4 a = row[0], b = row[8], c = row[16];
                        part[it] = dot8(a, qr) + dot8(b, qr + 8) + dot8(c, qr + 16);
                    }
                    if (hh & 1) {
                        __syncwarp();
                        if (lane == 0) mbar_arrive(bar_empty + st * 8);
                    }
#pragma unroll
                    for (int j = 0; j < 4; ++j) {
                        const float send = (sub & 4) ? part[j] : part[j + 4];
                        const float keep = (sub & 4) ? part[j + 4] : part[j];
                        part[j] = keep + __shfl_xor_sync(0xffffffffu, send, 4);
                    }
#pragma unroll
                    for (int j = 0; j < 2; ++j) {
                        const float send = (sub & 2) ? part[j] : part[j + 2];
                        const float keep = (sub & 2) ? part[j + 2] : part[j];
                        part[j] = keep + __shfl_xor_sync(0xffffffffu, send, 2);
                    }
                    {
                        const float send = (sub & 1) ? part[0] : part[1];
                        const float keep = (sub & 1) ? part[1] : part[0];
                        part[0] = keep + __shfl_xor_sync(0xffffffffu, send, 1);
                    }
                    const float s = bf16r(bf16r(part[0]) * 0.07216878364870323f);
                    asm volatile("st.relaxed.gpu.global.u32 [%0], %1;" ::"l"(gs + hh * 32 + sub * 4 + grp), "r"(__float_as_uint(s) | tag16) : "memory");
                    const float m_new = fmaxf(m_run, s);
                    l_run = l_run * __expf(m_run - m_new) + __expf(s - m_new);
                    m_run = m_new;
                }
                const float m = warp_max(m_run);
                const float l = warp_sum(l_run * __expf(m_run - m));
                if (lane == 0)
                    asm volatile("st.relaxed.gpu.global.u64 [%0], %1;" ::"l"(g_stat + item),
                                 "l"(((unsigned long long)__float_as_uint(l) << 32) | (__float_as_uint(m) | tag16)) : "memory");
            } else {
                float pr[2 * TPI];
                {
                    const unsigned int* gs = g_s + (size_t)(item - NITEM_K) * ITEM_KEYS + lane;
                    uint2 st2;
                    long long t0 = 0;
                    for (;;) {
                        st2 = ll_ld1(g_stat + bh * CHUNKS + lane);
                        bool ok = (st2.x & 0xffffu) == tag16;
#pragma unroll
                        for (int hh = 0; hh < 2 * TPI; ++hh) {
                            unsigned int w;
                            asm volatile("ld.relaxed.gpu.global.u32 %0, [%1];" : "=r"(w) : "l"(gs + hh * 32) : "memory");
                            ok = ok && (w & 0xffffu) == tag16;
                            pr[hh] = bf_hi(w);
                        }
                        if (__all_sync(0xffffffffu, ok)) break;
                        if (t0 == 0) t0 = clock64();
                        else if (clock64() - t0 > WAIT_LIMIT_CYCLES) __trap();
                    }
                    const float mi = bf_hi(st2.x);
                    const float mm = warp_max(mi);
                    const float ll = warp_sum(__uint_as_float(st2.y) * __expf(mi - mm));
#pragma unroll
                    for (int hh = 0; hh < 2 * TPI; ++hh) pr[hh] = bf16r(__fdiv_rn(__expf(pr[hh] - mm), ll));
                }
                float acc[3][8];
#pragma unroll
                for (int j = 0; j < 3; ++j)
#pragma unroll
                    for (int e = 0; e < 8; ++e) acc[j][e] = 0.f;
#pragma unroll
                for (int hh = 0; hh < 2 * TPI; ++hh) {
                    const int u = u0 + (hh >> 1), st = u % NST;
                    if (!(hh & 1)) stage_wait(bar_full, s_tag, u);
                    const uint4* tile = (const uint4*)(smem + SM_RING + st * STAGE_BYTES) + (hh & 1) * (32 * 24);
#pragma unroll
                    for (int it = 0; it < 8; ++it) {
                        const uint4* row = tile + (it * 4 + grp) * 24 + sub;
                        const uint4 a = row[0], b = row[8], c = row[16];
                        const float p = __shfl_sync(0xffffffffu, pr[hh], it * 4 + grp);
                        fma8(acc[0], a, p);
                        fma8(acc[1], b, p);
                        fma8(acc[2], c, p);
                    }
                    if (hh & 1) {
                        __syncwarp();
                        if (lane == 0) mbar_arrive(bar_empty + st * 8);
                    }
                }
                float* go = acc_o + (bh >> 5) * QN + (bh & 31) * DH + sub * 8;
#pragma unroll
                for (int j = 0; j < 3; ++j) {
#pragma unroll
                    for (int e = 0; e < 8; ++e) {
                        float v = acc[j][e];
                        v += __shfl_xor_sync(0xffffffffu, v, 8);
                        v += __shfl_xor_sync(0xffffffffu, v, 16);
                        acc[j][e] = v;
                    }
                    if (grp == 0) {
                        red_add_v4(go + j * 64, acc[j][0], acc[j][1], acc[j][2], acc[j][3]);
                        red_add_v4(go + j * 64 + 4, acc[j][4], acc[j][5], acc[j][6], acc[j][7]);
                    }
                }
            }
        }
    }
    PROF(5);
    grid_arrive(&g_bar[2], tid);
    PROF(6);
    const int ks = cta >> 3, ns = cta & 7;
    if (cta < 128) stage_rows(sbase + SM_WO, P80, wo + (size_t)ks * WO_ROWS * DM + ns * 80, DM * 2, WO_ROWS, 10, tid, NCONS);
    if (cta < DM / 16) stage_rows(sbase + SM_WD, P16, w_down + cta * 16, DM * 2, FF, 2, tid, NCONS);
    grid_wait(&g_bar[2], target, tid);
    if (cta == 0 && tid == 0) { g_work = 0u; g_epoch = ep; }
    PROF(7);

    if (cta < 128) {
#pragma unroll
        for (int r = 0; r < 2; ++r) {
            const int i = tid + r * NCONS;
            if (i < NB * WO_ROWS / 4) {
                const int b = i / 96, c4 = i - b * 96;
                const float4 v = __ldcg((const float4*)(acc_o + b * QN + ks * WO_ROWS) + c4);
                __nv_bfloat162 p0 = __floats2bfloat162_rn(v.x, v.y), p1 = __floats2bfloat162_rn(v.z, v.w);
                uint2 w2;
                w2.x = *(uint32_t*)&p0; w2.y = *(uint32_t*)&p1;
                *(uint2*)(smem + SM_A + b * A_PITCH + c4 * 8) = w2;
            }
        }
        cp_async_wait_all();
        cons_sync();
        gemv_mma<3, 5>(sbase + SM_WO + warp * 48 * P80, P80, sbase + SM_A + warp * 96, A_PITCH, s_part + warp * 320, lane);
        cons_sync();
        if (tid < 80) {
            const int b = tid / 20, n4 = tid - b * 20;
            float4 s4 = make_float4(0.f, 0.f, 0.f, 0.f);
#pragma unroll
            for (int w = 0; w < 8; ++w) {
                const float4 v = *(const float4*)(s_part + (w * 4 + b) * 80 + n4 * 4);
                s4.x += v.x; s4.y += v.y; s4.z += v.z; s4.w += v.w;
            }
            red_add_v4(acc_attn + b * DM + ns * 80 + n4 * 4, s4.x, s4.y, s4.z, s4.w);
        }
    }
    PROF(8);
    grid_arrive(&g_bar[3], tid);
    if (cta >= FF / 16) return;
    grid_wait(&g_bar[3], target, tid);
    PROF(9);
    {
        float4 v[3];
#pragma unroll
        for (int r = 0; r < 3; ++r)
            if (tid + r * NCONS < NB * DM / 4) v[r] = __ldcg((const float4*)acc_attn + tid + r * NCONS);
#pragma unroll
        for (int r = 0; r < 3; ++r)
            if (tid + r * NCONS < NB * DM / 4) ((float4*)s_part)[tid + r * NCONS] = v[r];
    }
    cons_sync();
#pragma unroll
    for (int i = 0; i < 5; ++i) {
        const float2 av = *((const float2*)(s_part + lrow * DM + lcol) + i);
        float2* xp = (float2*)(s_xp + lrow * DM + lcol) + i;
        const float2 xv = *xp;
        nv[2 * i] = bf16r(xv.x + bf16r(bf_lo(m_ga[i]) * bf16r(av.x)));
        nv[2 * i + 1] = bf16r(xv.y + bf16r(bf_hi(m_ga[i]) * bf16r(av.y)));
        *xp = make_float2(nv[2 * i], nv[2 * i + 1]);
    }
    ln_norm(nv, s_red, tid);
    modulate(nv, m_sb, m_cb, h_dst);
    cons_sync();
    gemv_mma<5, 2>(sbase + SM_W32 + warp * 80 * P32, P32, sbase + SM_A + warp * 160, A_PITCH, s_part + warp * 320, lane);
    cons_sync();
    if (tid < 32) {
        const int b = tid >> 3, n = (tid & 7) * 2;
        const float g0 = bf16r(tall_sum(s_part, b, n)), g1 = bf16r(tall_sum(s_part, b, n + 1));
        const float u0 = bf16r(tall_sum(s_part, b, 16 + n)), u1 = bf16r(tall_sum(s_part, b, 17 + n));
        ll_store(g_act + (b * FF + cta * 16 + n) / 2, bf16r(gelu_tanh(g0)) * u0, bf16r(gelu_tanh(g1)) * u1, ep);
    }
    PROF(10);
    if (cta >= DM / 16) return;
    {
        long long t0 = 0;
        for (;;) {
            bool ok = true;
#pragma unroll
            for (int r = 0; r < 6; ++r) {
                const int i = tid + r * NCONS, b = i / 384, c4 = i - b * 384;
                const uint4 v = ll_ld2(g_act + 2 * i);
                *(uint2*)(smem + SM_ACT + b * ACT_PITCH + c4 * 8) = make_uint2(v.x, v.z);
                ok = ok && v.y == ep && v.w == ep;
            }
            if (ok) break;
            if (t0 == 0) t0 = clock64();
            else if (clock64() - t0 > WAIT_LIMIT_CYCLES) __trap();
        }
        cons_sync();
        PROF(11);
        gemv_mma<12, 1>(sbase + SM_WD + warp * 192 * P16, P16, sbase + SM_ACT + warp * 384, ACT_PITCH, s_part + warp * 320, lane);
        cons_sync();
        if (tid < 32) {
            const int b = tid >> 3, n = (tid & 7) * 2, col = cta * 16 + n;
            const float f0 = bf16r(tall_sum(s_part, b, n)), f1 = bf16r(tall_sum(s_part, b, n + 1));
            __nv_bfloat162 p = __floats2bfloat162_rn(s_xp[b * DM + col] + bf16r(bf_lo(m_gb[0]) * f0),
                                                     s_xp[b * DM + col + 1] + bf16r(bf_hi(m_gb[0]) * f1));
            *(__nv_bfloat162*)(out + b * DM + col) = p;
        }
    }
    PROF(12);
}

}

extern "C" void kernel_launch(void* const* d_in, const int* in_sizes, int n_in, void* d_out, int out_size) {
    (void)in_sizes; (void)n_in; (void)out_size;
    const __nv_bfloat16* A_x = (const __nv_bfloat16*)d_in[0];
    const __nv_bfloat16* A_k = (const __nv_bfloat16*)d_in[1];
    const __nv_bfloat16* A_v = (const __nv_bfloat16*)d_in[2];
    const __nv_bfloat16* A_wq = (const __nv_bfloat16*)d_in[3];
    const __nv_bfloat16* A_wo = (const __nv_bfloat16*)d_in[4];
    const __nv_bfloat16* B_wg = (const __nv_bfloat16*)d_in[6];
    const __nv_bfloat16* B_wu = (const __nv_bfloat16*)d_in[7];
    const __nv_bfloat16* B_wd = (const __nv_bfloat16*)d_in[8];
    const __nv_bfloat16* c = (const __nv_bfloat16*)d_in[9];
    const __nv_bfloat16* w_mod = (const __nv_bfloat16*)d_in[10];
    static int grid = 0;
    if (grid == 0) {
        cudaFuncSetAttribute(decode_block_kernel, cudaFuncAttributeMaxDynamicSharedMemorySize, SM_TOTAL);
        int dev = 0, sms = 0;
        cudaGetDevice(&dev);
        cudaDeviceGetAttribute(&sms, cudaDevAttrMultiProcessorCount, dev);
        grid = sms < 132 ? sms : 132;
    }
    decode_block_kernel<<<grid, NTHREADS, SM_TOTAL>>>(A_x, A_k, A_v, A_wq, A_wo, B_wg, B_wu, B_wd, c, w_mod,
                                                      (__nv_bfloat16*)d_out);
}
```

```cpp
#include <cuda_runtime.h>
#include <cuda_bf16.h>
#include <stdint.h>

namespace {

constexpr int NB = 4;
constexpr int DM = 640;
constexpr int NH = 32;
constexpr int SK = 4096;
constexpr int DH = 192;
constexpr int FF = 1536;
constexpr int MODN = 6 * DM;
constexpr int QN = NH * DH;
constexpr int NBH = NB * NH;

constexpr int NCONS = 256;
constexpr int NTHREADS = NCONS + 32;
constexpr int TILE_KEYS = 64;
constexpr int TILE_BYTES = TILE_KEYS * DH * 2;
constexpr int STAGE_BYTES = TILE_BYTES;
constexpr int NST = 6;
constexpr int PRE = 3;
constexpr int TPI = 2;
constexpr int ITEM_KEYS = TPI * TILE_KEYS;
constexpr int CHUNKS = SK / ITEM_KEYS;
constexpr int NITEM_K = NBH * CHUNKS;
constexpr int NITEM = 2 * NITEM_K;

constexpr int A_PITCH = 1296;
constexpr int ACT_PITCH = FF * 2 + 16;
constexpr int P16 = 48;
constexpr int P32 = 80;
constexpr int P48 = 112;
constexpr int P80 = 176;
constexpr int WO_ROWS = 384;

constexpr int SM_RING = 0;
constexpr int SM_WQ = PRE * STAGE_BYTES;
constexpr int SM_WO = 0;
constexpr int SM_WD = SM_WO + WO_ROWS * P80;
constexpr int SM_W32 = NST * STAGE_BYTES;
constexpr int SM_ACT = SM_W32;
constexpr int SM_A = SM_W32 + DM * P32;
constexpr int SM_PART = SM_A + NB * A_PITCH;
constexpr int SM_XP = SM_PART + 8 * 4 * 80 * 4;
constexpr int SM_RED = SM_XP + NB * DM * 4;
constexpr int SM_ITEM = SM_RED + 16 * 4;
constexpr int SM_TAG = SM_ITEM + 16 * 4;
constexpr int SM_BAR = SM_TAG + 16 * 4;
constexpr int SM_TOTAL = SM_BAR + (2 * NST + 1) * 8;
static_assert(SM_WQ + DM * P48 <= NST * STAGE_BYTES, "prologue overlay");
static_assert(SM_WD + FF * P16 <= NST * STAGE_BYTES, "tail overlay");
static_assert(SM_TOTAL <= 232448, "smem");
#define PSTART 0

__device__ __align__(128) unsigned long long g_mod[NB * MODN / 2];
__device__ __align__(128) unsigned long long g_q[NB * QN / 2];
__device__ __align__(128) unsigned long long g_act[NB * FF / 2];
__device__ __align__(128) unsigned int g_s[NBH * SK];
__device__ __align__(128) unsigned long long g_stat[NBH * CHUNKS];
__device__ __align__(128) float g_o[2][NB * QN];
__device__ __align__(128) float g_attn[2][NB * DM];
__device__ __align__(128) unsigned int g_bar[8];
__device__ unsigned int g_work;
__device__ unsigned int g_epoch;

#define PROF(k) do { } while (0)
#define PROFP(k) do { } while (0)

__device__ __forceinline__ float bf16r(float x) { return __bfloat162float(__float2bfloat16_rn(x)); }
__device__ __forceinline__ float bf_lo(uint32_t u) { return __uint_as_float(u << 16); }
__device__ __forceinline__ float bf_hi(uint32_t u) { return __uint_as_float(u & 0xffff0000u); }

__device__ __forceinline__ uint32_t smem_u32(const void* p) { return (uint32_t)__cvta_generic_to_shared(p); }
__device__ __forceinline__ void mbar_init(uint32_t bar, uint32_t count) {
    asm volatile("mbarrier.init.shared::cta.b64 [%0], %1;" ::"r"(bar), "r"(count) : "memory");
}
__device__ __forceinline__ void mbar_expect_tx(uint32_t bar, uint32_t bytes) {
    asm volatile("mbarrier.arrive.expect_tx.shared::cta.b64 _, [%0], %1;" ::"r"(bar), "r"(bytes) : "memory");
}
__device__ __forceinline__ void mbar_arrive(uint32_t bar) {
    asm volatile("mbarrier.arrive.shared::cta.b64 _, [%0];" ::"r"(bar) : "memory");
}
constexpr long long WAIT_LIMIT_CYCLES = 200000000LL;
__device__ __forceinline__ uint32_t mbar_try(uint32_t bar, uint32_t parity) {
    uint32_t done;
    asm volatile(
        "{\n\t.reg .pred p;\n\t"
        "mbarrier.try_wait.parity.shared::cta.b64 p, [%1], %2;\n\t"
        "selp.u32 %0, 1, 0, p;\n\t}"
        : "=r"(done) : "r"(bar), "r"(parity) : "memory");
    return done;
}
__device__ __noinline__ void mbar_wait_slow(uint32_t bar, uint32_t parity) {
    const long long t0 = clock64();
    while (!mbar_try(bar, parity)) {
        if (clock64() - t0 > WAIT_LIMIT_CYCLES) __trap();
    }
}
__device__ __forceinline__ void mbar_wait(uint32_t bar, uint32_t parity) {
    if (!mbar_try(bar, parity)) mbar_wait_slow(bar, parity);
}
__device__ __noinline__ void tag_wait_slow(volatile int* tag, int u) {
    const long long t0 = clock64();
    while (*tag != u) {
        __nanosleep(32);
        if (clock64() - t0 > WAIT_LIMIT_CYCLES) __trap();
    }
}
__device__ __forceinline__ void stage_wait(uint32_t bar_full, volatile int* s_tag, int u) {
    const int st = u % NST;
    if (s_tag[st] != u) tag_wait_slow(s_tag + st, u);
    mbar_wait(bar_full + st * 8, (u / NST) & 1);
}
__device__ __forceinline__ void bulk_g2s(uint32_t dst, const void* src, uint32_t bytes, uint32_t bar, uint64_t pol) {
    asm volatile(
        "cp.async.bulk.shared::cluster.global.mbarrier::complete_tx::bytes.L2::cache_hint [%0], [%1], %2, [%3], %4;"
        ::"r"(dst), "l"(src), "r"(bytes), "r"(bar), "l"(pol) : "memory");
}
__device__ __forceinline__ void cp_async16(uint32_t dst, const void* src) {
    asm volatile("cp.async.cg.shared.global [%0], [%1], 16;" ::"r"(dst), "l"(src) : "memory");
}
__device__ __forceinline__ void cp_async_wait_all() { asm volatile("cp.async.wait_all;" ::: "memory"); }
__device__ __forceinline__ void cp_async_commit() { asm volatile("cp.async.commit_group;" ::: "memory"); }
__device__ __forceinline__ void cp_async_wait1() { asm volatile("cp.async.wait_group 1;" ::: "memory"); }
__device__ __forceinline__ void red_release_add(unsigned int* p, unsigned int v) {
    asm volatile("red.release.gpu.global.add.u32 [%0], %1;" ::"l"(p), "r"(v) : "memory");
}
__device__ __forceinline__ void cons_sync() { asm volatile("bar.sync 1, 256;" ::: "memory"); }

__device__ __forceinline__ void red_add_v4(float* p, float a, float b, float c, float d) {
    asm volatile("red.global.add.v4.f32 [%0], {%1, %2, %3, %4};" ::"l"(p), "f"(a), "f"(b), "f"(c), "f"(d) : "memory");
}
__device__ __forceinline__ unsigned int ld_acquire(const unsigned int* p) {
    unsigned int v;
    asm volatile("ld.acquire.gpu.global.u32 %0, [%1];" : "=r"(v) : "l"(p) : "memory");
    return v;
}
__device__ __forceinline__ void ll_store(unsigned long long* p, float a, float b, unsigned int ep) {
    __nv_bfloat162 v = __floats2bfloat162_rn(a, b);
    const unsigned long long w = ((unsigned long long)ep << 32) | *(uint32_t*)&v;
    asm volatile("st.relaxed.gpu.global.u64 [%0], %1;" ::"l"(p), "l"(w) : "memory");
}
__device__ __forceinline__ uint2 ll_ld1(const unsigned long long* p) {
    unsigned long long w;
    asm volatile("ld.relaxed.gpu.global.u64 %0, [%1];" : "=l"(w) : "l"(p) : "memory");
    return make_uint2((uint32_t)w, (uint32_t)(w >> 32));
}
__device__ __forceinline__ uint4 ll_ld2(const unsigned long long* p) {
    unsigned long long a, b;
    asm volatile("ld.relaxed.gpu.global.v2.u64 {%0, %1}, [%2];" : "=l"(a), "=l"(b) : "l"(p) : "memory");
    return make_uint4((uint32_t)a, (uint32_t)(a >> 32), (uint32_t)b, (uint32_t)(b >> 32));
}
template <int N>
__device__ __forceinline__ void ll_get(const unsigned long long* p, uint32_t (&d)[N], unsigned int ep) {
    long long t0 = 0;
    for (;;) {
        bool ok = true;
#pragma unroll
        for (int i = 0; i < N; ++i) {
            const uint2 v = ll_ld1(p + i);
            d[i] = v.x;
            ok = ok && (v.y == ep);
        }
        if (ok) break;
        if (t0 == 0) t0 = clock64();
        else if (clock64() - t0 > WAIT_LIMIT_CYCLES) __trap();
    }
}

__device__ __forceinline__ void grid_arrive(unsigned int* ctr, int tid) {
    cons_sync();
    if (tid == 0) red_release_add(ctr, 1u);
}
__device__ __noinline__ void grid_wait(const unsigned int* ctr, unsigned int target, int tid) {
    if (tid == 0) {
        const long long t0 = clock64();
        while ((int)(ld_acquire(ctr) - target) < 0) {
            if (clock64() - t0 > WAIT_LIMIT_CYCLES) __trap();
        }
    }
    cons_sync();
}

__device__ __forceinline__ float warp_sum(float v) {
#pragma unroll
    for (int o = 16; o > 0; o >>= 1) v += __shfl_xor_sync(0xffffffffu, v, o);
    return v;
}
__device__ __forceinline__ float warp_max(float v) {
#pragma unroll
    for (int o = 16; o > 0; o >>= 1) v = fmaxf(v, __shfl_xor_sync(0xffffffffu, v, o));
    return v;
}

__device__ __forceinline__ void fma8(float (&acc)[8], const uint4& w, float s) {
    acc[0] = fmaf(s, bf_lo(w.x), acc[0]);
    acc[1] = fmaf(s, bf_hi(w.x), acc[1]);
    acc[2] = fmaf(s, bf_lo(w.y), acc[2]);
    acc[3] = fmaf(s, bf_hi(w.y), acc[3]);
    acc[4] = fmaf(s, bf_lo(w.z), acc[4]);
    acc[5] = fmaf(s, bf_hi(w.z), acc[5]);
    acc[6] = fmaf(s, bf_lo(w.w), acc[6]);
    acc[7] = fmaf(s, bf_hi(w.w), acc[7]);
}
__device__ __forceinline__ float dot8(const uint4& w, const float* q) {
    float s = q[0] * bf_lo(w.x);
    s = fmaf(q[1], bf_hi(w.x), s);
    s = fmaf(q[2], bf_lo(w.y), s);
    s = fmaf(q[3], bf_hi(w.y), s);
    s = fmaf(q[4], bf_lo(w.z), s);
    s = fmaf(q[5], bf_hi(w.z), s);
    s = fmaf(q[6], bf_lo(w.w), s);
    s = fmaf(q[7], bf_hi(w.w), s);
    return s;
}

__device__ __noinline__ void stage_rows(uint32_t dst, int dst_pitch, const void* src, int src_stride, int rows,
                                        int cpr, int tid, int nthr) {
    const int n = rows * cpr;
#pragma unroll 1
    for (int i = tid; i < n; i += nthr) {
        const int r = i / cpr, c = i - r * cpr;
        cp_async16(dst + r * dst_pitch + c * 16, (const unsigned char*)src + (size_t)r * src_stride + c * 16);
    }
}

template <int KS, int NT>
__device__ __noinline__ void gemv_mma(uint32_t w, int w_pitch, uint32_t a, int a_pitch, float* part, int lane) {
    float c[NT][4];
#pragma unroll
    for (int nt = 0; nt < NT; ++nt) { c[nt][0] = 0.f; c[nt][1] = 0.f; c[nt][2] = 0.f; c[nt][3] = 0.f; }
    const uint32_t ap = a + (lane >> 2) * a_pitch + (lane & 3) * 4;
    const uint32_t wp = w + ((lane & 7) + ((lane >> 4) << 3)) * w_pitch + ((lane >> 3) & 1) * 16;
#pragma unroll
    for (int ks = 0; ks < KS; ++ks) {
        uint32_t b0 = 0, b1 = 0;
        if (lane < 16) {
            asm("ld.shared.u32 %0, [%1];" : "=r"(b0) : "r"(ap + ks * 32));
            asm("ld.shared.u32 %0, [%1];" : "=r"(b1) : "r"(ap + ks * 32 + 16));
        }
#pragma unroll
        for (int nt = 0; nt < NT; ++nt) {
            uint32_t a0, a1, a2, a3;
            asm("ldmatrix.sync.aligned.m8n8.x4.trans.shared.b16 {%0, %1, %2, %3}, [%4];"
                         : "=r"(a0), "=r"(a1), "=r"(a2), "=r"(a3) : "r"(wp + ks * 16 * w_pitch + nt * 32));
            asm("mma.sync.aligned.m16n8k16.row.col.f32.bf16.bf16.f32 {%0, %1, %2, %3}, {%4, %5, %6, %7}, "
                "{%8, %9}, {%0, %1, %2, %3};"
                : "+f"(c[nt][0]), "+f"(c[nt][1]), "+f"(c[nt][2]), "+f"(c[nt][3])
                : "r"(a0), "r"(a1), "r"(a2), "r"(a3), "r"(b0), "r"(b1));
        }
    }
    if ((lane & 3) < 2) {
        float* pp = part + (lane & 3) * 160 + (lane >> 2);
#pragma unroll
        for (int nt = 0; nt < NT; ++nt) {
            pp[nt * 16] = c[nt][0];
            pp[nt * 16 + 80] = c[nt][1];
            pp[nt * 16 + 8] = c[nt][2];
            pp[nt * 16 + 88] = c[nt][3];
        }
    }
}

__device__ __forceinline__ float tall_sum(const float* part, int b, int n) {
    float s = 0.f;
#pragma unroll
    for (int w = 0; w < 8; ++w) s += part[(w * 4 + b) * 80 + n];
    return s;
}

__device__ __forceinline__ void ln_norm(float (&v)[10], float* s_red, int tid) {
    const int warp = tid >> 5;
    const float pv = __shfl_sync(0xffffffffu, v[0], 0);
    float s = 0.f, q = 0.f;
#pragma unroll
    for (int i = 0; i < 10; ++i) { const float d = v[i] - pv; s += d; q = fmaf(d, d, q); }
#pragma unroll
    for (int o = 16; o > 0; o >>= 1) {
        s += __shfl_xor_sync(0xffffffffu, s, o);
        q += __shfl_xor_sync(0xffffffffu, q, o);
    }
    const float md = s * (2.0f / DM);
    if ((tid & 31) == 0) *(float2*)(s_red + 2 * warp) = make_float2(pv + md, fmaxf(q - s * md, 0.f));
    cons_sync();
    const float4 r = *(const float4*)(s_red + 4 * (warp >> 1));
    const float dm = r.x - r.z;
    const float var = (r.y + r.w + dm * dm * (DM / 4)) * (1.0f / DM);
    const float mean = bf16r(0.5f * (r.x + r.z));
    const float inv = __fdiv_rn(1.0f, bf16r(sqrtf(bf16r(bf16r(var) + 1e-5f))));
#pragma unroll
    for (int i = 0; i < 10; ++i) v[i] = bf16r(bf16r(v[i] - mean) * inv);
}
__device__ __forceinline__ void modulate(const float (&n)[10], const uint32_t (&sh)[5], const uint32_t (&sc)[5], uint32_t* dst) {
#pragma unroll
    for (int i = 0; i < 5; ++i) {
        const float h0 = bf16r(n[2 * i] * bf16r(1.0f + bf_lo(sc[i]))) + bf_lo(sh[i]);
        const float h1 = bf16r(n[2 * i + 1] * bf16r(1.0f + bf_hi(sc[i]))) + bf_hi(sh[i]);
        __nv_bfloat162 p = __floats2bfloat162_rn(h0, h1);
        dst[i] = *(uint32_t*)&p;
    }
}

__device__ __forceinline__ float gelu_tanh(float x) {
    const float kBeta = 0.7978845608028654f;
    const float inner = kBeta * (x + 0.044715f * x * x * x);
    return 0.5f * x * (1.0f + tanhf(inner));
}

__global__ void __launch_bounds__(NTHREADS, 1)
decode_block_kernel(const __nv_bfloat16* __restrict__ x_in, const __nv_bfloat16* __restrict__ k_cache,
                    const __nv_bfloat16* __restrict__ v_cache, const __nv_bfloat16* __restrict__ wq,
                    const __nv_bfloat16* __restrict__ wo, const __nv_bfloat16* __restrict__ w_gate,
                    const __nv_bfloat16* __restrict__ w_up, const __nv_bfloat16* __restrict__ w_down,
                    const __nv_bfloat16* __restrict__ cvec, const __nv_bfloat16* __restrict__ w_mod,
                    __nv_bfloat16* __restrict__ out) {
    extern __shared__ __align__(128) unsigned char smem[];
    const int tid = threadIdx.x;
    const int cta = blockIdx.x;

    const uint32_t sbase = smem_u32(smem);
    const uint32_t bar_full = sbase + SM_BAR;
    const uint32_t bar_empty = bar_full + NST * 8;
    volatile int* s_item = (volatile int*)(smem + SM_ITEM);
    volatile int* s_tag = (volatile int*)(smem + SM_TAG);

    const uint32_t bar_go = bar_empty + NST * 8;
    if (tid < NST) s_tag[tid] = -1;
    if (tid == 0) {
#pragma unroll 1
        for (int s = 0; s < 2 * NST + 1; ++s) mbar_init(bar_full + s * 8, 1);
        asm volatile("fence.mbarrier_init.release.cluster;" ::: "memory");
        asm volatile("fence.proxy.async.shared::cta;" ::: "memory");
#pragma unroll 1
        for (int s = 0; s < PRE; ++s) mbar_arrive(bar_empty + s * 8);
    }
    __syncthreads();

    if (tid >= NCONS) {
        if (tid == NCONS) {
            int u = 0;
            const int G = (int)gridDim.x;
            uint64_t pol;
            asm volatile("createpolicy.fractional.L2::evict_first.b64 %0, 1.0;" : "=l"(pol));
            auto produce = [&](const int item) {
                const int it = item & (NITEM_K - 1);
                const bool is_v = item >= NITEM_K;
                const unsigned char* src = (const unsigned char*)(is_v ? v_cache : k_cache) + (size_t)it * (ITEM_KEYS * DH * 2);
#pragma unroll 1
                for (int t = 0; t < TPI; ++t, ++u) {
                    const int st = u % NST;
                    const uint32_t fb = bar_full + st * 8;
                    mbar_wait(bar_empty + st * 8, (u / NST) & 1);
                    s_item[st] = item;
                    s_tag[st] = u;
                    mbar_expect_tx(fb, TILE_BYTES);
                    bulk_g2s(sbase + SM_RING + st * STAGE_BYTES, src + t * TILE_BYTES, TILE_BYTES, fb, pol);
                }
            };
            if (PSTART != 3) mbar_wait(bar_go, 0);
            int item = cta;
#pragma unroll 1
            while (item < NITEM) {
                const int next = (int)atomicAdd(&g_work, 1u) + G;
                produce(item);
                item = next;
            }
#pragma unroll 1
            for (int j = 0; j < 8; ++j, u += TPI) {
                const int st = u % NST;
                mbar_wait(bar_empty + st * 8, (u / NST) & 1);
                s_item[st] = -1;
                s_tag[st] = u;
                mbar_arrive(bar_full + st * 8);
            }
            PROFP(13);
        }
        return;
    }

    const int lane = tid & 31, warp = tid >> 5;
    float* s_part = (float*)(smem + SM_PART);
    float* s_xp = (float*)(smem + SM_XP);
    float* s_red = (float*)(smem + SM_RED);
    const int lrow = tid >> 6, lcol = (tid & 63) * 10;
    uint32_t* h_dst = (uint32_t*)(smem + SM_A + lrow * A_PITCH + lcol * 2);

    PROF(0);
    const unsigned int ep = ld_acquire(&g_epoch) + 1u;
    const unsigned int target = ep * gridDim.x, tag16 = ep & 0xffffu;
    const unsigned long long* mod_row = g_mod + (lrow * MODN + lcol) / 2;
    float nv[10];
    {
        const int i1 = tid + NCONS;
        const uint4 c0 = __ldg((const uint4*)cvec + tid);
        uint4 c1 = c0;
        if (i1 < 320) c1 = __ldg((const uint4*)cvec + i1);
        uint32_t xw[5];
#pragma unroll
        for (int i = 0; i < 5; ++i) xw[i] = __ldg((const uint32_t*)(x_in + lrow * DM + lcol) + i);
        if (cta < MODN / 32) stage_rows(sbase + SM_W32, P32, w_mod + cta * 32, MODN * 2, DM, 4, tid, NCONS);
        cp_async_commit();
        if (cta < QN / 48) stage_rows(sbase + SM_WQ, P48, wq + cta * 48, QN * 2, DM, 6, tid, NCONS);
        cp_async_commit();
        if (PSTART == 1 && tid == 0) mbar_arrive(bar_go);
#pragma unroll 1
        for (int r = 0; r < 2; ++r) {
            const int i = r ? i1 : tid;
            if (i < 320) {
                const uint4 cc = r ? c1 : c0;
                const uint32_t cw[4] = {cc.x, cc.y, cc.z, cc.w};
                uint32_t ow[4];
#pragma unroll
                for (int k = 0; k < 4; ++k) {
                    const float a = bf_lo(cw[k]), b = bf_hi(cw[k]);
                    __nv_bfloat162 p = __floats2bfloat162_rn(__fdiv_rn(a, 1.0f + __expf(-a)), __fdiv_rn(b, 1.0f + __expf(-b)));
                    ow[k] = *(uint32_t*)&p;
                }
                const int b = i / 80, c8 = i - b * 80;
                *(uint4*)(smem + SM_A + b * A_PITCH + c8 * 16) = make_uint4(ow[0], ow[1], ow[2], ow[3]);
            }
        }
#pragma unroll
        for (int i = 0; i < 5; ++i) {
            nv[2 * i] = bf_lo(xw[i]);
            nv[2 * i + 1] = bf_hi(xw[i]);
            *(float2*)(s_xp + lrow * DM + lcol + 2 * i) = make_float2(nv[2 * i], nv[2 * i + 1]);
        }
    }
    float* acc_o = g_o[ep & 1];
    float* acc_attn = g_attn[ep & 1];
    if (cta == gridDim.x - 1) {
#pragma unroll 1
        for (int i = tid; i < NB * QN / 4; i += NCONS) ((float4*)g_o[~ep & 1])[i] = make_float4(0.f, 0.f, 0.f, 0.f);
#pragma unroll 1
        for (int i = tid; i < NB * DM; i += NCONS) g_attn[~ep & 1][i] = 0.f;
    }
    ln_norm(nv, s_red, tid);
    cp_async_wait1();
    cons_sync();
    if (PSTART == 0 && tid == 0) mbar_arrive(bar_go);
    if (cta < MODN / 32) {
        gemv_mma<5, 2>(sbase + SM_W32 + warp * 80 * P32, P32, sbase + SM_A + warp * 160, A_PITCH, s_part + warp * 320, lane);
        cons_sync();
        if (tid < 64) {
            const int b = tid >> 4, n = (tid & 15) * 2;
            ll_store(g_mod + (b * MODN + cta * 32 + n) / 2, tall_sum(s_part, b, n), tall_sum(s_part, b, n + 1), ep);
        }
    }
    PROF(1);

    if (cta < QN / 48) {
        cons_sync();
        {
            long long t0 = 0;
            for (;;) {
                bool ok = true;
#pragma unroll
                for (int r = 0; r < 5; ++r) {
                    const int i = tid + r * NCONS, b = i / 320, c4 = i - b * 320;
                    const uint4 v = ll_ld2(g_mod + b * (MODN / 2) + 2 * c4);
                    *(uint2*)(s_part + b * DM + 2 * c4) = make_uint2(v.x, v.z);
                    ok = ok && v.y == ep && v.w == ep;
                }
                if (ok) break;
                if (t0 == 0) t0 = clock64();
                else if (clock64() - t0 > WAIT_LIMIT_CYCLES) __trap();
            }
        }
        cons_sync();
        PROF(2);
        uint32_t sh[5], sc[5];
#pragma unroll
        for (int i = 0; i < 5; ++i) {
            sh[i] = ((const uint32_t*)s_part)[lrow * DM + lcol / 2 + i];
            sc[i] = ((const uint32_t*)s_part)[lrow * DM + DM / 2 + lcol / 2 + i];
        }
        modulate(nv, sh, sc, h_dst);
        cp_async_wait_all();
        cons_sync();
        if (PSTART == 2 && tid == 0) mbar_arrive(bar_go);
        gemv_mma<5, 3>(sbase + SM_WQ + warp * 80 * P48, P48, sbase + SM_A + warp * 160, A_PITCH, s_part + warp * 320, lane);
        cons_sync();
        if (tid < 96) {
            const int b = tid / 24, n = (tid - b * 24) * 2;
            ll_store(g_q + (b * QN + cta * 48 + n) / 2, tall_sum(s_part, b, n), tall_sum(s_part, b, n + 1), ep);
        }
    } else if (PSTART == 2 && tid == 0) {
        mbar_arrive(bar_go);
    }
    PROF(3);
    if (tid == 0) {
#pragma unroll 1
        for (int s = PRE; s < NST; ++s) mbar_arrive(bar_empty + s * 8);
    }
    uint32_t m_ga[5], m_sb[5], m_cb[5], m_gb[1] = {0u};
    if (cta < FF / 16) {
        if (warp == 7) {
            stage_rows(sbase + SM_W32, P32, w_gate + cta * 16, FF * 2, DM, 2, lane, 32);
            stage_rows(sbase + SM_W32 + 32, P32, w_up + cta * 16, FF * 2, DM, 2, lane, 32);
        }
    }
    PROF(4);

    {
        const int sub = lane & 7, grp = lane >> 3;
        for (int u0 = warp * TPI;; u0 += 8 * TPI) {
            if (u0 >= 8 * TPI && u0 < 16 * TPI && cta < FF / 16) {
                ll_get(mod_row + DM, m_ga, ep);
                ll_get(mod_row + 3 * DM / 2, m_sb, ep);
                ll_get(mod_row + 2 * DM, m_cb, ep);
                if (tid < 32 && cta < DM / 16) ll_get(g_mod + ((tid >> 3) * MODN + 5 * DM + cta * 16) / 2 + (tid & 7), m_gb, ep);
            }
            if (u0 == (8 + 6) * TPI) {
                if (cta < QN / 48) {
#pragma unroll 1
                    for (int i = lane; i < 48 * DM * 2 / 128; i += 32) {
                        unsigned int v;
                        asm volatile("ld.global.L2::128B.u32 %0, [%1];" : "=r"(v) : "l"((const unsigned char*)(wo + (size_t)cta * 48 * DM) + i * 128));
                    }
                }
                if (cta < FF / 16) {
#pragma unroll 1
                    for (int i = lane; i < 16 * DM * 2 / 128; i += 32) {
                        unsigned int v;
                        asm volatile("ld.global.L2::128B.u32 %0, [%1];" : "=r"(v) : "l"((const unsigned char*)(w_down + (size_t)cta * 16 * DM) + i * 128));
                    }
                }
            }
            if (s_tag[u0 % NST] != u0) tag_wait_slow(s_tag + u0 % NST, u0);
            const int item = s_item[u0 % NST];
            if (item < 0) {
                mbar_wait(bar_full + (u0 % NST) * 8, (u0 / NST) & 1);
                __syncwarp();
                if (lane == 0) mbar_arrive(bar_empty + (u0 % NST) * 8);
                break;
            }
            const int bh = (item & (NITEM_K - 1)) / CHUNKS;
            if (item < NITEM_K) {
                unsigned int* gs = g_s + (size_t)item * ITEM_KEYS;
                float qr[24];
                {
                    const unsigned long long* qp = g_q + ((bh >> 5) * QN + (bh & 31) * DH) / 2 + sub * 4;
                    long long t0 = 0;
                    for (;;) {
                        bool ok = true;
#pragma unroll
                        for (int j = 0; j < 6; ++j) {
                            const uint4 v = ll_ld2(qp + (j >> 1) * 32 + (j & 1) * 2);
                            qr[j * 4 + 0] = bf_lo(v.x); qr[j * 4 + 1] = bf_hi(v.x);
                            qr[j * 4 + 2] = bf_lo(v.z); qr[j * 4 + 3] = bf_hi(v.z);
                            ok = ok && v.y == ep && v.w == ep;
                        }
                        if (ok) break;
                        if (t0 == 0) t0 = clock64();
                        else if (clock64() - t0 > WAIT_LIMIT_CYCLES) __trap();
                    }
                }
                float m_run = -INFINITY, l_run = 0.f;
#pragma unroll 1
                for (int hh = 0; hh < 2 * TPI; ++hh) {
                    const int u = u0 + (hh >> 1), st = u % NST;
                    if (!(hh & 1)) stage_wait(bar_full, s_tag, u);
                    const uint4* tile = (const uint4*)(smem + SM_RING + st * STAGE_BYTES) + (hh & 1) * (32 * 24);
                    float part[8];
#pragma unroll
                    for (int it = 0; it < 8; ++it) {
                        const uint4* row = tile + (it * 4 + grp) * 24 + sub;
                        const uint4 a = row[0], b = row[8], c = row[16];
                        part[it] = dot8(a, qr) + dot8(b, qr + 8) + dot8(c, qr + 16);
                    }
                    if (hh & 1) {
                        __syncwarp();
                        if (lane == 0) mbar_arrive(bar_empty + st * 8);
                    }
#pragma unroll
                    for (int j = 0; j < 4; ++j) {
                        const float send = (sub & 4) ? part[j] : part[j + 4];
                        const float keep = (sub & 4) ? part[j + 4] : part[j];
                        part[j] = keep + __shfl_xor_sync(0xffffffffu, send, 4);
                    }
#pragma unroll
                    for (int j = 0; j < 2; ++j) {
                        const float send = (sub & 2) ? part[j] : part[j + 2];
                        const float keep = (sub & 2) ? part[j + 2] : part[j];
                        part[j] = keep + __shfl_xor_sync(0xffffffffu, send, 2);
                    }
                    {
                        const float send = (sub & 1) ? part[0] : part[1];
                        const float keep = (sub & 1) ? part[1] : part[0];
                        part[0] = keep + __shfl_xor_sync(0xffffffffu, send, 1);
                    }
                    const float s = bf16r(bf16r(part[0]) * 0.07216878364870323f);
                    asm volatile("st.relaxed.gpu.global.u32 [%0], %1;" ::"l"(gs + hh * 32 + sub * 4 + grp), "r"(__float_as_uint(s) | tag16) : "memory");
                    const float m_new = fmaxf(m_run, s);
                    l_run = l_run * __expf(m_run - m_new) + __expf(s - m_new);
                    m_run = m_new;
                }
                const float m = warp_max(m_run);
                const float l = warp_sum(l_run * __expf(m_run - m));
                if (lane == 0)
                    asm volatile("st.relaxed.gpu.global.u64 [%0], %1;" ::"l"(g_stat + item),
                                 "l"(((unsigned long long)__float_as_uint(l) << 32) | (__float_as_uint(m) | tag16)) : "memory");
            } else {
                float pr[2 * TPI];
                {
                    const unsigned int* gs = g_s + (size_t)(item - NITEM_K) * ITEM_KEYS + lane;
                    uint2 st2;
                    long long t0 = 0;
                    for (;;) {
                        st2 = ll_ld1(g_stat + bh * CHUNKS + lane);
                        bool ok = (st2.x & 0xffffu) == tag16;
#pragma unroll
                        for (int hh = 0; hh < 2 * TPI; ++hh) {
                            unsigned int w;
                            asm volatile("ld.relaxed.gpu.global.u32 %0, [%1];" : "=r"(w) : "l"(gs + hh * 32) : "memory");
                            ok = ok && (w & 0xffffu) == tag16;
                            pr[hh] = bf_hi(w);
                        }
                        if (__all_sync(0xffffffffu, ok)) break;
                        if (t0 == 0) t0 = clock64();
                        else if (clock64() - t0 > WAIT_LIMIT_CYCLES) __trap();
                    }
                    const float mi = bf_hi(st2.x);
                    const float mm = warp_max(mi);
                    const float ll = warp_sum(__uint_as_float(st2.y) * __expf(mi - mm));
#pragma unroll
                    for (int hh = 0; hh < 2 * TPI; ++hh) pr[hh] = bf16r(__fdiv_rn(__expf(pr[hh] - mm), ll));
                }
                float acc[3][8];
#pragma unroll
                for (int j = 0; j < 3; ++j)
#pragma unroll
                    for (int e = 0; e < 8; ++e) acc[j][e] = 0.f;
#pragma unroll
                for (int hh = 0; hh < 2 * TPI; ++hh) {
                    const int u = u0 + (hh >> 1), st = u % NST;
                    if (!(hh & 1)) stage_wait(bar_full, s_tag, u);
                    const uint4* tile = (const uint4*)(smem + SM_RING + st * STAGE_BYTES) + (hh & 1) * (32 * 24);
#pragma unroll
                    for (int it = 0; it < 8; ++it) {
                        const uint4* row = tile + (it * 4 + grp) * 24 + sub;
                        const uint4 a = row[0], b = row[8], c = row[16];
                        const float p = __shfl_sync(0xffffffffu, pr[hh], it * 4 + grp);
                        fma8(acc[0], a, p);
                        fma8(acc[1], b, p);
                        fma8(acc[2], c, p);
                    }
                    if (hh & 1) {
                        __syncwarp();
                        if (lane == 0) mbar_arrive(bar_empty + st * 8);
                    }
                }
                float* go = acc_o + (bh >> 5) * QN + (bh & 31) * DH + sub * 8;
#pragma unroll
                for (int j = 0; j < 3; ++j) {
#pragma unroll
                    for (int e = 0; e < 8; ++e) {
                        float v = acc[j][e];
                        v += __shfl_xor_sync(0xffffffffu, v, 8);
                        v += __shfl_xor_sync(0xffffffffu, v, 16);
                        acc[j][e] = v;
                    }
                    if (grp == 0) {
                        red_add_v4(go + j * 64, acc[j][0], acc[j][1], acc[j][2], acc[j][3]);
                        red_add_v4(go + j * 64 + 4, acc[j][4], acc[j][5], acc[j][6], acc[j][7]);
                    }
                }
            }
        }
    }
    PROF(5);
    grid_arrive(&g_bar[2], tid);
    PROF(6);
    const int ks = cta >> 3, ns = cta & 7;
    if (cta < 128 && tid < 240) {
        const int r0 = tid / 10, c = tid - r0 * 10;
        const unsigned char* src = (const unsigned char*)(wo + ((size_t)ks * WO_ROWS + r0) * DM + ns * 80) + c * 16;
        const uint32_t dst = sbase + SM_WO + r0 * P80 + c * 16;
#pragma unroll
        for (int i = 0; i < WO_ROWS / 24; ++i) cp_async16(dst + i * 24 * P80, src + (size_t)i * 24 * DM * 2);
    }
    grid_wait(&g_bar[2], target, tid);
    if (cta == 0 && tid == 0) { g_work = 0u; g_epoch = ep; }
    PROF(7);

    if (cta < 128) {
#pragma unroll
        for (int r = 0; r < 2; ++r) {
            const int i = tid + r * NCONS;
            if (i < NB * WO_ROWS / 4) {
                const int b = i / 96, c4 = i - b * 96;
                const float4 v = __ldcg((const float4*)(acc_o + b * QN + ks * WO_ROWS) + c4);
                __nv_bfloat162 p0 = __floats2bfloat162_rn(v.x, v.y), p1 = __floats2bfloat162_rn(v.z, v.w);
                uint2 w2;
                w2.x = *(uint32_t*)&p0; w2.y = *(uint32_t*)&p1;
                *(uint2*)(smem + SM_A + b * A_PITCH + c4 * 8) = w2;
            }
        }
        cp_async_wait_all();
        cons_sync();
        gemv_mma<3, 5>(sbase + SM_WO + warp * 48 * P80, P80, sbase + SM_A + warp * 96, A_PITCH, s_part + warp * 320, lane);
        cons_sync();
        if (tid < 80) {
            const int b = tid / 20, n4 = tid - b * 20;
            float4 s4 = make_float4(0.f, 0.f, 0.f, 0.f);
#pragma unroll
            for (int w = 0; w < 8; ++w) {
                const float4 v = *(const float4*)(s_part + (w * 4 + b) * 80 + n4 * 4);
                s4.x += v.x; s4.y += v.y; s4.z += v.z; s4.w += v.w;
            }
            red_add_v4(acc_attn + b * DM + ns * 80 + n4 * 4, s4.x, s4.y, s4.z, s4.w);
        }
    }
    PROF(8);
    grid_arrive(&g_bar[3], tid);
    if (cta >= FF / 16) return;
    if (cta < DM / 16) {
        const unsigned char* src = (const unsigned char*)(w_down + (size_t)(tid >> 1) * DM + cta * 16) + (tid & 1) * 16;
        const uint32_t dst = sbase + SM_WD + (tid >> 1) * P16 + (tid & 1) * 16;
#pragma unroll
        for (int i = 0; i < FF / 128; ++i) cp_async16(dst + i * 128 * P16, src + (size_t)i * 128 * DM * 2);
    }
    grid_wait(&g_bar[3], target, tid);
    PROF(9);
    {
        float4 v[3];
#pragma unroll
        for (int r = 0; r < 3; ++r)
            if (tid + r * NCONS < NB * DM / 4) v[r] = __ldcg((const float4*)acc_attn + tid + r * NCONS);
#pragma unroll
        for (int r = 0; r < 3; ++r)
            if (tid + r * NCONS < NB * DM / 4) ((float4*)s_part)[tid + r * NCONS] = v[r];
    }
    cons_sync();
#pragma unroll
    for (int i = 0; i < 5; ++i) {
        const float2 av = *((const float2*)(s_part + lrow * DM + lcol) + i);
        float2* xp = (float2*)(s_xp + lrow * DM + lcol) + i;
        const float2 xv = *xp;
        nv[2 * i] = bf16r(xv.x + bf16r(bf_lo(m_ga[i]) * bf16r(av.x)));
        nv[2 * i + 1] = bf16r(xv.y + bf16r(bf_hi(m_ga[i]) * bf16r(av.y)));
        *xp = make_float2(nv[2 * i], nv[2 * i + 1]);
    }
    ln_norm(nv, s_red, tid);
    modulate(nv, m_sb, m_cb, h_dst);
    cons_sync();
    gemv_mma<5, 2>(sbase + SM_W32 + warp * 80 * P32, P32, sbase + SM_A + warp * 160, A_PITCH, s_part + warp * 320, lane);
    cons_sync();
    if (tid < 32) {
        const int b = tid >> 3, n = (tid & 7) * 2;
        const float g0 = bf16r(tall_sum(s_part, b, n)), g1 = bf16r(tall_sum(s_part, b, n + 1));
        const float u0 = bf16r(tall_sum(s_part, b, 16 + n)), u1 = bf16r(tall_sum(s_part, b, 17 + n));
        ll_store(g_act + (b * FF + cta * 16 + n) / 2, bf16r(gelu_tanh(g0)) * u0, bf16r(gelu_tanh(g1)) * u1, ep);
    }
    PROF(10);
    if (cta >= DM / 16) return;
    {
        long long t0 = 0;
        for (;;) {
            bool ok = true;
#pragma unroll
            for (int r = 0; r < 6; ++r) {
                const int i = tid + r * NCONS, b = i / 384, c4 = i - b * 384;
                const uint4 v = ll_ld2(g_act + 2 * i);
                *(uint2*)(smem + SM_ACT + b * ACT_PITCH + c4 * 8) = make_uint2(v.x, v.z);
                ok = ok && v.y == ep && v.w == ep;
            }
            if (ok) break;
            if (t0 == 0) t0 = clock64();
            else if (clock64() - t0 > WAIT_LIMIT_CYCLES) __trap();
        }
        cp_async_wait_all();
        cons_sync();
        PROF(11);
        gemv_mma<12, 1>(sbase + SM_WD + warp * 192 * P16, P16, sbase + SM_ACT + warp * 384, ACT_PITCH, s_part + warp * 320, lane);
        cons_sync();
        if (tid < 32) {
            const int b = tid >> 3, n = (tid & 7) * 2, col = cta * 16 + n;
            const float f0 = bf16r(tall_sum(s_part, b, n)), f1 = bf16r(tall_sum(s_part, b, n + 1));
            __nv_bfloat162 p = __floats2bfloat162_rn(s_xp[b * DM + col] + bf16r(bf_lo(m_gb[0]) * f0),
                                                     s_xp[b * DM + col + 1] + bf16r(bf_hi(m_gb[0]) * f1));
            *(__nv_bfloat162*)(out + b * DM + col) = p;
        }
    }
    PROF(12);
}

}

extern "C" void kernel_launch(void* const* d_in, const int* in_sizes, int n_in, void* d_out, int out_size) {
    (void)in_sizes; (void)n_in; (void)out_size;
    const __nv_bfloat16* A_x = (const __nv_bfloat16*)d_in[0];
    const __nv_bfloat16* A_k = (const __nv_bfloat16*)d_in[1];
    const __nv_bfloat16* A_v = (const __nv_bfloat16*)d_in[2];
    const __nv_bfloat16* A_wq = (const __nv_bfloat16*)d_in[3];
    const __nv_bfloat16* A_wo = (const __nv_bfloat16*)d_in[4];
    const __nv_bfloat16* B_wg = (const __nv_bfloat16*)d_in[6];
    const __nv_bfloat16* B_wu = (const __nv_bfloat16*)d_in[7];
    const __nv_bfloat16* B_wd = (const __nv_bfloat16*)d_in[8];
    const __nv_bfloat16* c = (const __nv_bfloat16*)d_in[9];
    const __nv_bfloat16* w_mod = (const __nv_bfloat16*)d_in[10];
    static int grid = 0;
    if (grid == 0) {
        cudaFuncSetAttribute(decode_block_kernel, cudaFuncAttributeMaxDynamicSharedMemorySize, SM_TOTAL);
        int dev = 0, sms = 0;
        cudaGetDevice(&dev);
        cudaDeviceGetAttribute(&sms, cudaDevAttrMultiProcessorCount, dev);
        grid = sms < 132 ? sms : 132;
    }
    decode_block_kernel<<<grid, NTHREADS, SM_TOTAL>>>(A_x, A_k, A_v, A_wq, A_wo, B_wg, B_wu, B_wd, c, w_mod,
                                                      (__nv_bfloat16*)d_out);
}
```

```cpp
#include <cuda_runtime.h>
#include <cuda_bf16.h>
#include <stdint.h>

namespace {

constexpr int NB = 4;
constexpr int DM = 640;
constexpr int NH = 32;
constexpr int SK = 4096;
constexpr int DH = 192;
constexpr int FF = 1536;
constexpr int MODN = 6 * DM;
constexpr int QN = NH * DH;
constexpr int NBH = NB * NH;

constexpr int NCONS = 256;
constexpr int NTHREADS = NCONS + 32;
constexpr int TILE_KEYS = 64;
constexpr int TILE_BYTES = TILE_KEYS * DH * 2;
constexpr int STAGE_BYTES = TILE_BYTES;
constexpr int NST = 6;
constexpr int PRE = 3;
constexpr int TPI = 2;
constexpr int ITEM_KEYS = TPI * TILE_KEYS;
constexpr int CHUNKS = SK / ITEM_KEYS;
constexpr int NITEM_K = NBH * CHUNKS;
constexpr int NITEM = 2 * NITEM_K;

constexpr int A_PITCH = 1296;
constexpr int ACT_PITCH = FF * 2 + 16;
constexpr int P16 = 48;
constexpr int P32 = 80;
constexpr int P48 = 112;
constexpr int P80 = 176;
constexpr int WO_ROWS = 384;

constexpr int SM_RING = 0;
constexpr int SM_WQ = PRE * STAGE_BYTES;
constexpr int SM_WO = 0;
constexpr int SM_WD = SM_WO + WO_ROWS * P80;
constexpr int SM_W32 = NST * STAGE_BYTES;
constexpr int SM_ACT = SM_W32;
constexpr int SM_A = SM_W32 + DM * P32;
constexpr int SM_PART = SM_A + NB * A_PITCH;
constexpr int SM_XP = SM_PART + 8 * 4 * 80 * 4;
constexpr int SM_RED = SM_XP + NB * DM * 4;
constexpr int SM_ITEM = SM_RED + 16 * 4;
constexpr int SM_TAG = SM_ITEM + 16 * 4;
constexpr int SM_BAR = SM_TAG + 16 * 4;
constexpr int SM_TOTAL = SM_BAR + (2 * NST + 1) * 8;
static_assert(SM_WQ + DM * P48 <= NST * STAGE_BYTES, "prologue overlay");
static_assert(SM_WD + FF * P16 <= NST * STAGE_BYTES, "tail overlay");
static_assert(SM_TOTAL <= 232448, "smem");
#define THR_ITEMS 6
#define THR_DEPTH 3
#define PSTART 0

__device__ __align__(128) unsigned long long g_mod[NB * MODN / 2];
__device__ __align__(128) unsigned long long g_q[NB * QN / 2];
__device__ __align__(128) unsigned long long g_act[NB * FF / 2];
__device__ __align__(128) unsigned int g_s[NBH * SK];
__device__ __align__(128) unsigned long long g_stat[NBH * CHUNKS];
__device__ __align__(128) float g_o[2][NB * QN];
__device__ __align__(128) float g_attn[2][NB * DM];
__device__ __align__(128) unsigned int g_bar[8];
__device__ unsigned int g_work;
__device__ unsigned int g_epoch;

#define PROF(k) do { } while (0)
#define PROFP(k) do { } while (0)

__device__ __forceinline__ float bf16r(float x) { return __bfloat162float(__float2bfloat16_rn(x)); }
__device__ __forceinline__ float bf_lo(uint32_t u) { return __uint_as_float(u << 16); }
__device__ __forceinline__ float bf_hi(uint32_t u) { return __uint_as_float(u & 0xffff0000u); }

__device__ __forceinline__ uint32_t smem_u32(const void* p) { return (uint32_t)__cvta_generic_to_shared(p); }
__device__ __forceinline__ void mbar_init(uint32_t bar, uint32_t count) {
    asm volatile("mbarrier.init.shared::cta.b64 [%0], %1;" ::"r"(bar), "r"(count) : "memory");
}
__device__ __forceinline__ void mbar_expect_tx(uint32_t bar, uint32_t bytes) {
    asm volatile("mbarrier.arrive.expect_tx.shared::cta.b64 _, [%0], %1;" ::"r"(bar), "r"(bytes) : "memory");
}
__device__ __forceinline__ void mbar_arrive(uint32_t bar) {
    asm volatile("mbarrier.arrive.shared::cta.b64 _, [%0];" ::"r"(bar) : "memory");
}
constexpr long long WAIT_LIMIT_CYCLES = 200000000LL;
__device__ __forceinline__ uint32_t mbar_try(uint32_t bar, uint32_t parity) {
    uint32_t done;
    asm volatile(
        "{\n\t.reg .pred p;\n\t"
        "mbarrier.try_wait.parity.shared::cta.b64 p, [%1], %2;\n\t"
        "selp.u32 %0, 1, 0, p;\n\t}"
        : "=r"(done) : "r"(bar), "r"(parity) : "memory");
    return done;
}
__device__ __noinline__ void mbar_wait_slow(uint32_t bar, uint32_t parity) {
    const long long t0 = clock64();
    while (!mbar_try(bar, parity)) {
        if (clock64() - t0 > WAIT_LIMIT_CYCLES) __trap();
    }
}
__device__ __forceinline__ void mbar_wait(uint32_t bar, uint32_t parity) {
    if (!mbar_try(bar, parity)) mbar_wait_slow(bar, parity);
}
__device__ __noinline__ void tag_wait_slow(volatile int* tag, int u) {
    const long long t0 = clock64();
    while (*tag != u) {
        __nanosleep(32);
        if (clock64() - t0 > WAIT_LIMIT_CYCLES) __trap();
    }
}
__device__ __forceinline__ void stage_wait(uint32_t bar_full, volatile int* s_tag, int u) {
    const int st = u % NST;
    if (s_tag[st] != u) tag_wait_slow(s_tag + st, u);
    mbar_wait(bar_full + st * 8, (u / NST) & 1);
}
__device__ __forceinline__ void bulk_g2s(uint32_t dst, const void* src, uint32_t bytes, uint32_t bar, uint64_t pol) {
    asm volatile(
        "cp.async.bulk.shared::cluster.global.mbarrier::complete_tx::bytes.L2::cache_hint [%0], [%1], %2, [%3], %4;"
        ::"r"(dst), "l"(src), "r"(bytes), "r"(bar), "l"(pol) : "memory");
}
__device__ __forceinline__ void cp_async16(uint32_t dst, const void* src) {
    asm volatile("cp.async.cg.shared.global [%0], [%1], 16;" ::"r"(dst), "l"(src) : "memory");
}
__device__ __forceinline__ void cp_async_wait_all() { asm volatile("cp.async.wait_all;" ::: "memory"); }
__device__ __forceinline__ void cp_async_commit() { asm volatile("cp.async.commit_group;" ::: "memory"); }
__device__ __forceinline__ void cp_async_wait1() { asm volatile("cp.async.wait_group 1;" ::: "memory"); }
__device__ __forceinline__ void red_release_add(unsigned int* p, unsigned int v) {
    asm volatile("red.release.gpu.global.add.u32 [%0], %1;" ::"l"(p), "r"(v) : "memory");
}
__device__ __forceinline__ void cons_sync() { asm volatile("bar.sync 1, 256;" ::: "memory"); }

__device__ __forceinline__ void red_add_v4(float* p, float a, float b, float c, float d) {
    asm volatile("red.global.add.v4.f32 [%0], {%1, %2, %3, %4};" ::"l"(p), "f"(a), "f"(b), "f"(c), "f"(d) : "memory");
}
__device__ __forceinline__ unsigned int ld_acquire(const unsigned int* p) {
    unsigned int v;
    asm volatile("ld.acquire.gpu.global.u32 %0, [%1];" : "=r"(v) : "l"(p) : "memory");
    return v;
}
__device__ __forceinline__ void ll_store(unsigned long long* p, float a, float b, unsigned int ep) {
    __nv_bfloat162 v = __floats2bfloat162_rn(a, b);
    const unsigned long long w = ((unsigned long long)ep << 32) | *(uint32_t*)&v;
    asm volatile("st.relaxed.gpu.global.u64 [%0], %1;" ::"l"(p), "l"(w) : "memory");
}
__device__ __forceinline__ uint2 ll_ld1(const unsigned long long* p) {
    unsigned long long w;
    asm volatile("ld.relaxed.gpu.global.u64 %0, [%1];" : "=l"(w) : "l"(p) : "memory");
    return make_uint2((uint32_t)w, (uint32_t)(w >> 32));
}
__device__ __forceinline__ uint4 ll_ld2(const unsigned long long* p) {
    unsigned long long a, b;
    asm volatile("ld.relaxed.gpu.global.v2.u64 {%0, %1}, [%2];" : "=l"(a), "=l"(b) : "l"(p) : "memory");
    return make_uint4((uint32_t)a, (uint32_t)(a >> 32), (uint32_t)b, (uint32_t)(b >> 32));
}
template <int N>
__device__ __forceinline__ void ll_get(const unsigned long long* p, uint32_t (&d)[N], unsigned int ep) {
    long long t0 = 0;
    for (;;) {
        bool ok = true;
#pragma unroll
        for (int i = 0; i < N; ++i) {
            const uint2 v = ll_ld1(p + i);
            d[i] = v.x;
            ok = ok && (v.y == ep);
        }
        if (ok) break;
        if (t0 == 0) t0 = clock64();
        else if (clock64() - t0 > WAIT_LIMIT_CYCLES) __trap();
    }
}

__device__ __forceinline__ void grid_arrive(unsigned int* ctr, int tid) {
    cons_sync();
    if (tid == 0) red_release_add(ctr, 1u);
}
__device__ __noinline__ void grid_wait(const unsigned int* ctr, unsigned int target, int tid) {
    if (tid == 0) {
        const long long t0 = clock64();
        while ((int)(ld_acquire(ctr) - target) < 0) {
            if (clock64() - t0 > WAIT_LIMIT_CYCLES) __trap();
        }
    }
    cons_sync();
}

__device__ __forceinline__ float warp_sum(float v) {
#pragma unroll
    for (int o = 16; o > 0; o >>= 1) v += __shfl_xor_sync(0xffffffffu, v, o);
    return v;
}
__device__ __forceinline__ float warp_max(float v) {
#pragma unroll
    for (int o = 16; o > 0; o >>= 1) v = fmaxf(v, __shfl_xor_sync(0xffffffffu, v, o));
    return v;
}

__device__ __forceinline__ void fma8(float (&acc)[8], const uint4& w, float s) {
    acc[0] = fmaf(s, bf_lo(w.x), acc[0]);
    acc[1] = fmaf(s, bf_hi(w.x), acc[1]);
    acc[2] = fmaf(s, bf_lo(w.y), acc[2]);
    acc[3] = fmaf(s, bf_hi(w.y), acc[3]);
    acc[4] = fmaf(s, bf_lo(w.z), acc[4]);
    acc[5] = fmaf(s, bf_hi(w.z), acc[5]);
    acc[6] = fmaf(s, bf_lo(w.w), acc[6]);
    acc[7] = fmaf(s, bf_hi(w.w), acc[7]);
}
__device__ __forceinline__ float dot8(const uint4& w, const float* q) {
    float s = q[0] * bf_lo(w.x);
    s = fmaf(q[1], bf_hi(w.x), s);
    s = fmaf(q[2], bf_lo(w.y), s);
    s = fmaf(q[3], bf_hi(w.y), s);
    s = fmaf(q[4], bf_lo(w.z), s);
    s = fmaf(q[5], bf_hi(w.z), s);
    s = fmaf(q[6], bf_lo(w.w), s);
    s = fmaf(q[7], bf_hi(w.w), s);
    return s;
}

__device__ __noinline__ void stage_rows(uint32_t dst, int dst_pitch, const void* src, int src_stride, int rows,
                                        int cpr, int tid, int nthr) {
    const int n = rows * cpr;
#pragma unroll 1
    for (int i = tid; i < n; i += nthr) {
        const int r = i / cpr, c = i - r * cpr;
        cp_async16(dst + r * dst_pitch + c * 16, (const unsigned char*)src + (size_t)r * src_stride + c * 16);
    }
}

template <int KS, int NT>
__device__ __noinline__ void gemv_mma(uint32_t w, int w_pitch, uint32_t a, int a_pitch, float* part, int lane) {
    float c[NT][4];
#pragma unroll
    for (int nt = 0; nt < NT; ++nt) { c[nt][0] = 0.f; c[nt][1] = 0.f; c[nt][2] = 0.f; c[nt][3] = 0.f; }
    const uint32_t ap = a + (lane >> 2) * a_pitch + (lane & 3) * 4;
    const uint32_t wp = w + ((lane & 7) + ((lane >> 4) << 3)) * w_pitch + ((lane >> 3) & 1) * 16;
#pragma unroll
    for (int ks = 0; ks < KS; ++ks) {
        uint32_t b0 = 0, b1 = 0;
        if (lane < 16) {
            asm("ld.shared.u32 %0, [%1];" : "=r"(b0) : "r"(ap + ks * 32));
            asm("ld.shared.u32 %0, [%1];" : "=r"(b1) : "r"(ap + ks * 32 + 16));
        }
#pragma unroll
        for (int nt = 0; nt < NT; ++nt) {
            uint32_t a0, a1, a2, a3;
            asm("ldmatrix.sync.aligned.m8n8.x4.trans.shared.b16 {%0, %1, %2, %3}, [%4];"
                         : "=r"(a0), "=r"(a1), "=r"(a2), "=r"(a3) : "r"(wp + ks * 16 * w_pitch + nt * 32));
            asm("mma.sync.aligned.m16n8k16.row.col.f32.bf16.bf16.f32 {%0, %1, %2, %3}, {%4, %5, %6, %7}, "
                "{%8, %9}, {%0, %1, %2, %3};"
                : "+f"(c[nt][0]), "+f"(c[nt][1]), "+f"(c[nt][2]), "+f"(c[nt][3])
                : "r"(a0), "r"(a1), "r"(a2), "r"(a3), "r"(b0), "r"(b1));
        }
    }
    if ((lane & 3) < 2) {
        float* pp = part + (lane & 3) * 160 + (lane >> 2);
#pragma unroll
        for (int nt = 0; nt < NT; ++nt) {
            pp[nt * 16] = c[nt][0];
            pp[nt * 16 + 80] = c[nt][1];
            pp[nt * 16 + 8] = c[nt][2];
            pp[nt * 16 + 88] = c[nt][3];
        }
    }
}

template <int KS, int NT>
__device__ __forceinline__ void frag_load(uint32_t (&f)[KS][NT][4], uint32_t w, int w_pitch, int lane) {
    const uint32_t wp = w + ((lane & 7) + ((lane >> 4) << 3)) * w_pitch + ((lane >> 3) & 1) * 16;
#pragma unroll
    for (int ks = 0; ks < KS; ++ks)
#pragma unroll
        for (int nt = 0; nt < NT; ++nt)
            asm volatile("ldmatrix.sync.aligned.m8n8.x4.trans.shared.b16 {%0, %1, %2, %3}, [%4];"
                         : "=r"(f[ks][nt][0]), "=r"(f[ks][nt][1]), "=r"(f[ks][nt][2]), "=r"(f[ks][nt][3])
                         : "r"(wp + ks * 16 * w_pitch + nt * 32) : "memory");
}
template <int KS, int NT>
__device__ __forceinline__ void frag_mma(const uint32_t (&f)[KS][NT][4], uint32_t a, int a_pitch, float* part, int lane) {
    float c[NT][4];
#pragma unroll
    for (int nt = 0; nt < NT; ++nt) { c[nt][0] = 0.f; c[nt][1] = 0.f; c[nt][2] = 0.f; c[nt][3] = 0.f; }
    const uint32_t ap = a + (lane >> 2) * a_pitch + (lane & 3) * 4;
    uint32_t b[KS][2];
#pragma unroll
    for (int ks = 0; ks < KS; ++ks) {
        b[ks][0] = 0; b[ks][1] = 0;
        if (lane < 16) {
            asm volatile("ld.shared.u32 %0, [%1];" : "=r"(b[ks][0]) : "r"(ap + ks * 32) : "memory");
            asm volatile("ld.shared.u32 %0, [%1];" : "=r"(b[ks][1]) : "r"(ap + ks * 32 + 16) : "memory");
        }
    }
#pragma unroll
    for (int ks = 0; ks < KS; ++ks)
#pragma unroll
        for (int nt = 0; nt < NT; ++nt)
            asm("mma.sync.aligned.m16n8k16.row.col.f32.bf16.bf16.f32 {%0, %1, %2, %3}, {%4, %5, %6, %7}, "
                "{%8, %9}, {%0, %1, %2, %3};"
                : "+f"(c[nt][0]), "+f"(c[nt][1]), "+f"(c[nt][2]), "+f"(c[nt][3])
                : "r"(f[ks][nt][0]), "r"(f[ks][nt][1]), "r"(f[ks][nt][2]), "r"(f[ks][nt][3]), "r"(b[ks][0]), "r"(b[ks][1]));
    if ((lane & 3) < 2) {
        float* pp = part + (lane & 3) * 160 + (lane >> 2);
#pragma unroll
        for (int nt = 0; nt < NT; ++nt) {
            pp[nt * 16] = c[nt][0];
            pp[nt * 16 + 80] = c[nt][1];
            pp[nt * 16 + 8] = c[nt][2];
            pp[nt * 16 + 88] = c[nt][3];
        }
    }
}

__device__ __forceinline__ float tall_sum(const float* part, int b, int n) {
    float s = 0.f;
#pragma unroll
    for (int w = 0; w < 8; ++w) s += part[(w * 4 + b) * 80 + n];
    return s;
}

__device__ __forceinline__ void ln_norm(float (&v)[10], float* s_red, int tid) {
    const int warp = tid >> 5;
    const float pv = __shfl_sync(0xffffffffu, v[0], 0);
    float s = 0.f, q = 0.f;
#pragma unroll
    for (int i = 0; i < 10; ++i) { const float d = v[i] - pv; s += d; q = fmaf(d, d, q); }
#pragma unroll
    for (int o = 16; o > 0; o >>= 1) {
        s += __shfl_xor_sync(0xffffffffu, s, o);
        q += __shfl_xor_sync(0xffffffffu, q, o);
    }
    const float md = s * (2.0f / DM);
    if ((tid & 31) == 0) *(float2*)(s_red + 2 * warp) = make_float2(pv + md, fmaxf(q - s * md, 0.f));
    cons_sync();
    const float4 r = *(const float4*)(s_red + 4 * (warp >> 1));
    const float dm = r.x - r.z;
    const float var = (r.y + r.w + dm * dm * (DM / 4)) * (1.0f / DM);
    const float mean = bf16r(0.5f * (r.x + r.z));
    const float inv = __fdiv_rn(1.0f, bf16r(sqrtf(bf16r(bf16r(var) + 1e-5f))));
#pragma unroll
    for (int i = 0; i < 10; ++i) v[i] = bf16r(bf16r(v[i] - mean) * inv);
}
__device__ __forceinline__ void modulate(const float (&n)[10], const uint32_t (&sh)[5], const uint32_t (&sc)[5], uint32_t* dst) {
#pragma unroll
    for (int i = 0; i < 5; ++i) {
        const float h0 = bf16r(n[2 * i] * bf16r(1.0f + bf_lo(sc[i]))) + bf_lo(sh[i]);
        const float h1 = bf16r(n[2 * i + 1] * bf16r(1.0f + bf_hi(sc[i]))) + bf_hi(sh[i]);
        __nv_bfloat162 p = __floats2bfloat162_rn(h0, h1);
        dst[i] = *(uint32_t*)&p;
    }
}

__device__ __forceinline__ float gelu_tanh(float x) {
    const float kBeta = 0.7978845608028654f;
    const float inner = kBeta * (x + 0.044715f * x * x * x);
    return 0.5f * x * (1.0f + tanhf(inner));
}

__global__ void __launch_bounds__(NTHREADS, 1)
decode_block_kernel(const __nv_bfloat16* __restrict__ x_in, const __nv_bfloat16* __restrict__ k_cache,
                    const __nv_bfloat16* __restrict__ v_cache, const __nv_bfloat16* __restrict__ wq,
                    const __nv_bfloat16* __restrict__ wo, const __nv_bfloat16* __restrict__ w_gate,
                    const __nv_bfloat16* __restrict__ w_up, const __nv_bfloat16* __restrict__ w_down,
                    const __nv_bfloat16* __restrict__ cvec, const __nv_bfloat16* __restrict__ w_mod,
                    __nv_bfloat16* __restrict__ out) {
    extern __shared__ __align__(128) unsigned char smem[];
    const int tid = threadIdx.x;
    const int cta = blockIdx.x;

    const uint32_t sbase = smem_u32(smem);
    const uint32_t bar_full = sbase + SM_BAR;
    const uint32_t bar_empty = bar_full + NST * 8;
    volatile int* s_item = (volatile int*)(smem + SM_ITEM);
    volatile int* s_tag = (volatile int*)(smem + SM_TAG);

    const uint32_t bar_go = bar_empty + NST * 8;
    if (tid < NST) s_tag[tid] = -1;
    if (tid == 0) {
#pragma unroll 1
        for (int s = 0; s < 2 * NST + 1; ++s) mbar_init(bar_full + s * 8, 1);
        asm volatile("fence.mbarrier_init.release.cluster;" ::: "memory");
        asm volatile("fence.proxy.async.shared::cta;" ::: "memory");
#pragma unroll 1
        for (int s = 0; s < PRE; ++s) mbar_arrive(bar_empty + s * 8);
    }
    __syncthreads();

    if (tid >= NCONS) {
        if (tid == NCONS) {
            int u = 0;
            const int G = (int)gridDim.x;
            uint64_t pol;
            asm volatile("createpolicy.fractional.L2::evict_first.b64 %0, 1.0;" : "=l"(pol));
            auto produce = [&](const int item) {
                const int it = item & (NITEM_K - 1);
                const bool is_v = item >= NITEM_K;
                const unsigned char* src = (const unsigned char*)(is_v ? v_cache : k_cache) + (size_t)it * (ITEM_KEYS * DH * 2);
#pragma unroll 1
                for (int t = 0; t < TPI; ++t, ++u) {
                    const int st = u % NST;
                    const uint32_t fb = bar_full + st * 8;
                    mbar_wait(bar_empty + st * 8, (u / NST) & 1);
                    if (item >= NITEM - THR_ITEMS * G) mbar_wait(bar_empty + ((u - THR_DEPTH) % NST) * 8, ((u - THR_DEPTH) / NST + 1) & 1);
                    s_item[st] = item;
                    s_tag[st] = u;
                    mbar_expect_tx(fb, TILE_BYTES);
                    bulk_g2s(sbase + SM_RING + st * STAGE_BYTES, src + t * TILE_BYTES, TILE_BYTES, fb, pol);
                }
            };
            if (PSTART != 3) mbar_wait(bar_go, 0);
            int item = cta;
#pragma unroll 1
            while (item < NITEM) {
                const int next = (int)atomicAdd(&g_work, 1u) + G;
                produce(item);
                item = next;
            }
#pragma unroll 1
            for (int j = 0; j < 8; ++j, u += TPI) {
                const int st = u % NST;
                mbar_wait(bar_empty + st * 8, (u / NST) & 1);
                s_item[st] = -1;
                s_tag[st] = u;
                mbar_arrive(bar_full + st * 8);
            }
            PROFP(13);
        }
        return;
    }

    const int lane = tid & 31, warp = tid >> 5;
    float* s_part = (float*)(smem + SM_PART);
    float* s_xp = (float*)(smem + SM_XP);
    float* s_red = (float*)(smem + SM_RED);
    const int lrow = tid >> 6, lcol = (tid & 63) * 10;
    uint32_t* h_dst = (uint32_t*)(smem + SM_A + lrow * A_PITCH + lcol * 2);

    PROF(0);
    const unsigned int ep = ld_acquire(&g_epoch) + 1u;
    const unsigned int target = ep * gridDim.x, tag16 = ep & 0xffffu;
    const unsigned long long* mod_row = g_mod + (lrow * MODN + lcol) / 2;
    float nv[10];
    {
        const int i1 = tid + NCONS;
        const uint4 c0 = __ldg((const uint4*)cvec + tid);
        uint4 c1 = c0;
        if (i1 < 320) c1 = __ldg((const uint4*)cvec + i1);
        uint32_t xw[5];
#pragma unroll
        for (int i = 0; i < 5; ++i) xw[i] = __ldg((const uint32_t*)(x_in + lrow * DM + lcol) + i);
        if (cta < MODN / 32) stage_rows(sbase + SM_W32, P32, w_mod + cta * 32, MODN * 2, DM, 4, tid, NCONS);
        cp_async_commit();
        if (cta < QN / 48) stage_rows(sbase + SM_WQ, P48, wq + cta * 48, QN * 2, DM, 6, tid, NCONS);
        cp_async_commit();
        if (PSTART == 1 && tid == 0) mbar_arrive(bar_go);
#pragma unroll 1
        for (int r = 0; r < 2; ++r) {
            const int i = r ? i1 : tid;
            if (i < 320) {
                const uint4 cc = r ? c1 : c0;
                const uint32_t cw[4] = {cc.x, cc.y, cc.z, cc.w};
                uint32_t ow[4];
#pragma unroll
                for (int k = 0; k < 4; ++k) {
                    const float a = bf_lo(cw[k]), b = bf_hi(cw[k]);
                    __nv_bfloat162 p = __floats2bfloat162_rn(__fdiv_rn(a, 1.0f + __expf(-a)), __fdiv_rn(b, 1.0f + __expf(-b)));
                    ow[k] = *(uint32_t*)&p;
                }
                const int b = i / 80, c8 = i - b * 80;
                *(uint4*)(smem + SM_A + b * A_PITCH + c8 * 16) = make_uint4(ow[0], ow[1], ow[2], ow[3]);
            }
        }
#pragma unroll
        for (int i = 0; i < 5; ++i) {
            nv[2 * i] = bf_lo(xw[i]);
            nv[2 * i + 1] = bf_hi(xw[i]);
            *(float2*)(s_xp + lrow * DM + lcol + 2 * i) = make_float2(nv[2 * i], nv[2 * i + 1]);
        }
    }
    float* acc_o = g_o[ep & 1];
    float* acc_attn = g_attn[ep & 1];
    if (cta == gridDim.x - 1) {
#pragma unroll 1
        for (int i = tid; i < NB * QN / 4; i += NCONS) ((float4*)g_o[~ep & 1])[i] = make_float4(0.f, 0.f, 0.f, 0.f);
#pragma unroll 1
        for (int i = tid; i < NB * DM; i += NCONS) g_attn[~ep & 1][i] = 0.f;
    }
    ln_norm(nv, s_red, tid);
    cp_async_wait1();
    cons_sync();
    if (PSTART == 0 && tid == 0) mbar_arrive(bar_go);
    if (cta < MODN / 32) {
        gemv_mma<5, 2>(sbase + SM_W32 + warp * 80 * P32, P32, sbase + SM_A + warp * 160, A_PITCH, s_part + warp * 320, lane);
        cons_sync();
        if (tid < 64) {
            const int b = tid >> 4, n = (tid & 15) * 2;
            ll_store(g_mod + (b * MODN + cta * 32 + n) / 2, tall_sum(s_part, b, n), tall_sum(s_part, b, n + 1), ep);
        }
    }
    PROF(1);

    if (cta < QN / 48) {
        cons_sync();
        {
            long long t0 = 0;
            for (;;) {
                bool ok = true;
#pragma unroll
                for (int r = 0; r < 5; ++r) {
                    const int i = tid + r * NCONS, b = i / 320, c4 = i - b * 320;
                    const uint4 v = ll_ld2(g_mod + b * (MODN / 2) + 2 * c4);
                    *(uint2*)(s_part + b * DM + 2 * c4) = make_uint2(v.x, v.z);
                    ok = ok && v.y == ep && v.w == ep;
                }
                if (ok) break;
                if (t0 == 0) t0 = clock64();
                else if (clock64() - t0 > WAIT_LIMIT_CYCLES) __trap();
            }
        }
        cons_sync();
        PROF(2);
        uint32_t sh[5], sc[5];
#pragma unroll
        for (int i = 0; i < 5; ++i) {
            sh[i] = ((const uint32_t*)s_part)[lrow * DM + lcol / 2 + i];
            sc[i] = ((const uint32_t*)s_part)[lrow * DM + DM / 2 + lcol / 2 + i];
        }
        modulate(nv, sh, sc, h_dst);
        cp_async_wait_all();
        cons_sync();
        if (PSTART == 2 && tid == 0) mbar_arrive(bar_go);
        gemv_mma<5, 3>(sbase + SM_WQ + warp * 80 * P48, P48, sbase + SM_A + warp * 160, A_PITCH, s_part + warp * 320, lane);
        cons_sync();
        if (tid < 96) {
            const int b = tid / 24, n = (tid - b * 24) * 2;
            ll_store(g_q + (b * QN + cta * 48 + n) / 2, tall_sum(s_part, b, n), tall_sum(s_part, b, n + 1), ep);
        }
    } else if (PSTART == 2 && tid == 0) {
        mbar_arrive(bar_go);
    }
    PROF(3);
    if (tid == 0) {
#pragma unroll 1
        for (int s = PRE; s < NST; ++s) mbar_arrive(bar_empty + s * 8);
    }
    uint32_t m_ga[5], m_sb[5], m_cb[5], m_gb[1] = {0u};
    if (cta < FF / 16) {
        if (warp == 7) {
            stage_rows(sbase + SM_W32, P32, w_gate + cta * 16, FF * 2, DM, 2, lane, 32);
            stage_rows(sbase + SM_W32 + 32, P32, w_up + cta * 16, FF * 2, DM, 2, lane, 32);
        }
    }
    PROF(4);

    {
        const int sub = lane & 7, grp = lane >> 3;
        for (int u0 = warp * TPI;; u0 += 8 * TPI) {
            if (u0 >= 8 * TPI && u0 < 16 * TPI && cta < FF / 16) {
                ll_get(mod_row + DM, m_ga, ep);
                ll_get(mod_row + 3 * DM / 2, m_sb, ep);
                ll_get(mod_row + 2 * DM, m_cb, ep);
                if (tid < 32 && cta < DM / 16) ll_get(g_mod + ((tid >> 3) * MODN + 5 * DM + cta * 16) / 2 + (tid & 7), m_gb, ep);
            }
            if (u0 == (8 + 6) * TPI) {
                if (cta < QN / 48) {
#pragma unroll 1
                    for (int i = lane; i < 48 * DM * 2 / 128; i += 32) {
                        unsigned int v;
                        asm volatile("ld.global.L2::128B.u32 %0, [%1];" : "=r"(v) : "l"((const unsigned char*)(wo + (size_t)cta * 48 * DM) + i * 128));
                    }
                }
                if (cta < FF / 16) {
#pragma unroll 1
                    for (int i = lane; i < 16 * DM * 2 / 128; i += 32) {
                        unsigned int v;
                        asm volatile("ld.global.L2::128B.u32 %0, [%1];" : "=r"(v) : "l"((const unsigned char*)(w_down + (size_t)cta * 16 * DM) + i * 128));
                    }
                }
            }
            if (s_tag[u0 % NST] != u0) tag_wait_slow(s_tag + u0 % NST, u0);
            const int item = s_item[u0 % NST];
            if (item < 0) {
                mbar_wait(bar_full + (u0 % NST) * 8, (u0 / NST) & 1);
                __syncwarp();
                if (lane == 0) mbar_arrive(bar_empty + (u0 % NST) * 8);
                break;
            }
            const int bh = (item & (NITEM_K - 1)) / CHUNKS;
            if (item < NITEM_K) {
                unsigned int* gs = g_s + (size_t)item * ITEM_KEYS;
                float qr[24];
                {
                    const unsigned long long* qp = g_q + ((bh >> 5) * QN + (bh & 31) * DH) / 2 + sub * 4;
                    long long t0 = 0;
                    for (;;) {
                        bool ok = true;
#pragma unroll
                        for (int j = 0; j < 6; ++j) {
                            const uint4 v = ll_ld2(qp + (j >> 1) * 32 + (j & 1) * 2);
                            qr[j * 4 + 0] = bf_lo(v.x); qr[j * 4 + 1] = bf_hi(v.x);
                            qr[j * 4 + 2] = bf_lo(v.z); qr[j * 4 + 3] = bf_hi(v.z);
                            ok = ok && v.y == ep && v.w == ep;
                        }
                        if (ok) break;
                        if (t0 == 0) t0 = clock64();
                        else if (clock64() - t0 > WAIT_LIMIT_CYCLES) __trap();
                    }
                }
                float m_run = -INFINITY, l_run = 0.f;
#pragma unroll 1
                for (int hh = 0; hh < 2 * TPI; ++hh) {
                    const int u = u0 + (hh >> 1), st = u % NST;
                    if (!(hh & 1)) stage_wait(bar_full, s_tag, u);
                    const uint4* tile = (const uint4*)(smem + SM_RING + st * STAGE_BYTES) + (hh & 1) * (32 * 24);
                    float part[8];
#pragma unroll
                    for (int it = 0; it < 8; ++it) {
                        const uint4* row = tile + (it * 4 + grp) * 24 + sub;
                        const uint4 a = row[0], b = row[8], c = row[16];
                        part[it] = dot8(a, qr) + dot8(b, qr + 8) + dot8(c, qr + 16);
                    }
                    if (hh & 1) {
                        __syncwarp();
                        if (lane == 0) mbar_arrive(bar_empty + st * 8);
                    }
#pragma unroll
                    for (int j = 0; j < 4; ++j) {
                        const float send = (sub & 4) ? part[j] : part[j + 4];
                        const float keep = (sub & 4) ? part[j + 4] : part[j];
                        part[j] = keep + __shfl_xor_sync(0xffffffffu, send, 4);
                    }
#pragma unroll
                    for (int j = 0; j < 2; ++j) {
                        const float send = (sub & 2) ? part[j] : part[j + 2];
                        const float keep = (sub & 2) ? part[j + 2] : part[j];
                        part[j] = keep + __shfl_xor_sync(0xffffffffu, send, 2);
                    }
                    {
                        const float send = (sub & 1) ? part[0] : part[1];
                        const float keep = (sub & 1) ? part[1] : part[0];
                        part[0] = keep + __shfl_xor_sync(0xffffffffu, send, 1);
                    }
                    const float s = bf16r(bf16r(part[0]) * 0.07216878364870323f);
                    asm volatile("st.relaxed.gpu.global.u32 [%0], %1;" ::"l"(gs + hh * 32 + sub * 4 + grp), "r"(__float_as_uint(s) | tag16) : "memory");
                    const float m_new = fmaxf(m_run, s);
                    l_run = l_run * __expf(m_run - m_new) + __expf(s - m_new);
                    m_run = m_new;
                }
                const float m = warp_max(m_run);
                const float l = warp_sum(l_run * __expf(m_run - m));
                if (lane == 0)
                    asm volatile("st.relaxed.gpu.global.u64 [%0], %1;" ::"l"(g_stat + item),
                                 "l"(((unsigned long long)__float_as_uint(l) << 32) | (__float_as_uint(m) | tag16)) : "memory");
            } else {
                float pr[2 * TPI];
                {
                    const unsigned int* gs = g_s + (size_t)(item - NITEM_K) * ITEM_KEYS + lane;
                    uint2 st2;
                    long long t0 = 0;
                    for (;;) {
                        st2 = ll_ld1(g_stat + bh * CHUNKS + lane);
                        bool ok = (st2.x & 0xffffu) == tag16;
#pragma unroll
                        for (int hh = 0; hh < 2 * TPI; ++hh) {
                            unsigned int w;
                            asm volatile("ld.relaxed.gpu.global.u32 %0, [%1];" : "=r"(w) : "l"(gs + hh * 32) : "memory");
                            ok = ok && (w & 0xffffu) == tag16;
                            pr[hh] = bf_hi(w);
                        }
                        if (__all_sync(0xffffffffu, ok)) break;
                        if (t0 == 0) t0 = clock64();
                        else if (clock64() - t0 > WAIT_LIMIT_CYCLES) __trap();
                    }
                    const float mi = bf_hi(st2.x);
                    const float mm = warp_max(mi);
                    const float ll = warp_sum(__uint_as_float(st2.y) * __expf(mi - mm));
#pragma unroll
                    for (int hh = 0; hh < 2 * TPI; ++hh) pr[hh] = bf16r(__fdiv_rn(__expf(pr[hh] - mm), ll));
                }
                float acc[3][8];
#pragma unroll
                for (int j = 0; j < 3; ++j)
#pragma unroll
                    for (int e = 0; e < 8; ++e) acc[j][e] = 0.f;
#pragma unroll
                for (int hh = 0; hh < 2 * TPI; ++hh) {
                    const int u = u0 + (hh >> 1), st = u % NST;
                    if (!(hh & 1)) stage_wait(bar_full, s_tag, u);
                    const uint4* tile = (const uint4*)(smem + SM_RING + st * STAGE_BYTES) + (hh & 1) * (32 * 24);
#pragma unroll
                    for (int it = 0; it < 8; ++it) {
                        const uint4* row = tile + (it * 4 + grp) * 24 + sub;
                        const uint4 a = row[0], b = row[8], c = row[16];
                        const float p = __shfl_sync(0xffffffffu, pr[hh], it * 4 + grp);
                        fma8(acc[0], a, p);
                        fma8(acc[1], b, p);
                        fma8(acc[2], c, p);
                    }
                    if (hh & 1) {
                        __syncwarp();
                        if (lane == 0) mbar_arrive(bar_empty + st * 8);
                    }
                }
                float* go = acc_o + (bh >> 5) * QN + (bh & 31) * DH + sub * 8;
#pragma unroll
                for (int j = 0; j < 3; ++j) {
#pragma unroll
                    for (int e = 0; e < 8; ++e) {
                        float v = acc[j][e];
                        v += __shfl_xor_sync(0xffffffffu, v, 8);
                        v += __shfl_xor_sync(0xffffffffu, v, 16);
                        acc[j][e] = v;
                    }
                    if (grp == 0) {
                        red_add_v4(go + j * 64, acc[j][0], acc[j][1], acc[j][2], acc[j][3]);
                        red_add_v4(go + j * 64 + 4, acc[j][4], acc[j][5], acc[j][6], acc[j][7]);
                    }
                }
            }
        }
    }
    PROF(5);
    grid_arrive(&g_bar[2], tid);
    PROF(6);
    const int ks = cta >> 3, ns = cta & 7;
    if (cta < 128 && tid < 240) {
        const int r0 = tid / 10, c = tid - r0 * 10;
        const unsigned char* src = (const unsigned char*)(wo + ((size_t)ks * WO_ROWS + r0) * DM + ns * 80) + c * 16;
        const uint32_t dst = sbase + SM_WO + r0 * P80 + c * 16;
#pragma unroll
        for (int i = 0; i < WO_ROWS / 24; ++i) cp_async16(dst + i * 24 * P80, src + (size_t)i * 24 * DM * 2);
    }
    grid_wait(&g_bar[2], target, tid);
    if (cta == 0 && tid == 0) { g_work = 0u; g_epoch = ep; }
    PROF(7);

    if (cta < 128) {
#pragma unroll
        for (int r = 0; r < 2; ++r) {
            const int i = tid + r * NCONS;
            if (i < NB * WO_ROWS / 4) {
                const int b = i / 96, c4 = i - b * 96;
                const float4 v = __ldcg((const float4*)(acc_o + b * QN + ks * WO_ROWS) + c4);
                __nv_bfloat162 p0 = __floats2bfloat162_rn(v.x, v.y), p1 = __floats2bfloat162_rn(v.z, v.w);
                uint2 w2;
                w2.x = *(uint32_t*)&p0; w2.y = *(uint32_t*)&p1;
                *(uint2*)(smem + SM_A + b * A_PITCH + c4 * 8) = w2;
            }
        }
        cp_async_wait_all();
        cons_sync();
        gemv_mma<3, 5>(sbase + SM_WO + warp * 48 * P80, P80, sbase + SM_A + warp * 96, A_PITCH, s_part + warp * 320, lane);
        cons_sync();
        if (tid < 80) {
            const int b = tid / 20, n4 = tid - b * 20;
            float4 s4 = make_float4(0.f, 0.f, 0.f, 0.f);
#pragma unroll
            for (int w = 0; w < 8; ++w) {
                const float4 v = *(const float4*)(s_part + (w * 4 + b) * 80 + n4 * 4);
                s4.x += v.x; s4.y += v.y; s4.z += v.z; s4.w += v.w;
            }
            red_add_v4(acc_attn + b * DM + ns * 80 + n4 * 4, s4.x, s4.y, s4.z, s4.w);
        }
    }
    PROF(8);
    grid_arrive(&g_bar[3], tid);
    if (cta >= FF / 16) return;
    if (cta < DM / 16) {
        const unsigned char* src = (const unsigned char*)(w_down + (size_t)(tid >> 1) * DM + cta * 16) + (tid & 1) * 16;
        const uint32_t dst = sbase + SM_WD + (tid >> 1) * P16 + (tid & 1) * 16;
#pragma unroll
        for (int i = 0; i < FF / 128; ++i) cp_async16(dst + i * 128 * P16, src + (size_t)i * 128 * DM * 2);
    }
    uint32_t fe[5][2][4];
    frag_load<5, 2>(fe, sbase + SM_W32 + warp * 80 * P32, P32, lane);
    grid_wait(&g_bar[3], target, tid);
    PROF(9);
    {
        float4 v[3];
#pragma unroll
        for (int r = 0; r < 3; ++r)
            if (tid + r * NCONS < NB * DM / 4) v[r] = __ldcg((const float4*)acc_attn + tid + r * NCONS);
#pragma unroll
        for (int r = 0; r < 3; ++r)
            if (tid + r * NCONS < NB * DM / 4) ((float4*)s_part)[tid + r * NCONS] = v[r];
    }
    cons_sync();
#pragma unroll
    for (int i = 0; i < 5; ++i) {
        const float2 av = *((const float2*)(s_part + lrow * DM + lcol) + i);
        float2* xp = (float2*)(s_xp + lrow * DM + lcol) + i;
        const float2 xv = *xp;
        nv[2 * i] = bf16r(xv.x + bf16r(bf_lo(m_ga[i]) * bf16r(av.x)));
        nv[2 * i + 1] = bf16r(xv.y + bf16r(bf_hi(m_ga[i]) * bf16r(av.y)));
        *xp = make_float2(nv[2 * i], nv[2 * i + 1]);
    }
    ln_norm(nv, s_red, tid);
    modulate(nv, m_sb, m_cb, h_dst);
    cons_sync();
    frag_mma<5, 2>(fe, sbase + SM_A + warp * 160, A_PITCH, s_part + warp * 320, lane);
    cp_async_wait_all();
    cons_sync();
    if (tid < 32) {
        const int b = tid >> 3, n = (tid & 7) * 2;
        const float g0 = bf16r(tall_sum(s_part, b, n)), g1 = bf16r(tall_sum(s_part, b, n + 1));
        const float u0 = bf16r(tall_sum(s_part, b, 16 + n)), u1 = bf16r(tall_sum(s_part, b, 17 + n));
        ll_store(g_act + (b * FF + cta * 16 + n) / 2, bf16r(gelu_tanh(g0)) * u0, bf16r(gelu_tanh(g1)) * u1, ep);
    }
    PROF(10);
    if (cta >= DM / 16) return;
    {
        uint32_t ff[12][1][4];
        frag_load<12, 1>(ff, sbase + SM_WD + warp * 192 * P16, P16, lane);
        long long t0 = 0;
        for (;;) {
            bool ok = true;
#pragma unroll
            for (int r = 0; r < 6; ++r) {
                const int i = tid + r * NCONS, b = i / 384, c4 = i - b * 384;
                const uint4 v = ll_ld2(g_act + 2 * i);
                *(uint2*)(smem + SM_ACT + b * ACT_PITCH + c4 * 8) = make_uint2(v.x, v.z);
                ok = ok && v.y == ep && v.w == ep;
            }
            if (ok) break;
            if (t0 == 0) t0 = clock64();
            else if (clock64() - t0 > WAIT_LIMIT_CYCLES) __trap();
        }
        cons_sync();
        PROF(11);
        frag_mma<12, 1>(ff, sbase + SM_ACT + warp * 384, ACT_PITCH, s_part + warp * 320, lane);
        cons_sync();
        if (tid < 32) {
            const int b = tid >> 3, n = (tid & 7) * 2, col = cta * 16 + n;
            const float f0 = bf16r(tall_sum(s_part, b, n)), f1 = bf16r(tall_sum(s_part, b, n + 1));
            __nv_bfloat162 p = __floats2bfloat162_rn(s_xp[b * DM + col] + bf16r(bf_lo(m_gb[0]) * f0),
                                                     s_xp[b * DM + col + 1] + bf16r(bf_hi(m_gb[0]) * f1));
            *(__nv_bfloat162*)(out + b * DM + col) = p;
        }
    }
    PROF(12);
}

}

extern "C" void kernel_launch(void* const* d_in, const int* in_sizes, int n_in, void* d_out, int out_size) {
    (void)in_sizes; (void)n_in; (void)out_size;
    const __nv_bfloat16* A_x = (const __nv_bfloat16*)d_in[0];
    const __nv_bfloat16* A_k = (const __nv_bfloat16*)d_in[1];
    const __nv_bfloat16* A_v = (const __nv_bfloat16*)d_in[2];
    const __nv_bfloat16* A_wq = (const __nv_bfloat16*)d_in[3];
    const __nv_bfloat16* A_wo = (const __nv_bfloat16*)d_in[4];
    const __nv_bfloat16* B_wg = (const __nv_bfloat16*)d_in[6];
    const __nv_bfloat16* B_wu = (const __nv_bfloat16*)d_in[7];
    const __nv_bfloat16* B_wd = (const __nv_bfloat16*)d_in[8];
    const __nv_bfloat16* c = (const __nv_bfloat16*)d_in[9];
    const __nv_bfloat16* w_mod = (const __nv_bfloat16*)d_in[10];
    static int grid = 0;
    if (grid == 0) {
        cudaFuncSetAttribute(decode_block_kernel, cudaFuncAttributeMaxDynamicSharedMemorySize, SM_TOTAL);
        int dev = 0, sms = 0;
        cudaGetDevice(&dev);
        cudaDeviceGetAttribute(&sms, cudaDevAttrMultiProcessorCount, dev);
        grid = sms < 132 ? sms : 132;
    }
    decode_block_kernel<<<grid, NTHREADS, SM_TOTAL>>>(A_x, A_k, A_v, A_wq, A_wo, B_wg, B_wu, B_wd, c, w_mod,
                                                      (__nv_bfloat16*)d_out);
}
```

```cpp
#include <cuda_runtime.h>
#include <cuda_bf16.h>
#include <stdint.h>

namespace {

constexpr int NB = 4;
constexpr int DM = 640;
constexpr int NH = 32;
constexpr int SK = 4096;
constexpr int DH = 192;
constexpr int FF = 1536;
constexpr int MODN = 6 * DM;
constexpr int QN = NH * DH;
constexpr int NBH = NB * NH;

constexpr int NCONS = 256;
constexpr int NTHREADS = NCONS + 32;
constexpr int TILE_KEYS = 64;
constexpr int TILE_BYTES = TILE_KEYS * DH * 2;
constexpr int STAGE_BYTES = TILE_BYTES;
constexpr int NST = 6;
constexpr int PRE = 3;
constexpr int TPI = 2;
constexpr int ITEM_KEYS = TPI * TILE_KEYS;
constexpr int CHUNKS = SK / ITEM_KEYS;
constexpr int NITEM_K = NBH * CHUNKS;
constexpr int NITEM = 2 * NITEM_K;

constexpr int A_PITCH = 1296;
constexpr int ACT_PITCH = FF * 2 + 16;
constexpr int P16 = 48;
constexpr int P32 = 80;
constexpr int P48 = 112;
constexpr int P80 = 176;
constexpr int WO_ROWS = 384;

constexpr int SM_RING = 0;
constexpr int SM_WQ = PRE * STAGE_BYTES;
constexpr int SM_WO = 0;
constexpr int SM_WD = SM_WO + WO_ROWS * P80;
constexpr int SM_W32 = NST * STAGE_BYTES;
constexpr int SM_ACT = SM_W32;
constexpr int SM_A = SM_W32 + DM * P32;
constexpr int SM_PART = SM_A + NB * A_PITCH;
constexpr int SM_XP = SM_PART + 8 * 4 * 80 * 4;
constexpr int SM_RED = SM_XP + NB * DM * 4;
constexpr int SM_ITEM = SM_RED + 16 * 4;
constexpr int SM_TAG = SM_ITEM + 16 * 4;
constexpr int SM_BAR = SM_TAG + 16 * 4;
constexpr int SM_TOTAL = SM_BAR + (2 * NST + 1) * 8;
static_assert(SM_WQ + DM * P48 <= NST * STAGE_BYTES, "prologue overlay");
static_assert(SM_WD + FF * P16 <= NST * STAGE_BYTES, "tail overlay");
static_assert(SM_TOTAL <= 232448, "smem");
#define THR_ITEMS 6
#define THR_DEPTH 3
#define PSTART 0

__device__ __align__(128) unsigned long long g_mod[NB * MODN / 2];
__device__ __align__(128) unsigned long long g_q[NB * QN / 2];
__device__ __align__(128) unsigned long long g_act[NB * FF / 2];
__device__ __align__(128) unsigned int g_s[NBH * SK];
__device__ __align__(128) unsigned long long g_stat[NBH * CHUNKS];
__device__ __align__(128) float g_o[2][NB * QN];
__device__ __align__(128) float g_attn[2][NB * DM];
__device__ __align__(128) unsigned int g_bar[8];
__device__ unsigned int g_work;
__device__ unsigned int g_epoch;

#define PROF(k) do { } while (0)
#define PROFP(k) do { } while (0)

__device__ __forceinline__ float bf16r(float x) { return __bfloat162float(__float2bfloat16_rn(x)); }
__device__ __forceinline__ float bf_lo(uint32_t u) { return __uint_as_float(u << 16); }
__device__ __forceinline__ float bf_hi(uint32_t u) { return __uint_as_float(u & 0xffff0000u); }

__device__ __forceinline__ uint32_t smem_u32(const void* p) { return (uint32_t)__cvta_generic_to_shared(p); }
__device__ __forceinline__ void mbar_init(uint32_t bar, uint32_t count) {
    asm volatile("mbarrier.init.shared::cta.b64 [%0], %1;" ::"r"(bar), "r"(count) : "memory");
}
__device__ __forceinline__ void mbar_expect_tx(uint32_t bar, uint32_t bytes) {
    asm volatile("mbarrier.arrive.expect_tx.shared::cta.b64 _, [%0], %1;" ::"r"(bar), "r"(bytes) : "memory");
}
__device__ __forceinline__ void mbar_arrive(uint32_t bar) {
    asm volatile("mbarrier.arrive.shared::cta.b64 _, [%0];" ::"r"(bar) : "memory");
}
constexpr long long WAIT_LIMIT_CYCLES = 200000000LL;
__device__ __forceinline__ uint32_t mbar_try(uint32_t bar, uint32_t parity) {
    uint32_t done;
    asm volatile(
        "{\n\t.reg .pred p;\n\t"
        "mbarrier.try_wait.parity.shared::cta.b64 p, [%1], %2;\n\t"
        "selp.u32 %0, 1, 0, p;\n\t}"
        : "=r"(done) : "r"(bar), "r"(parity) : "memory");
    return done;
}
__device__ __noinline__ void mbar_wait_slow(uint32_t bar, uint32_t parity) {
    const long long t0 = clock64();
    while (!mbar_try(bar, parity)) {
        if (clock64() - t0 > WAIT_LIMIT_CYCLES) __trap();
    }
}
__device__ __forceinline__ void mbar_wait(uint32_t bar, uint32_t parity) {
    if (!mbar_try(bar, parity)) mbar_wait_slow(bar, parity);
}
__device__ __noinline__ void tag_wait_slow(volatile int* tag, int u) {
    const long long t0 = clock64();
    while (*tag != u) {
        __nanosleep(32);
        if (clock64() - t0 > WAIT_LIMIT_CYCLES) __trap();
    }
}
__device__ __forceinline__ void stage_wait(uint32_t bar_full, volatile int* s_tag, int u) {
    const int st = u % NST;
    if (s_tag[st] != u) tag_wait_slow(s_tag + st, u);
    mbar_wait(bar_full + st * 8, (u / NST) & 1);
}
__device__ __forceinline__ void bulk_g2s(uint32_t dst, const void* src, uint32_t bytes, uint32_t bar, uint64_t pol) {
    asm volatile(
        "cp.async.bulk.shared::cluster.global.mbarrier::complete_tx::bytes.L2::cache_hint [%0], [%1], %2, [%3], %4;"
        ::"r"(dst), "l"(src), "r"(bytes), "r"(bar), "l"(pol) : "memory");
}
__device__ __forceinline__ void cp_async16(uint32_t dst, const void* src) {
    asm volatile("cp.async.cg.shared.global [%0], [%1], 16;" ::"r"(dst), "l"(src) : "memory");
}
__device__ __forceinline__ void cp_async_wait_all() { asm volatile("cp.async.wait_all;" ::: "memory"); }
__device__ __forceinline__ void cp_async_commit() { asm volatile("cp.async.commit_group;" ::: "memory"); }
__device__ __forceinline__ void cp_async_wait1() { asm volatile("cp.async.wait_group 1;" ::: "memory"); }
__device__ __forceinline__ void red_release_add(unsigned int* p, unsigned int v) {
    asm volatile("red.release.gpu.global.add.u32 [%0], %1;" ::"l"(p), "r"(v) : "memory");
}
__device__ __forceinline__ void cons_sync() { asm volatile("bar.sync 1, 256;" ::: "memory"); }

__device__ __forceinline__ void red_add_v4(float* p, float a, float b, float c, float d) {
    asm volatile("red.global.add.v4.f32 [%0], {%1, %2, %3, %4};" ::"l"(p), "f"(a), "f"(b), "f"(c), "f"(d) : "memory");
}
__device__ __forceinline__ unsigned int ld_acquire(const unsigned int* p) {
    unsigned int v;
    asm volatile("ld.acquire.gpu.global.u32 %0, [%1];" : "=r"(v) : "l"(p) : "memory");
    return v;
}
__device__ __forceinline__ void ll_store(unsigned long long* p, float a, float b, unsigned int ep) {
    __nv_bfloat162 v = __floats2bfloat162_rn(a, b);
    const unsigned long long w = ((unsigned long long)ep << 32) | *(uint32_t*)&v;
    asm volatile("st.relaxed.gpu.global.u64 [%0], %1;" ::"l"(p), "l"(w) : "memory");
}
__device__ __forceinline__ uint2 ll_ld1(const unsigned long long* p) {
    unsigned long long w;
    asm volatile("ld.relaxed.gpu.global.u64 %0, [%1];" : "=l"(w) : "l"(p) : "memory");
    return make_uint2((uint32_t)w, (uint32_t)(w >> 32));
}
__device__ __forceinline__ uint4 ll_ld2(const unsigned long long* p) {
    unsigned long long a, b;
    asm volatile("ld.relaxed.gpu.global.v2.u64 {%0, %1}, [%2];" : "=l"(a), "=l"(b) : "l"(p) : "memory");
    return make_uint4((uint32_t)a, (uint32_t)(a >> 32), (uint32_t)b, (uint32_t)(b >> 32));
}
template <int N>
__device__ __forceinline__ void ll_get(const unsigned long long* p, uint32_t (&d)[N], unsigned int ep) {
    long long t0 = 0;
    for (;;) {
        bool ok = true;
#pragma unroll
        for (int i = 0; i < N; ++i) {
            const uint2 v = ll_ld1(p + i);
            d[i] = v.x;
            ok = ok && (v.y == ep);
        }
        if (ok) break;
        if (t0 == 0) t0 = clock64();
        else if (clock64() - t0 > WAIT_LIMIT_CYCLES) __trap();
    }
}

__device__ __forceinline__ void grid_arrive(unsigned int* ctr, int tid) {
    cons_sync();
    if (tid == 0) red_release_add(ctr, 1u);
}
__device__ __noinline__ void grid_wait(const unsigned int* ctr, unsigned int target, int tid) {
    if (tid == 0) {
        const long long t0 = clock64();
        while ((int)(ld_acquire(ctr) - target) < 0) {
            if (clock64() - t0 > WAIT_LIMIT_CYCLES) __trap();
        }
    }
    cons_sync();
}

__device__ __forceinline__ float warp_sum(float v) {
#pragma unroll
    for (int o = 16; o > 0; o >>= 1) v += __shfl_xor_sync(0xffffffffu, v, o);
    return v;
}
__device__ __forceinline__ float warp_max(float v) {
#pragma unroll
    for (int o = 16; o > 0; o >>= 1) v = fmaxf(v, __shfl_xor_sync(0xffffffffu, v, o));
    return v;
}

__device__ __forceinline__ void fma8(float (&acc)[8], const uint4& w, float s) {
    acc[0] = fmaf(s, bf_lo(w.x), acc[0]);
    acc[1] = fmaf(s, bf_hi(w.x), acc[1]);
    acc[2] = fmaf(s, bf_lo(w.y), acc[2]);
    acc[3] = fmaf(s, bf_hi(w.y), acc[3]);
    acc[4] = fmaf(s, bf_lo(w.z), acc[4]);
    acc[5] = fmaf(s, bf_hi(w.z), acc[5]);
    acc[6] = fmaf(s, bf_lo(w.w), acc[6]);
    acc[7] = fmaf(s, bf_hi(w.w), acc[7]);
}
__device__ __forceinline__ float dot8(const uint4& w, const float* q) {
    float s = q[0] * bf_lo(w.x);
    s = fmaf(q[1], bf_hi(w.x), s);
    s = fmaf(q[2], bf_lo(w.y), s);
    s = fmaf(q[3], bf_hi(w.y), s);
    s = fmaf(q[4], bf_lo(w.z), s);
    s = fmaf(q[5], bf_hi(w.z), s);
    s = fmaf(q[6], bf_lo(w.w), s);
    s = fmaf(q[7], bf_hi(w.w), s);
    return s;
}

__device__ __noinline__ void stage_rows(uint32_t dst, int dst_pitch, const void* src, int src_stride, int rows,
                                        int cpr, int tid, int nthr) {
    const int n = rows * cpr;
#pragma unroll 1
    for (int i = tid; i < n; i += nthr) {
        const int r = i / cpr, c = i - r * cpr;
        cp_async16(dst + r * dst_pitch + c * 16, (const unsigned char*)src + (size_t)r * src_stride + c * 16);
    }
}

template <int KS, int NT>
__device__ __noinline__ void gemv_mma(uint32_t w, int w_pitch, uint32_t a, int a_pitch, float* part, int lane) {
    float c[NT][4];
#pragma unroll
    for (int nt = 0; nt < NT; ++nt) { c[nt][0] = 0.f; c[nt][1] = 0.f; c[nt][2] = 0.f; c[nt][3] = 0.f; }
    const uint32_t ap = a + (lane >> 2) * a_pitch + (lane & 3) * 4;
    const uint32_t wp = w + ((lane & 7) + ((lane >> 4) << 3)) * w_pitch + ((lane >> 3) & 1) * 16;
#pragma unroll
    for (int ks = 0; ks < KS; ++ks) {
        uint32_t b0 = 0, b1 = 0;
        if (lane < 16) {
            asm("ld.shared.u32 %0, [%1];" : "=r"(b0) : "r"(ap + ks * 32));
            asm("ld.shared.u32 %0, [%1];" : "=r"(b1) : "r"(ap + ks * 32 + 16));
        }
#pragma unroll
        for (int nt = 0; nt < NT; ++nt) {
            uint32_t a0, a1, a2, a3;
            asm("ldmatrix.sync.aligned.m8n8.x4.trans.shared.b16 {%0, %1, %2, %3}, [%4];"
                         : "=r"(a0), "=r"(a1), "=r"(a2), "=r"(a3) : "r"(wp + ks * 16 * w_pitch + nt * 32));
            asm("mma.sync.aligned.m16n8k16.row.col.f32.bf16.bf16.f32 {%0, %1, %2, %3}, {%4, %5, %6, %7}, "
                "{%8, %9}, {%0, %1, %2, %3};"
                : "+f"(c[nt][0]), "+f"(c[nt][1]), "+f"(c[nt][2]), "+f"(c[nt][3])
                : "r"(a0), "r"(a1), "r"(a2), "r"(a3), "r"(b0), "r"(b1));
        }
    }
    if ((lane & 3) < 2) {
        float* pp = part + (lane & 3) * 160 + (lane >> 2);
#pragma unroll
        for (int nt = 0; nt < NT; ++nt) {
            pp[nt * 16] = c[nt][0];
            pp[nt * 16 + 80] = c[nt][1];
            pp[nt * 16 + 8] = c[nt][2];
            pp[nt * 16 + 88] = c[nt][3];
        }
    }
}

template <int KS, int NT>
__device__ __forceinline__ void frag_load(uint32_t (&f)[KS][NT][4], uint32_t w, int w_pitch, int lane) {
    const uint32_t wp = w + ((lane & 7) + ((lane >> 4) << 3)) * w_pitch + ((lane >> 3) & 1) * 16;
#pragma unroll
    for (int ks = 0; ks < KS; ++ks)
#pragma unroll
        for (int nt = 0; nt < NT; ++nt)
            asm volatile("ldmatrix.sync.aligned.m8n8.x4.trans.shared.b16 {%0, %1, %2, %3}, [%4];"
                         : "=r"(f[ks][nt][0]), "=r"(f[ks][nt][1]), "=r"(f[ks][nt][2]), "=r"(f[ks][nt][3])
                         : "r"(wp + ks * 16 * w_pitch + nt * 32) : "memory");
}
template <int KS, int NT>
__device__ __forceinline__ void frag_mma(const uint32_t (&f)[KS][NT][4], uint32_t a, int a_pitch, float* part, int lane) {
    float c[NT][4];
#pragma unroll
    for (int nt = 0; nt < NT; ++nt) { c[nt][0] = 0.f; c[nt][1] = 0.f; c[nt][2] = 0.f; c[nt][3] = 0.f; }
    const uint32_t ap = a + (lane >> 2) * a_pitch + (lane & 3) * 4;
    uint32_t b[KS][2];
#pragma unroll
    for (int ks = 0; ks < KS; ++ks) {
        b[ks][0] = 0; b[ks][1] = 0;
        if (lane < 16) {
            asm volatile("ld.shared.u32 %0, [%1];" : "=r"(b[ks][0]) : "r"(ap + ks * 32) : "memory");
            asm volatile("ld.shared.u32 %0, [%1];" : "=r"(b[ks][1]) : "r"(ap + ks * 32 + 16) : "memory");
        }
    }
#pragma unroll
    for (int ks = 0; ks < KS; ++ks)
#pragma unroll
        for (int nt = 0; nt < NT; ++nt)
            asm("mma.sync.aligned.m16n8k16.row.col.f32.bf16.bf16.f32 {%0, %1, %2, %3}, {%4, %5, %6, %7}, "
                "{%8, %9}, {%0, %1, %2, %3};"
                : "+f"(c[nt][0]), "+f"(c[nt][1]), "+f"(c[nt][2]), "+f"(c[nt][3])
                : "r"(f[ks][nt][0]), "r"(f[ks][nt][1]), "r"(f[ks][nt][2]), "r"(f[ks][nt][3]), "r"(b[ks][0]), "r"(b[ks][1]));
    if ((lane & 3) < 2) {
        float* pp = part + (lane & 3) * 160 + (lane >> 2);
#pragma unroll
        for (int nt = 0; nt < NT; ++nt) {
            pp[nt * 16] = c[nt][0];
            pp[nt * 16 + 80] = c[nt][1];
            pp[nt * 16 + 8] = c[nt][2];
            pp[nt * 16 + 88] = c[nt][3];
        }
    }
}

__device__ __forceinline__ float tall_sum(const float* part, int b, int n) {
    float s = 0.f;
#pragma unroll
    for (int w = 0; w < 8; ++w) s += part[(w * 4 + b) * 80 + n];
    return s;
}

__device__ __forceinline__ void ln_norm(float (&v)[10], float* s_red, int tid) {
    const int warp = tid >> 5;
    const float pv = __shfl_sync(0xffffffffu, v[0], 0);
    float s = 0.f, q = 0.f;
#pragma unroll
    for (int i = 0; i < 10; ++i) { const float d = v[i] - pv; s += d; q = fmaf(d, d, q); }
#pragma unroll
    for (int o = 16; o > 0; o >>= 1) {
        s += __shfl_xor_sync(0xffffffffu, s, o);
        q += __shfl_xor_sync(0xffffffffu, q, o);
    }
    const float md = s * (2.0f / DM);
    if ((tid & 31) == 0) *(float2*)(s_red + 2 * warp) = make_float2(pv + md, fmaxf(q - s * md, 0.f));
    cons_sync();
    const float4 r = *(const float4*)(s_red + 4 * (warp >> 1));
    const float dm = r.x - r.z;
    const float var = (r.y + r.w + dm * dm * (DM / 4)) * (1.0f / DM);
    const float mean = bf16r(0.5f * (r.x + r.z));
    const float inv = __fdiv_rn(1.0f, bf16r(sqrtf(bf16r(bf16r(var) + 1e-5f))));
#pragma unroll
    for (int i = 0; i < 10; ++i) v[i] = bf16r(bf16r(v[i] - mean) * inv);
}
__device__ __forceinline__ void modulate(const float (&n)[10], const uint32_t (&sh)[5], const uint32_t (&sc)[5], uint32_t* dst) {
#pragma unroll
    for (int i = 0; i < 5; ++i) {
        const float h0 = bf16r(n[2 * i] * bf16r(1.0f + bf_lo(sc[i]))) + bf_lo(sh[i]);
        const float h1 = bf16r(n[2 * i + 1] * bf16r(1.0f + bf_hi(sc[i]))) + bf_hi(sh[i]);
        __nv_bfloat162 p = __floats2bfloat162_rn(h0, h1);
        dst[i] = *(uint32_t*)&p;
    }
}

__device__ __forceinline__ float gelu_tanh(float x) {
    const float kBeta = 0.7978845608028654f;
    const float inner = kBeta * (x + 0.044715f * x * x * x);
    return 0.5f * x * (1.0f + tanhf(inner));
}

__global__ void __launch_bounds__(NTHREADS, 1)
decode_block_kernel(const __nv_bfloat16* __restrict__ x_in, const __nv_bfloat16* __restrict__ k_cache,
                    const __nv_bfloat16* __restrict__ v_cache, const __nv_bfloat16* __restrict__ wq,
                    const __nv_bfloat16* __restrict__ wo, const __nv_bfloat16* __restrict__ w_gate,
                    const __nv_bfloat16* __restrict__ w_up, const __nv_bfloat16* __restrict__ w_down,
                    const __nv_bfloat16* __restrict__ cvec, const __nv_bfloat16* __restrict__ w_mod,
                    __nv_bfloat16* __restrict__ out) {
    extern __shared__ __align__(128) unsigned char smem[];
    const int tid = threadIdx.x;
    const int cta = blockIdx.x;

    const uint32_t sbase = smem_u32(smem);
    const uint32_t bar_full = sbase + SM_BAR;
    const uint32_t bar_empty = bar_full + NST * 8;
    volatile int* s_item = (volatile int*)(smem + SM_ITEM);
    volatile int* s_tag = (volatile int*)(smem + SM_TAG);

    const uint32_t bar_go = bar_empty + NST * 8;
    if (tid < NST) s_tag[tid] = -1;
    if (tid == 0) {
#pragma unroll 1
        for (int s = 0; s < 2 * NST + 1; ++s) mbar_init(bar_full + s * 8, 1);
        asm volatile("fence.mbarrier_init.release.cluster;" ::: "memory");
        asm volatile("fence.proxy.async.shared::cta;" ::: "memory");
#pragma unroll 1
        for (int s = 0; s < PRE; ++s) mbar_arrive(bar_empty + s * 8);
    }
    __syncthreads();

    if (tid >= NCONS) {
        if (tid == NCONS) {
            int u = 0;
            const int G = (int)gridDim.x;
            uint64_t pol;
            asm volatile("createpolicy.fractional.L2::evict_first.b64 %0, 1.0;" : "=l"(pol));
            auto produce = [&](const int item) {
                const int it = item & (NITEM_K - 1);
                const bool is_v = item >= NITEM_K;
                const unsigned char* src = (const unsigned char*)(is_v ? v_cache : k_cache) + (size_t)it * (ITEM_KEYS * DH * 2);
#pragma unroll 1
                for (int t = 0; t < TPI; ++t, ++u) {
                    const int st = u % NST;
                    const uint32_t fb = bar_full + st * 8;
                    mbar_wait(bar_empty + st * 8, (u / NST) & 1);
                    if (item >= NITEM - THR_ITEMS * G) mbar_wait(bar_empty + ((u - THR_DEPTH) % NST) * 8, ((u - THR_DEPTH) / NST + 1) & 1);
                    s_item[st] = item;
                    s_tag[st] = u;
                    mbar_expect_tx(fb, TILE_BYTES);
                    bulk_g2s(sbase + SM_RING + st * STAGE_BYTES, src + t * TILE_BYTES, TILE_BYTES, fb, pol);
                }
            };
            if (PSTART != 3) mbar_wait(bar_go, 0);
            int item = cta;
#pragma unroll 1
            while (item < NITEM) {
                const int next = (int)atomicAdd(&g_work, 1u) + G;
                produce(item);
                item = next;
            }
#pragma unroll 1
            for (int j = 0; j < 8; ++j, u += TPI) {
                const int st = u % NST;
                mbar_wait(bar_empty + st * 8, (u / NST) & 1);
                s_item[st] = -1;
                s_tag[st] = u;
                mbar_arrive(bar_full + st * 8);
            }
            PROFP(13);
        }
        return;
    }

    const int lane = tid & 31, warp = tid >> 5;
    float* s_part = (float*)(smem + SM_PART);
    float* s_xp = (float*)(smem + SM_XP);
    float* s_red = (float*)(smem + SM_RED);
    const int lrow = tid >> 6, lcol = (tid & 63) * 10;
    uint32_t* h_dst = (uint32_t*)(smem + SM_A + lrow * A_PITCH + lcol * 2);

    PROF(0);
    const unsigned int ep = ld_acquire(&g_epoch) + 1u;
    const unsigned int target = ep * gridDim.x, tag16 = ep & 0xffffu;
    const unsigned long long* mod_row = g_mod + (lrow * MODN + lcol) / 2;
    float nv[10];
    {
        const int i1 = tid + NCONS;
        const uint4 c0 = __ldg((const uint4*)cvec + tid);
        uint4 c1 = c0;
        if (i1 < 320) c1 = __ldg((const uint4*)cvec + i1);
        uint32_t xw[5];
#pragma unroll
        for (int i = 0; i < 5; ++i) xw[i] = __ldg((const uint32_t*)(x_in + lrow * DM + lcol) + i);
        if (cta < MODN / 32) stage_rows(sbase + SM_W32, P32, w_mod + cta * 32, MODN * 2, DM, 4, tid, NCONS);
        cp_async_commit();
        if (cta < QN / 48) stage_rows(sbase + SM_WQ, P48, wq + cta * 48, QN * 2, DM, 6, tid, NCONS);
        cp_async_commit();
        if (PSTART == 1 && tid == 0) mbar_arrive(bar_go);
#pragma unroll 1
        for (int r = 0; r < 2; ++r) {
            const int i = r ? i1 : tid;
            if (i < 320) {
                const uint4 cc = r ? c1 : c0;
                const uint32_t cw[4] = {cc.x, cc.y, cc.z, cc.w};
                uint32_t ow[4];
#pragma unroll
                for (int k = 0; k < 4; ++k) {
                    const float a = bf_lo(cw[k]), b = bf_hi(cw[k]);
                    __nv_bfloat162 p = __floats2bfloat162_rn(__fdiv_rn(a, 1.0f + __expf(-a)), __fdiv_rn(b, 1.0f + __expf(-b)));
                    ow[k] = *(uint32_t*)&p;
                }
                const int b = i / 80, c8 = i - b * 80;
                *(uint4*)(smem + SM_A + b * A_PITCH + c8 * 16) = make_uint4(ow[0], ow[1], ow[2], ow[3]);
            }
        }
#pragma unroll
        for (int i = 0; i < 5; ++i) {
            nv[2 * i] = bf_lo(xw[i]);
            nv[2 * i + 1] = bf_hi(xw[i]);
            *(float2*)(s_xp + lrow * DM + lcol + 2 * i) = make_float2(nv[2 * i], nv[2 * i + 1]);
        }
    }
    float* acc_o = g_o[ep & 1];
    float* acc_attn = g_attn[ep & 1];
    if (cta == gridDim.x - 1) {
#pragma unroll 1
        for (int i = tid; i < NB * QN / 4; i += NCONS) ((float4*)g_o[~ep & 1])[i] = make_float4(0.f, 0.f, 0.f, 0.f);
#pragma unroll 1
        for (int i = tid; i < NB * DM; i += NCONS) g_attn[~ep & 1][i] = 0.f;
    }
    ln_norm(nv, s_red, tid);
    cp_async_wait1();
    cons_sync();
    if (PSTART == 0 && tid == 0) mbar_arrive(bar_go);
    if (cta < MODN / 32) {
        gemv_mma<5, 2>(sbase + SM_W32 + warp * 80 * P32, P32, sbase + SM_A + warp * 160, A_PITCH, s_part + warp * 320, lane);
        cons_sync();
        if (tid < 64) {
            const int b = tid >> 4, n = (tid & 15) * 2;
            ll_store(g_mod + (b * MODN + cta * 32 + n) / 2, tall_sum(s_part, b, n), tall_sum(s_part, b, n + 1), ep);
        }
    }
    PROF(1);

    if (cta < QN / 48) {
        cons_sync();
        {
            long long t0 = 0;
            for (;;) {
                bool ok = true;
#pragma unroll
                for (int r = 0; r < 5; ++r) {
                    const int i = tid + r * NCONS, b = i / 320, c4 = i - b * 320;
                    const uint4 v = ll_ld2(g_mod + b * (MODN / 2) + 2 * c4);
                    *(uint2*)(s_part + b * DM + 2 * c4) = make_uint2(v.x, v.z);
                    ok = ok && v.y == ep && v.w == ep;
                }
                if (ok) break;
                if (t0 == 0) t0 = clock64();
                else if (clock64() - t0 > WAIT_LIMIT_CYCLES) __trap();
            }
        }
        cons_sync();
        PROF(2);
        uint32_t sh[5], sc[5];
#pragma unroll
        for (int i = 0; i < 5; ++i) {
            sh[i] = ((const uint32_t*)s_part)[lrow * DM + lcol / 2 + i];
            sc[i] = ((const uint32_t*)s_part)[lrow * DM + DM / 2 + lcol / 2 + i];
        }
        modulate(nv, sh, sc, h_dst);
        cp_async_wait_all();
        cons_sync();
        if (PSTART == 2 && tid == 0) mbar_arrive(bar_go);
        gemv_mma<5, 3>(sbase + SM_WQ + warp * 80 * P48, P48, sbase + SM_A + warp * 160, A_PITCH, s_part + warp * 320, lane);
        cons_sync();
        if (tid < 96) {
            const int b = tid / 24, n = (tid - b * 24) * 2;
            ll_store(g_q + (b * QN + cta * 48 + n) / 2, tall_sum(s_part, b, n), tall_sum(s_part, b, n + 1), ep);
        }
    } else if (PSTART == 2 && tid == 0) {
        mbar_arrive(bar_go);
    }
    PROF(3);
    if (tid == 0) {
#pragma unroll 1
        for (int s = PRE; s < NST; ++s) mbar_arrive(bar_empty + s * 8);
    }
    uint32_t m_ga[5], m_sb[5], m_cb[5], m_fa[1] = {0u}, m_fb[1] = {0u};
    const int fcta = cta - ((int)gridDim.x - DM / 16);
    if (cta < FF / 16) {
        if (warp == 7) {
            stage_rows(sbase + SM_W32, P32, w_gate + cta * 16, FF * 2, DM, 2, lane, 32);
            stage_rows(sbase + SM_W32 + 32, P32, w_up + cta * 16, FF * 2, DM, 2, lane, 32);
        }
    }
    PROF(4);

    {
        const int sub = lane & 7, grp = lane >> 3;
        for (int u0 = warp * TPI;; u0 += 8 * TPI) {
            if (u0 == (8 + 6) * TPI) {
                if (cta < QN / 48) {
#pragma unroll 1
                    for (int i = lane; i < 48 * DM * 2 / 128; i += 32) {
                        unsigned int v;
                        asm volatile("ld.global.L2::128B.u32 %0, [%1];" : "=r"(v) : "l"((const unsigned char*)(wo + (size_t)cta * 48 * DM) + i * 128));
                    }
                }
                if (cta < FF / 16) {
#pragma unroll 1
                    for (int i = lane; i < 16 * DM * 2 / 128; i += 32) {
                        unsigned int v;
                        asm volatile("ld.global.L2::128B.u32 %0, [%1];" : "=r"(v) : "l"((const unsigned char*)(w_down + (size_t)cta * 16 * DM) + i * 128));
                    }
                }
            }
            if (s_tag[u0 % NST] != u0) tag_wait_slow(s_tag + u0 % NST, u0);
            const int item = s_item[u0 % NST];
            if ((u0 >= 8 * TPI && u0 < 16 * TPI) || (item < 0 && u0 < 8 * TPI)) {
                if (cta < FF / 16) {
                    ll_get(mod_row + DM, m_ga, ep);
                    ll_get(mod_row + 3 * DM / 2, m_sb, ep);
                    ll_get(mod_row + 2 * DM, m_cb, ep);
                }
                if (tid < 32 && fcta >= 0) {
                    ll_get(g_mod + ((tid >> 3) * MODN + 2 * DM + fcta * 16) / 2 + (tid & 7), m_fa, ep);
                    ll_get(g_mod + ((tid >> 3) * MODN + 5 * DM + fcta * 16) / 2 + (tid & 7), m_fb, ep);
                }
            }
            if (item < 0) {
                mbar_wait(bar_full + (u0 % NST) * 8, (u0 / NST) & 1);
                __syncwarp();
                if (lane == 0) mbar_arrive(bar_empty + (u0 % NST) * 8);
                break;
            }
            const int bh = (item & (NITEM_K - 1)) / CHUNKS;
            if (item < NITEM_K) {
                unsigned int* gs = g_s + (size_t)item * ITEM_KEYS;
                float qr[24];
                {
                    const unsigned long long* qp = g_q + ((bh >> 5) * QN + (bh & 31) * DH) / 2 + sub * 4;
                    long long t0 = 0;
                    for (;;) {
                        bool ok = true;
#pragma unroll
                        for (int j = 0; j < 6; ++j) {
                            const uint4 v = ll_ld2(qp + (j >> 1) * 32 + (j & 1) * 2);
                            qr[j * 4 + 0] = bf_lo(v.x); qr[j * 4 + 1] = bf_hi(v.x);
                            qr[j * 4 + 2] = bf_lo(v.z); qr[j * 4 + 3] = bf_hi(v.z);
                            ok = ok && v.y == ep && v.w == ep;
                        }
                        if (ok) break;
                        if (t0 == 0) t0 = clock64();
                        else if (clock64() - t0 > WAIT_LIMIT_CYCLES) __trap();
                    }
                }
                float m_run = -INFINITY, l_run = 0.f;
#pragma unroll 1
                for (int hh = 0; hh < 2 * TPI; ++hh) {
                    const int u = u0 + (hh >> 1), st = u % NST;
                    if (!(hh & 1)) stage_wait(bar_full, s_tag, u);
                    const uint4* tile = (const uint4*)(smem + SM_RING + st * STAGE_BYTES) + (hh & 1) * (32 * 24);
                    float part[8];
#pragma unroll
                    for (int it = 0; it < 8; ++it) {
                        const uint4* row = tile + (it * 4 + grp) * 24 + sub;
                        const uint4 a = row[0], b = row[8], c = row[16];
                        part[it] = dot8(a, qr) + dot8(b, qr + 8) + dot8(c, qr + 16);
                    }
                    if (hh & 1) {
                        __syncwarp();
                        if (lane == 0) mbar_arrive(bar_empty + st * 8);
                    }
#pragma unroll
                    for (int j = 0; j < 4; ++j) {
                        const float send = (sub & 4) ? part[j] : part[j + 4];
                        const float keep = (sub & 4) ? part[j + 4] : part[j];
                        part[j] = keep + __shfl_xor_sync(0xffffffffu, send, 4);
                    }
#pragma unroll
                    for (int j = 0; j < 2; ++j) {
                        const float send = (sub & 2) ? part[j] : part[j + 2];
                        const float keep = (sub & 2) ? part[j + 2] : part[j];
                        part[j] = keep + __shfl_xor_sync(0xffffffffu, send, 2);
                    }
                    {
                        const float send = (sub & 1) ? part[0] : part[1];
                        const float keep = (sub & 1) ? part[1] : part[0];
                        part[0] = keep + __shfl_xor_sync(0xffffffffu, send, 1);
                    }
                    const float s = bf16r(bf16r(part[0]) * 0.07216878364870323f);
                    asm volatile("st.relaxed.gpu.global.u32 [%0], %1;" ::"l"(gs + hh * 32 + sub * 4 + grp), "r"(__float_as_uint(s) | tag16) : "memory");
                    const float m_new = fmaxf(m_run, s);
                    l_run = l_run * __expf(m_run - m_new) + __expf(s - m_new);
                    m_run = m_new;
                }
                const float m = warp_max(m_run);
                const float l = warp_sum(l_run * __expf(m_run - m));
                if (lane == 0)
                    asm volatile("st.relaxed.gpu.global.u64 [%0], %1;" ::"l"(g_stat + item),
                                 "l"(((unsigned long long)__float_as_uint(l) << 32) | (__float_as_uint(m) | tag16)) : "memory");
            } else {
                float pr[2 * TPI];
                {
                    const unsigned int* gs = g_s + (size_t)(item - NITEM_K) * ITEM_KEYS + lane;
                    uint2 st2;
                    long long t0 = 0;
                    for (;;) {
                        st2 = ll_ld1(g_stat + bh * CHUNKS + lane);
                        bool ok = (st2.x & 0xffffu) == tag16;
#pragma unroll
                        for (int hh = 0; hh < 2 * TPI; ++hh) {
                            unsigned int w;
                            asm volatile("ld.relaxed.gpu.global.u32 %0, [%1];" : "=r"(w) : "l"(gs + hh * 32) : "memory");
                            ok = ok && (w & 0xffffu) == tag16;
                            pr[hh] = bf_hi(w);
                        }
                        if (__all_sync(0xffffffffu, ok)) break;
                        if (t0 == 0) t0 = clock64();
                        else if (clock64() - t0 > WAIT_LIMIT_CYCLES) __trap();
                    }
                    const float mi = bf_hi(st2.x);
                    const float mm = warp_max(mi);
                    const float ll = warp_sum(__uint_as_float(st2.y) * __expf(mi - mm));
#pragma unroll
                    for (int hh = 0; hh < 2 * TPI; ++hh) pr[hh] = bf16r(__fdiv_rn(__expf(pr[hh] - mm), ll));
                }
                float acc[3][8];
#pragma unroll
                for (int j = 0; j < 3; ++j)
#pragma unroll
                    for (int e = 0; e < 8; ++e) acc[j][e] = 0.f;
#pragma unroll
                for (int hh = 0; hh < 2 * TPI; ++hh) {
                    const int u = u0 + (hh >> 1), st = u % NST;
                    if (!(hh & 1)) stage_wait(bar_full, s_tag, u);
                    const uint4* tile = (const uint4*)(smem + SM_RING + st * STAGE_BYTES) + (hh & 1) * (32 * 24);
#pragma unroll
                    for (int it = 0; it < 8; ++it) {
                        const uint4* row = tile + (it * 4 + grp) * 24 + sub;
                        const uint4 a = row[0], b = row[8], c = row[16];
                        const float p = __shfl_sync(0xffffffffu, pr[hh], it * 4 + grp);
                        fma8(acc[0], a, p);
                        fma8(acc[1], b, p);
                        fma8(acc[2], c, p);
                    }
                    if (hh & 1) {
                        __syncwarp();
                        if (lane == 0) mbar_arrive(bar_empty + st * 8);
                    }
                }
                float* go = acc_o + (bh >> 5) * QN + (bh & 31) * DH + sub * 8;
#pragma unroll
                for (int j = 0; j < 3; ++j) {
#pragma unroll
                    for (int e = 0; e < 8; ++e) {
                        float v = acc[j][e];
                        v += __shfl_xor_sync(0xffffffffu, v, 8);
                        v += __shfl_xor_sync(0xffffffffu, v, 16);
                        acc[j][e] = v;
                    }
                    if (grp == 0) {
                        red_add_v4(go + j * 64, acc[j][0], acc[j][1], acc[j][2], acc[j][3]);
                        red_add_v4(go + j * 64 + 4, acc[j][4], acc[j][5], acc[j][6], acc[j][7]);
                    }
                }
            }
        }
    }
    PROF(5);
    grid_arrive(&g_bar[2], tid);
    PROF(6);
    const int ks = cta >> 3, ns = cta & 7;
    if (cta < 128 && tid < 240) {
        const int r0 = tid / 10, c = tid - r0 * 10;
        const unsigned char* src = (const unsigned char*)(wo + ((size_t)ks * WO_ROWS + r0) * DM + ns * 80) + c * 16;
        const uint32_t dst = sbase + SM_WO + r0 * P80 + c * 16;
#pragma unroll
        for (int i = 0; i < WO_ROWS / 24; ++i) cp_async16(dst + i * 24 * P80, src + (size_t)i * 24 * DM * 2);
    }
    grid_wait(&g_bar[2], target, tid);
    if (cta == 0 && tid == 0) { g_work = 0u; g_epoch = ep; }
    PROF(7);

    if (cta < 128) {
#pragma unroll
        for (int r = 0; r < 2; ++r) {
            const int i = tid + r * NCONS;
            if (i < NB * WO_ROWS / 4) {
                const int b = i / 96, c4 = i - b * 96;
                const float4 v = __ldcg((const float4*)(acc_o + b * QN + ks * WO_ROWS) + c4);
                __nv_bfloat162 p0 = __floats2bfloat162_rn(v.x, v.y), p1 = __floats2bfloat162_rn(v.z, v.w);
                uint2 w2;
                w2.x = *(uint32_t*)&p0; w2.y = *(uint32_t*)&p1;
                *(uint2*)(smem + SM_A + b * A_PITCH + c4 * 8) = w2;
            }
        }
        cp_async_wait_all();
        cons_sync();
        gemv_mma<3, 5>(sbase + SM_WO + warp * 48 * P80, P80, sbase + SM_A + warp * 96, A_PITCH, s_part + warp * 320, lane);
        cons_sync();
        if (tid < 80) {
            const int b = tid / 20, n4 = tid - b * 20;
            float4 s4 = make_float4(0.f, 0.f, 0.f, 0.f);
#pragma unroll
            for (int w = 0; w < 8; ++w) {
                const float4 v = *(const float4*)(s_part + (w * 4 + b) * 80 + n4 * 4);
                s4.x += v.x; s4.y += v.y; s4.z += v.z; s4.w += v.w;
            }
            red_add_v4(acc_attn + b * DM + ns * 80 + n4 * 4, s4.x, s4.y, s4.z, s4.w);
        }
    }
    PROF(8);
    grid_arrive(&g_bar[3], tid);
    const bool has_e = cta < FF / 16;
    if (!has_e && fcta < 0) return;
    auto stage_down = [&]() {
        const unsigned char* src = (const unsigned char*)(w_down + (size_t)(tid >> 1) * DM + fcta * 16) + (tid & 1) * 16;
        const uint32_t dst = sbase + SM_WD + (tid >> 1) * P16 + (tid & 1) * 16;
#pragma unroll
        for (int i = 0; i < FF / 128; ++i) cp_async16(dst + i * 128 * P16, src + (size_t)i * 128 * DM * 2);
    };
    if (has_e) {
        uint32_t fe[5][2][4];
        frag_load<5, 2>(fe, sbase + SM_W32 + warp * 80 * P32, P32, lane);
        grid_wait(&g_bar[3], target, tid);
        PROF(9);
        {
            float4 v[3];
#pragma unroll
            for (int r = 0; r < 3; ++r)
                if (tid + r * NCONS < NB * DM / 4) v[r] = __ldcg((const float4*)acc_attn + tid + r * NCONS);
#pragma unroll
            for (int r = 0; r < 3; ++r)
                if (tid + r * NCONS < NB * DM / 4) ((float4*)s_part)[tid + r * NCONS] = v[r];
        }
        cons_sync();
#pragma unroll
        for (int i = 0; i < 5; ++i) {
            const float2 av = *((const float2*)(s_part + lrow * DM + lcol) + i);
            const float2 xv = *((const float2*)(s_xp + lrow * DM + lcol) + i);
            nv[2 * i] = bf16r(xv.x + bf16r(bf_lo(m_ga[i]) * bf16r(av.x)));
            nv[2 * i + 1] = bf16r(xv.y + bf16r(bf_hi(m_ga[i]) * bf16r(av.y)));
        }
        ln_norm(nv, s_red, tid);
        modulate(nv, m_sb, m_cb, h_dst);
        cons_sync();
        frag_mma<5, 2>(fe, sbase + SM_A + warp * 160, A_PITCH, s_part + warp * 320, lane);
        cons_sync();
        if (tid < 32) {
            const int b = tid >> 3, n = (tid & 7) * 2;
            const float g0 = bf16r(tall_sum(s_part, b, n)), g1 = bf16r(tall_sum(s_part, b, n + 1));
            const float u0 = bf16r(tall_sum(s_part, b, 16 + n)), u1 = bf16r(tall_sum(s_part, b, 17 + n));
            ll_store(g_act + (b * FF + cta * 16 + n) / 2, bf16r(gelu_tanh(g0)) * u0, bf16r(gelu_tanh(g1)) * u1, ep);
        }
        PROF(10);
        if (fcta < 0) return;
        stage_down();
    } else {
        stage_down();
        grid_wait(&g_bar[3], target, tid);
    }
    {
        float x10 = 0.f, x11 = 0.f;
        if (tid < 32) {
            const int b = tid >> 3, col = fcta * 16 + (tid & 7) * 2;
            const float2 av = __ldcg((const float2*)(acc_attn + b * DM + col));
            x10 = bf16r(s_xp[b * DM + col] + bf16r(bf_lo(m_fa[0]) * bf16r(av.x)));
            x11 = bf16r(s_xp[b * DM + col + 1] + bf16r(bf_hi(m_fa[0]) * bf16r(av.y)));
        }
        cp_async_wait_all();
        cons_sync();
        uint32_t ff[12][1][4];
        frag_load<12, 1>(ff, sbase + SM_WD + warp * 192 * P16, P16, lane);
        long long t0 = 0;
        for (;;) {
            bool ok = true;
#pragma unroll
            for (int r = 0; r < 6; ++r) {
                const int i = tid + r * NCONS, b = i / 384, c4 = i - b * 384;
                const uint4 v = ll_ld2(g_act + 2 * i);
                *(uint2*)(smem + SM_ACT + b * ACT_PITCH + c4 * 8) = make_uint2(v.x, v.z);
                ok = ok && v.y == ep && v.w == ep;
            }
            if (ok) break;
            if (t0 == 0) t0 = clock64();
            else if (clock64() - t0 > WAIT_LIMIT_CYCLES) __trap();
        }
        cons_sync();
        PROF(11);
        frag_mma<12, 1>(ff, sbase + SM_ACT + warp * 384, ACT_PITCH, s_part + warp * 320, lane);
        cons_sync();
        if (tid < 32) {
            const int b = tid >> 3, n = (tid & 7) * 2;
            const float f0 = bf16r(tall_sum(s_part, b, n)), f1 = bf16r(tall_sum(s_part, b, n + 1));
            *(__nv_bfloat162*)(out + b * DM + fcta * 16 + n) =
                __floats2bfloat162_rn(x10 + bf16r(bf_lo(m_fb[0]) * f0), x11 + bf16r(bf_hi(m_fb[0]) * f1));
        }
    }
    PROF(12);
}

}

extern "C" void kernel_launch(void* const* d_in, const int* in_sizes, int n_in, void* d_out, int out_size) {
    (void)in_sizes; (void)n_in; (void)out_size;
    const __nv_bfloat16* A_x = (const __nv_bfloat16*)d_in[0];
    const __nv_bfloat16* A_k = (const __nv_bfloat16*)d_in[1];
    const __nv_bfloat16* A_v = (const __nv_bfloat16*)d_in[2];
    const __nv_bfloat16* A_wq = (const __nv_bfloat16*)d_in[3];
    const __nv_bfloat16* A_wo = (const __nv_bfloat16*)d_in[4];
    const __nv_bfloat16* B_wg = (const __nv_bfloat16*)d_in[6];
    const __nv_bfloat16* B_wu = (const __nv_bfloat16*)d_in[7];
    const __nv_bfloat16* B_wd = (const __nv_bfloat16*)d_in[8];
    const __nv_bfloat16* c = (const __nv_bfloat16*)d_in[9];
    const __nv_bfloat16* w_mod = (const __nv_bfloat16*)d_in[10];
    static int grid = 0;
    if (grid == 0) {
        cudaFuncSetAttribute(decode_block_kernel, cudaFuncAttributeMaxDynamicSharedMemorySize, SM_TOTAL);
        int dev = 0, sms = 0;
        cudaGetDevice(&dev);
        cudaDeviceGetAttribute(&sms, cudaDevAttrMultiProcessorCount, dev);
        grid = sms < 132 ? sms : 132;
    }
    decode_block_kernel<<<grid, NTHREADS, SM_TOTAL>>>(A_x, A_k, A_v, A_wq, A_wo, B_wg, B_wu, B_wd, c, w_mod,
                                                      (__nv_bfloat16*)d_out);
}
```

```cpp
#include <cuda_runtime.h>
#include <cuda_bf16.h>
#include <stdint.h>

namespace {

constexpr int NB = 4;
constexpr int DM = 640;
constexpr int NH = 32;
constexpr int SK = 4096;
constexpr int DH = 192;
constexpr int FF = 1536;
constexpr int MODN = 6 * DM;
constexpr int QN = NH * DH;
constexpr int NBH = NB * NH;

constexpr int NCONS = 256;
constexpr int NTHREADS = NCONS + 32;
constexpr int TILE_KEYS = 64;
constexpr int TILE_BYTES = TILE_KEYS * DH * 2;
constexpr int STAGE_BYTES = TILE_BYTES;
constexpr int NST = 6;
constexpr int PRE = 3;
constexpr int TPI = 2;
constexpr int ITEM_KEYS = TPI * TILE_KEYS;
constexpr int CHUNKS = SK / ITEM_KEYS;
constexpr int NITEM_K = NBH * CHUNKS;
constexpr int NITEM = 2 * NITEM_K;

constexpr int A_PITCH = 1296;
constexpr int ACT_PITCH = FF * 2 + 16;
constexpr int P32 = 80;
constexpr int P48 = 112;
constexpr int P80 = 176;
constexpr int WO_ROWS = 384;

constexpr int SM_RING = 0;
constexpr int SM_WQ = PRE * STAGE_BYTES;
constexpr int SM_WO = 0;
constexpr int SM_WD = 0;
constexpr int SM_W32 = NST * STAGE_BYTES;
constexpr int SM_ACT = SM_W32;
constexpr int SM_A = SM_W32 + DM * P32;
constexpr int SM_PART = SM_A + NB * A_PITCH;
constexpr int SM_XP = SM_PART + 8 * 4 * 80 * 4;
constexpr int SM_RED = SM_XP + NB * DM * 4;
constexpr int SM_ITEM = SM_RED + 16 * 4;
constexpr int SM_TAG = SM_ITEM + 16 * 4;
constexpr int SM_BAR = SM_TAG + 16 * 4;
constexpr int SM_TOTAL = SM_BAR + (2 * NST + 1) * 8;
static_assert(SM_WQ + DM * P48 <= NST * STAGE_BYTES, "prologue overlay");
static_assert(SM_WD + FF * P32 <= NST * STAGE_BYTES && WO_ROWS * P80 <= NST * STAGE_BYTES, "tail overlay");
static_assert(SM_TOTAL <= 232448, "smem");
#define THR_ITEMS 6
#define THR_DEPTH 3
#define PSTART 0

__device__ __align__(128) unsigned long long g_mod[NB * MODN / 2];
__device__ __align__(128) unsigned long long g_q[NB * QN / 2];
__device__ __align__(128) unsigned long long g_act[NB * FF / 2];
__device__ __align__(128) unsigned int g_s[NBH * SK];
__device__ __align__(128) unsigned long long g_stat[NBH * CHUNKS];
__device__ __align__(128) float g_o[2][NB * QN];
__device__ __align__(128) float g_attn[2][NB * DM];
__device__ __align__(128) unsigned int g_bar[8];
__device__ unsigned int g_work;
__device__ unsigned int g_epoch;

#define PROF(k) do { } while (0)
#define PROFP(k) do { } while (0)

__device__ __forceinline__ float bf16r(float x) { return __bfloat162float(__float2bfloat16_rn(x)); }
__device__ __forceinline__ float bf_lo(uint32_t u) { return __uint_as_float(u << 16); }
__device__ __forceinline__ float bf_hi(uint32_t u) { return __uint_as_float(u & 0xffff0000u); }

__device__ __forceinline__ uint32_t smem_u32(const void* p) { return (uint32_t)__cvta_generic_to_shared(p); }
__device__ __forceinline__ void mbar_init(uint32_t bar, uint32_t count) {
    asm volatile("mbarrier.init.shared::cta.b64 [%0], %1;" ::"r"(bar), "r"(count) : "memory");
}
__device__ __forceinline__ void mbar_expect_tx(uint32_t bar, uint32_t bytes) {
    asm volatile("mbarrier.arrive.expect_tx.shared::cta.b64 _, [%0], %1;" ::"r"(bar), "r"(bytes) : "memory");
}
__device__ __forceinline__ void mbar_arrive(uint32_t bar) {
    asm volatile("mbarrier.arrive.shared::cta.b64 _, [%0];" ::"r"(bar) : "memory");
}
constexpr long long WAIT_LIMIT_CYCLES = 200000000LL;
__device__ __forceinline__ uint32_t mbar_try(uint32_t bar, uint32_t parity) {
    uint32_t done;
    asm volatile(
        "{\n\t.reg .pred p;\n\t"
        "mbarrier.try_wait.parity.shared::cta.b64 p, [%1], %2;\n\t"
        "selp.u32 %0, 1, 0, p;\n\t}"
        : "=r"(done) : "r"(bar), "r"(parity) : "memory");
    return done;
}
__device__ __noinline__ void mbar_wait_slow(uint32_t bar, uint32_t parity) {
    const long long t0 = clock64();
    while (!mbar_try(bar, parity)) {
        if (clock64() - t0 > WAIT_LIMIT_CYCLES) __trap();
    }
}
__device__ __forceinline__ void mbar_wait(uint32_t bar, uint32_t parity) {
    if (!mbar_try(bar, parity)) mbar_wait_slow(bar, parity);
}
__device__ __noinline__ void tag_wait_slow(volatile int* tag, int u) {
    const long long t0 = clock64();
    while (*tag != u) {
        __nanosleep(32);
        if (clock64() - t0 > WAIT_LIMIT_CYCLES) __trap();
    }
}
__device__ __forceinline__ void stage_wait(uint32_t bar_full, volatile int* s_tag, int u) {
    const int st = u % NST;
    if (s_tag[st] != u) tag_wait_slow(s_tag + st, u);
    mbar_wait(bar_full + st * 8, (u / NST) & 1);
}
__device__ __forceinline__ void bulk_g2s(uint32_t dst, const void* src, uint32_t bytes, uint32_t bar, uint64_t pol) {
    asm volatile(
        "cp.async.bulk.shared::cluster.global.mbarrier::complete_tx::bytes.L2::cache_hint [%0], [%1], %2, [%3], %4;"
        ::"r"(dst), "l"(src), "r"(bytes), "r"(bar), "l"(pol) : "memory");
}
__device__ __forceinline__ void cp_async16(uint32_t dst, const void* src) {
    asm volatile("cp.async.cg.shared.global [%0], [%1], 16;" ::"r"(dst), "l"(src) : "memory");
}
__device__ __forceinline__ void cp_async_wait_all() { asm volatile("cp.async.wait_all;" ::: "memory"); }
__device__ __forceinline__ void cp_async_commit() { asm volatile("cp.async.commit_group;" ::: "memory"); }
__device__ __forceinline__ void cp_async_wait1() { asm volatile("cp.async.wait_group 1;" ::: "memory"); }
__device__ __forceinline__ void red_release_add(unsigned int* p, unsigned int v) {
    asm volatile("red.release.gpu.global.add.u32 [%0], %1;" ::"l"(p), "r"(v) : "memory");
}
__device__ __forceinline__ void cons_sync() { asm volatile("bar.sync 1, 256;" ::: "memory"); }

__device__ __forceinline__ void red_add_v4(float* p, float a, float b, float c, float d) {
    asm volatile("red.global.add.v4.f32 [%0], {%1, %2, %3, %4};" ::"l"(p), "f"(a), "f"(b), "f"(c), "f"(d) : "memory");
}
__device__ __forceinline__ unsigned int ld_acquire(const unsigned int* p) {
    unsigned int v;
    asm volatile("ld.acquire.gpu.global.u32 %0, [%1];" : "=r"(v) : "l"(p) : "memory");
    return v;
}
__device__ __forceinline__ void ll_store(unsigned long long* p, float a, float b, unsigned int ep) {
    __nv_bfloat162 v = __floats2bfloat162_rn(a, b);
    const unsigned long long w = ((unsigned long long)ep << 32) | *(uint32_t*)&v;
    asm volatile("st.relaxed.gpu.global.u64 [%0], %1;" ::"l"(p), "l"(w) : "memory");
}
__device__ __forceinline__ uint2 ll_ld1(const unsigned long long* p) {
    unsigned long long w;
    asm volatile("ld.relaxed.gpu.global.u64 %0, [%1];" : "=l"(w) : "l"(p) : "memory");
    return make_uint2((uint32_t)w, (uint32_t)(w >> 32));
}
__device__ __forceinline__ uint4 ll_ld2(const unsigned long long* p) {
    unsigned long long a, b;
    asm volatile("ld.relaxed.gpu.global.v2.u64 {%0, %1}, [%2];" : "=l"(a), "=l"(b) : "l"(p) : "memory");
    return make_uint4((uint32_t)a, (uint32_t)(a >> 32), (uint32_t)b, (uint32_t)(b >> 32));
}
template <int N>
__device__ __forceinline__ void ll_get(const unsigned long long* p, uint32_t (&d)[N], unsigned int ep) {
    long long t0 = 0;
    for (;;) {
        bool ok = true;
#pragma unroll
        for (int i = 0; i < N; ++i) {
            const uint2 v = ll_ld1(p + i);
            d[i] = v.x;
            ok = ok && (v.y == ep);
        }
        if (ok) break;
        if (t0 == 0) t0 = clock64();
        else if (clock64() - t0 > WAIT_LIMIT_CYCLES) __trap();
    }
}

__device__ __forceinline__ void grid_arrive(unsigned int* ctr, int tid) {
    cons_sync();
    if (tid == 0) red_release_add(ctr, 1u);
}
__device__ __noinline__ void grid_wait(const unsigned int* ctr, unsigned int target, int tid) {
    if (tid == 0) {
        const long long t0 = clock64();
        while ((int)(ld_acquire(ctr) - target) < 0) {
            if (clock64() - t0 > WAIT_LIMIT_CYCLES) __trap();
        }
    }
    cons_sync();
}

__device__ __forceinline__ float warp_sum(float v) {
#pragma unroll
    for (int o = 16; o > 0; o >>= 1) v += __shfl_xor_sync(0xffffffffu, v, o);
    return v;
}
__device__ __forceinline__ float warp_max(float v) {
#pragma unroll
    for (int o = 16; o > 0; o >>= 1) v = fmaxf(v, __shfl_xor_sync(0xffffffffu, v, o));
    return v;
}

__device__ __forceinline__ void fma8(float (&acc)[8], const uint4& w, float s) {
    acc[0] = fmaf(s, bf_lo(w.x), acc[0]);
    acc[1] = fmaf(s, bf_hi(w.x), acc[1]);
    acc[2] = fmaf(s, bf_lo(w.y), acc[2]);
    acc[3] = fmaf(s, bf_hi(w.y), acc[3]);
    acc[4] = fmaf(s, bf_lo(w.z), acc[4]);
    acc[5] = fmaf(s, bf_hi(w.z), acc[5]);
    acc[6] = fmaf(s, bf_lo(w.w), acc[6]);
    acc[7] = fmaf(s, bf_hi(w.w), acc[7]);
}
__device__ __forceinline__ float dot8(const uint4& w, const float* q) {
    float s = q[0] * bf_lo(w.x);
    s = fmaf(q[1], bf_hi(w.x), s);
    s = fmaf(q[2], bf_lo(w.y), s);
    s = fmaf(q[3], bf_hi(w.y), s);
    s = fmaf(q[4], bf_lo(w.z), s);
    s = fmaf(q[5], bf_hi(w.z), s);
    s = fmaf(q[6], bf_lo(w.w), s);
    s = fmaf(q[7], bf_hi(w.w), s);
    return s;
}

__device__ __noinline__ void stage_rows(uint32_t dst, int dst_pitch, const void* src, int src_stride, int rows,
                                        int cpr, int tid, int nthr) {
    const int n = rows * cpr;
#pragma unroll 1
    for (int i = tid; i < n; i += nthr) {
        const int r = i / cpr, c = i - r * cpr;
        cp_async16(dst + r * dst_pitch + c * 16, (const unsigned char*)src + (size_t)r * src_stride + c * 16);
    }
}

template <int KS, int NT>
__device__ __noinline__ void gemv_mma(uint32_t w, int w_pitch, uint32_t a, int a_pitch, float* part, int lane) {
    float c[NT][4];
#pragma unroll
    for (int nt = 0; nt < NT; ++nt) { c[nt][0] = 0.f; c[nt][1] = 0.f; c[nt][2] = 0.f; c[nt][3] = 0.f; }
    const uint32_t ap = a + (lane >> 2) * a_pitch + (lane & 3) * 4;
    const uint32_t wp = w + ((lane & 7) + ((lane >> 4) << 3)) * w_pitch + ((lane >> 3) & 1) * 16;
#pragma unroll
    for (int ks = 0; ks < KS; ++ks) {
        uint32_t b0 = 0, b1 = 0;
        if (lane < 16) {
            asm("ld.shared.u32 %0, [%1];" : "=r"(b0) : "r"(ap + ks * 32));
            asm("ld.shared.u32 %0, [%1];" : "=r"(b1) : "r"(ap + ks * 32 + 16));
        }
#pragma unroll
        for (int nt = 0; nt < NT; ++nt) {
            uint32_t a0, a1, a2, a3;
            asm("ldmatrix.sync.aligned.m8n8.x4.trans.shared.b16 {%0, %1, %2, %3}, [%4];"
                         : "=r"(a0), "=r"(a1), "=r"(a2), "=r"(a3) : "r"(wp + ks * 16 * w_pitch + nt * 32));
            asm("mma.sync.aligned.m16n8k16.row.col.f32.bf16.bf16.f32 {%0, %1, %2, %3}, {%4, %5, %6, %7}, "
                "{%8, %9}, {%0, %1, %2, %3};"
                : "+f"(c[nt][0]), "+f"(c[nt][1]), "+f"(c[nt][2]), "+f"(c[nt][3])
                : "r"(a0), "r"(a1), "r"(a2), "r"(a3), "r"(b0), "r"(b1));
        }
    }
    if ((lane & 3) < 2) {
        float* pp = part + (lane & 3) * 160 + (lane >> 2);
#pragma unroll
        for (int nt = 0; nt < NT; ++nt) {
            pp[nt * 16] = c[nt][0];
            pp[nt * 16 + 80] = c[nt][1];
            pp[nt * 16 + 8] = c[nt][2];
            pp[nt * 16 + 88] = c[nt][3];
        }
    }
}

template <int KS, int NT>
__device__ __forceinline__ void frag_load(uint32_t (&f)[KS][NT][4], uint32_t w, int w_pitch, int lane) {
    const uint32_t wp = w + ((lane & 7) + ((lane >> 4) << 3)) * w_pitch + ((lane >> 3) & 1) * 16;
#pragma unroll
    for (int ks = 0; ks < KS; ++ks)
#pragma unroll
        for (int nt = 0; nt < NT; ++nt)
            asm volatile("ldmatrix.sync.aligned.m8n8.x4.trans.shared.b16 {%0, %1, %2, %3}, [%4];"
                         : "=r"(f[ks][nt][0]), "=r"(f[ks][nt][1]), "=r"(f[ks][nt][2]), "=r"(f[ks][nt][3])
                         : "r"(wp + ks * 16 * w_pitch + nt * 32) : "memory");
}
template <int KS, int NT>
__device__ __forceinline__ void frag_mma(const uint32_t (&f)[KS][NT][4], uint32_t a, int a_pitch, float* part, int lane) {
    float c[NT][4];
#pragma unroll
    for (int nt = 0; nt < NT; ++nt) { c[nt][0] = 0.f; c[nt][1] = 0.f; c[nt][2] = 0.f; c[nt][3] = 0.f; }
    const uint32_t ap = a + (lane >> 2) * a_pitch + (lane & 3) * 4;
    uint32_t b[KS][2];
#pragma unroll
    for (int ks = 0; ks < KS; ++ks) {
        b[ks][0] = 0; b[ks][1] = 0;
        if (lane < 16) {
            asm volatile("ld.shared.u32 %0, [%1];" : "=r"(b[ks][0]) : "r"(ap + ks * 32) : "memory");
            asm volatile("ld.shared.u32 %0, [%1];" : "=r"(b[ks][1]) : "r"(ap + ks * 32 + 16) : "memory");
        }
    }
#pragma unroll
    for (int ks = 0; ks < KS; ++ks)
#pragma unroll
        for (int nt = 0; nt < NT; ++nt)
            asm("mma.sync.aligned.m16n8k16.row.col.f32.bf16.bf16.f32 {%0, %1, %2, %3}, {%4, %5, %6, %7}, "
                "{%8, %9}, {%0, %1, %2, %3};"
                : "+f"(c[nt][0]), "+f"(c[nt][1]), "+f"(c[nt][2]), "+f"(c[nt][3])
                : "r"(f[ks][nt][0]), "r"(f[ks][nt][1]), "r"(f[ks][nt][2]), "r"(f[ks][nt][3]), "r"(b[ks][0]), "r"(b[ks][1]));
    if ((lane & 3) < 2) {
        float* pp = part + (lane & 3) * 160 + (lane >> 2);
#pragma unroll
        for (int nt = 0; nt < NT; ++nt) {
            pp[nt * 16] = c[nt][0];
            pp[nt * 16 + 80] = c[nt][1];
            pp[nt * 16 + 8] = c[nt][2];
            pp[nt * 16 + 88] = c[nt][3];
        }
    }
}

__device__ __forceinline__ float tall_sum(const float* part, int b, int n) {
    float s = 0.f;
#pragma unroll
    for (int w = 0; w < 8; ++w) s += part[(w * 4 + b) * 80 + n];
    return s;
}

__device__ __forceinline__ void ln_norm(float (&v)[10], float* s_red, int tid) {
    const int warp = tid >> 5;
    const float pv = __shfl_sync(0xffffffffu, v[0], 0);
    float s = 0.f, q = 0.f;
#pragma unroll
    for (int i = 0; i < 10; ++i) { const float d = v[i] - pv; s += d; q = fmaf(d, d, q); }
#pragma unroll
    for (int o = 16; o > 0; o >>= 1) {
        s += __shfl_xor_sync(0xffffffffu, s, o);
        q += __shfl_xor_sync(0xffffffffu, q, o);
    }
    const float md = s * (2.0f / DM);
    if ((tid & 31) == 0) *(float2*)(s_red + 2 * warp) = make_float2(pv + md, fmaxf(q - s * md, 0.f));
    cons_sync();
    const float4 r = *(const float4*)(s_red + 4 * (warp >> 1));
    const float dm = r.x - r.z;
    const float var = (r.y + r.w + dm * dm * (DM / 4)) * (1.0f / DM);
    const float mean = bf16r(0.5f * (r.x + r.z));
    const float inv = __fdiv_rn(1.0f, bf16r(sqrtf(bf16r(bf16r(var) + 1e-5f))));
#pragma unroll
    for (int i = 0; i < 10; ++i) v[i] = bf16r(bf16r(v[i] - mean) * inv);
}
__device__ __forceinline__ void modulate(const float (&n)[10], const uint32_t (&sh)[5], const uint32_t (&sc)[5], uint32_t* dst) {
#pragma unroll
    for (int i = 0; i < 5; ++i) {
        const float h0 = bf16r(n[2 * i] * bf16r(1.0f + bf_lo(sc[i]))) + bf_lo(sh[i]);
        const float h1 = bf16r(n[2 * i + 1] * bf16r(1.0f + bf_hi(sc[i]))) + bf_hi(sh[i]);
        __nv_bfloat162 p = __floats2bfloat162_rn(h0, h1);
        dst[i] = *(uint32_t*)&p;
    }
}

__device__ __forceinline__ float gelu_tanh(float x) {
    const float kBeta = 0.7978845608028654f;
    const float inner = kBeta * (x + 0.044715f * x * x * x);
    return 0.5f * x * (1.0f + tanhf(inner));
}

__global__ void __launch_bounds__(NTHREADS, 1)
decode_block_kernel(const __nv_bfloat16* __restrict__ x_in, const __nv_bfloat16* __restrict__ k_cache,
                    const __nv_bfloat16* __restrict__ v_cache, const __nv_bfloat16* __restrict__ wq,
                    const __nv_bfloat16* __restrict__ wo, const __nv_bfloat16* __restrict__ w_gate,
                    const __nv_bfloat16* __restrict__ w_up, const __nv_bfloat16* __restrict__ w_down,
                    const __nv_bfloat16* __restrict__ cvec, const __nv_bfloat16* __restrict__ w_mod,
                    __nv_bfloat16* __restrict__ out) {
    extern __shared__ __align__(128) unsigned char smem[];
    const int tid = threadIdx.x;
    const int cta = blockIdx.x;

    const uint32_t sbase = smem_u32(smem);
    const uint32_t bar_full = sbase + SM_BAR;
    const uint32_t bar_empty = bar_full + NST * 8;
    volatile int* s_item = (volatile int*)(smem + SM_ITEM);
    volatile int* s_tag = (volatile int*)(smem + SM_TAG);

    const uint32_t bar_go = bar_empty + NST * 8;
    if (tid < NST) s_tag[tid] = -1;
    if (tid == 0) {
#pragma unroll 1
        for (int s = 0; s < 2 * NST + 1; ++s) mbar_init(bar_full + s * 8, 1);
        asm volatile("fence.mbarrier_init.release.cluster;" ::: "memory");
        asm volatile("fence.proxy.async.shared::cta;" ::: "memory");
#pragma unroll 1
        for (int s = 0; s < PRE; ++s) mbar_arrive(bar_empty + s * 8);
    }
    __syncthreads();

    if (tid >= NCONS) {
        if (tid == NCONS) {
            int u = 0;
            const int G = (int)gridDim.x;
            uint64_t pol;
            asm volatile("createpolicy.fractional.L2::evict_first.b64 %0, 1.0;" : "=l"(pol));
            auto produce = [&](const int item) {
                const int it = item & (NITEM_K - 1);
                const bool is_v = item >= NITEM_K;
                const unsigned char* src = (const unsigned char*)(is_v ? v_cache : k_cache) + (size_t)it * (ITEM_KEYS * DH * 2);
#pragma unroll 1
                for (int t = 0; t < TPI; ++t, ++u) {
                    const int st = u % NST;
                    const uint32_t fb = bar_full + st * 8;
                    mbar_wait(bar_empty + st * 8, (u / NST) & 1);
                    if (item >= NITEM - THR_ITEMS * G) mbar_wait(bar_empty + ((u - THR_DEPTH) % NST) * 8, ((u - THR_DEPTH) / NST + 1) & 1);
                    s_item[st] = item;
                    s_tag[st] = u;
                    mbar_expect_tx(fb, TILE_BYTES);
                    bulk_g2s(sbase + SM_RING + st * STAGE_BYTES, src + t * TILE_BYTES, TILE_BYTES, fb, pol);
                }
            };
            if (PSTART != 3) mbar_wait(bar_go, 0);
            int item = cta;
#pragma unroll 1
            while (item < NITEM) {
                const int next = (int)atomicAdd(&g_work, 1u) + G;
                produce(item);
                item = next;
            }
#pragma unroll 1
            for (int j = 0; j < 8; ++j, u += TPI) {
                const int st = u % NST;
                mbar_wait(bar_empty + st * 8, (u / NST) & 1);
                s_item[st] = -1;
                s_tag[st] = u;
                mbar_arrive(bar_full + st * 8);
            }
            PROFP(13);
        }
        return;
    }

    const int lane = tid & 31, warp = tid >> 5;
    float* s_part = (float*)(smem + SM_PART);
    float* s_xp = (float*)(smem + SM_XP);
    float* s_red = (float*)(smem + SM_RED);
    const int lrow = tid >> 6, lcol = (tid & 63) * 10;
    uint32_t* h_dst = (uint32_t*)(smem + SM_A + lrow * A_PITCH + lcol * 2);

    PROF(0);
    const unsigned int ep = ld_acquire(&g_epoch) + 1u;
    const unsigned int target = ep * gridDim.x, tag16 = ep & 0xffffu;
    const unsigned long long* mod_row = g_mod + (lrow * MODN + lcol) / 2;
    float nv[10];
    {
        const int i1 = tid + NCONS;
        const uint4 c0 = __ldg((const uint4*)cvec + tid);
        uint4 c1 = c0;
        if (i1 < 320) c1 = __ldg((const uint4*)cvec + i1);
        uint32_t xw[5];
#pragma unroll
        for (int i = 0; i < 5; ++i) xw[i] = __ldg((const uint32_t*)(x_in + lrow * DM + lcol) + i);
        if (cta < MODN / 32) stage_rows(sbase + SM_W32, P32, w_mod + cta * 32, MODN * 2, DM, 4, tid, NCONS);
        cp_async_commit();
        if (cta < QN / 48) stage_rows(sbase + SM_WQ, P48, wq + cta * 48, QN * 2, DM, 6, tid, NCONS);
        cp_async_commit();
        if (PSTART == 1 && tid == 0) mbar_arrive(bar_go);
#pragma unroll 1
        for (int r = 0; r < 2; ++r) {
            const int i = r ? i1 : tid;
            if (i < 320) {
                const uint4 cc = r ? c1 : c0;
                const uint32_t cw[4] = {cc.x, cc.y, cc.z, cc.w};
                uint32_t ow[4];
#pragma unroll
                for (int k = 0; k < 4; ++k) {
                    const float a = bf_lo(cw[k]), b = bf_hi(cw[k]);
                    __nv_bfloat162 p = __floats2bfloat162_rn(__fdiv_rn(a, 1.0f + __expf(-a)), __fdiv_rn(b, 1.0f + __expf(-b)));
                    ow[k] = *(uint32_t*)&p;
                }
                const int b = i / 80, c8 = i - b * 80;
                *(uint4*)(smem + SM_A + b * A_PITCH + c8 * 16) = make_uint4(ow[0], ow[1], ow[2], ow[3]);
            }
        }
#pragma unroll
        for (int i = 0; i < 5; ++i) {
            nv[2 * i] = bf_lo(xw[i]);
            nv[2 * i + 1] = bf_hi(xw[i]);
            *(float2*)(s_xp + lrow * DM + lcol + 2 * i) = make_float2(nv[2 * i], nv[2 * i + 1]);
        }
    }
    float* acc_o = g_o[ep & 1];
    float* acc_attn = g_attn[ep & 1];
    if (cta == gridDim.x - 1) {
#pragma unroll 1
        for (int i = tid; i < NB * QN / 4; i += NCONS) ((float4*)g_o[~ep & 1])[i] = make_float4(0.f, 0.f, 0.f, 0.f);
#pragma unroll 1
        for (int i = tid; i < NB * DM; i += NCONS) g_attn[~ep & 1][i] = 0.f;
    }
    ln_norm(nv, s_red, tid);
    cp_async_wait1();
    cons_sync();
    if (PSTART == 0 && tid == 0) mbar_arrive(bar_go);
    if (cta < MODN / 32) {
        gemv_mma<5, 2>(sbase + SM_W32 + warp * 80 * P32, P32, sbase + SM_A + warp * 160, A_PITCH, s_part + warp * 320, lane);
        cons_sync();
        if (tid < 64) {
            const int b = tid >> 4, n = (tid & 15) * 2;
            ll_store(g_mod + (b * MODN + cta * 32 + n) / 2, tall_sum(s_part, b, n), tall_sum(s_part, b, n + 1), ep);
        }
    }
    PROF(1);

    if (cta < QN / 48) {
        cons_sync();
        {
            long long t0 = 0;
            for (;;) {
                bool ok = true;
#pragma unroll
                for (int r = 0; r < 5; ++r) {
                    const int i = tid + r * NCONS, b = i / 320, c4 = i - b * 320;
                    const uint4 v = ll_ld2(g_mod + b * (MODN / 2) + 2 * c4);
                    *(uint2*)(s_part + b * DM + 2 * c4) = make_uint2(v.x, v.z);
                    ok = ok && v.y == ep && v.w == ep;
                }
                if (ok) break;
                if (t0 == 0) t0 = clock64();
                else if (clock64() - t0 > WAIT_LIMIT_CYCLES) __trap();
            }
        }
        cons_sync();
        PROF(2);
        uint32_t sh[5], sc[5];
#pragma unroll
        for (int i = 0; i < 5; ++i) {
            sh[i] = ((const uint32_t*)s_part)[lrow * DM + lcol / 2 + i];
            sc[i] = ((const uint32_t*)s_part)[lrow * DM + DM / 2 + lcol / 2 + i];
        }
        modulate(nv, sh, sc, h_dst);
        cp_async_wait_all();
        cons_sync();
        if (PSTART == 2 && tid == 0) mbar_arrive(bar_go);
        gemv_mma<5, 3>(sbase + SM_WQ + warp * 80 * P48, P48, sbase + SM_A + warp * 160, A_PITCH, s_part + warp * 320, lane);
        cons_sync();
        if (tid < 96) {
            const int b = tid / 24, n = (tid - b * 24) * 2;
            ll_store(g_q + (b * QN + cta * 48 + n) / 2, tall_sum(s_part, b, n), tall_sum(s_part, b, n + 1), ep);
        }
    } else if (PSTART == 2 && tid == 0) {
        mbar_arrive(bar_go);
    }
    PROF(3);
    if (tid == 0) {
#pragma unroll 1
        for (int s = PRE; s < NST; ++s) mbar_arrive(bar_empty + s * 8);
    }
    uint32_t m_ga[5], m_sb[5], m_cb[5], m_fa[1] = {0u}, m_fb[1] = {0u};
    const int fcta = cta - ((int)gridDim.x - DM / 32);
    if (cta < FF / 16) {
        if (warp == 7) {
            stage_rows(sbase + SM_W32, P32, w_gate + cta * 16, FF * 2, DM, 2, lane, 32);
            stage_rows(sbase + SM_W32 + 32, P32, w_up + cta * 16, FF * 2, DM, 2, lane, 32);
        }
    }
    PROF(4);

    {
        const int sub = lane & 7, grp = lane >> 3;
        for (int u0 = warp * TPI;; u0 += 8 * TPI) {
            if (u0 == (8 + 6) * TPI) {
                if (cta < QN / 48) {
#pragma unroll 1
                    for (int i = lane; i < 48 * DM * 2 / 128; i += 32) {
                        unsigned int v;
                        asm volatile("ld.global.L2::128B.u32 %0, [%1];" : "=r"(v) : "l"((const unsigned char*)(wo + (size_t)cta * 48 * DM) + i * 128));
                    }
                }
                if (cta < FF / 16) {
#pragma unroll 1
                    for (int i = lane; i < 16 * DM * 2 / 128; i += 32) {
                        unsigned int v;
                        asm volatile("ld.global.L2::128B.u32 %0, [%1];" : "=r"(v) : "l"((const unsigned char*)(w_down + (size_t)cta * 16 * DM) + i * 128));
                    }
                }
            }
            if (s_tag[u0 % NST] != u0) tag_wait_slow(s_tag + u0 % NST, u0);
            const int item = s_item[u0 % NST];
            if ((u0 >= 8 * TPI && u0 < 16 * TPI) || (item < 0 && u0 < 8 * TPI)) {
                if (cta < FF / 16) {
                    ll_get(mod_row + DM, m_ga, ep);
                    ll_get(mod_row + 3 * DM / 2, m_sb, ep);
                    ll_get(mod_row + 2 * DM, m_cb, ep);
                }
                if (tid < 64 && fcta >= 0) {
                    ll_get(g_mod + ((tid >> 4) * MODN + 2 * DM + fcta * 32) / 2 + (tid & 15), m_fa, ep);
                    ll_get(g_mod + ((tid >> 4) * MODN + 5 * DM + fcta * 32) / 2 + (tid & 15), m_fb, ep);
                }
            }
            if (item < 0) {
                mbar_wait(bar_full + (u0 % NST) * 8, (u0 / NST) & 1);
                __syncwarp();
                if (lane == 0) mbar_arrive(bar_empty + (u0 % NST) * 8);
                break;
            }
            const int bh = (item & (NITEM_K - 1)) / CHUNKS;
            if (item < NITEM_K) {
                unsigned int* gs = g_s + (size_t)item * ITEM_KEYS;
                float qr[24];
                {
                    const unsigned long long* qp = g_q + ((bh >> 5) * QN + (bh & 31) * DH) / 2 + sub * 4;
                    long long t0 = 0;
                    for (;;) {
                        bool ok = true;
#pragma unroll
                        for (int j = 0; j < 6; ++j) {
                            const uint4 v = ll_ld2(qp + (j >> 1) * 32 + (j & 1) * 2);
                            qr[j * 4 + 0] = bf_lo(v.x); qr[j * 4 + 1] = bf_hi(v.x);
                            qr[j * 4 + 2] = bf_lo(v.z); qr[j * 4 + 3] = bf_hi(v.z);
                            ok = ok && v.y == ep && v.w == ep;
                        }
                        if (ok) break;
                        if (t0 == 0) t0 = clock64();
                        else if (clock64() - t0 > WAIT_LIMIT_CYCLES) __trap();
                    }
                }
                float m_run = -INFINITY, l_run = 0.f;
#pragma unroll 1
                for (int hh = 0; hh < 2 * TPI; ++hh) {
                    const int u = u0 + (hh >> 1), st = u % NST;
                    if (!(hh & 1)) stage_wait(bar_full, s_tag, u);
                    const uint4* tile = (const uint4*)(smem + SM_RING + st * STAGE_BYTES) + (hh & 1) * (32 * 24);
                    float part[8];
#pragma unroll
                    for (int it = 0; it < 8; ++it) {
                        const uint4* row = tile + (it * 4 + grp) * 24 + sub;
                        const uint4 a = row[0], b = row[8], c = row[16];
                        part[it] = dot8(a, qr) + dot8(b, qr + 8) + dot8(c, qr + 16);
                    }
                    if (hh & 1) {
                        __syncwarp();
                        if (lane == 0) mbar_arrive(bar_empty + st * 8);
                    }
#pragma unroll
                    for (int j = 0; j < 4; ++j) {
                        const float send = (sub & 4) ? part[j] : part[j + 4];
                        const float keep = (sub & 4) ? part[j + 4] : part[j];
                        part[j] = keep + __shfl_xor_sync(0xffffffffu, send, 4);
                    }
#pragma unroll
                    for (int j = 0; j < 2; ++j) {
                        const float send = (sub & 2) ? part[j] : part[j + 2];
                        const float keep = (sub & 2) ? part[j + 2] : part[j];
                        part[j] = keep + __shfl_xor_sync(0xffffffffu, send, 2);
                    }
                    {
                        const float send = (sub & 1) ? part[0] : part[1];
                        const float keep = (sub & 1) ? part[1] : part[0];
                        part[0] = keep + __shfl_xor_sync(0xffffffffu, send, 1);
                    }
                    const float s = bf16r(bf16r(part[0]) * 0.07216878364870323f);
                    asm volatile("st.relaxed.gpu.global.u32 [%0], %1;" ::"l"(gs + hh * 32 + sub * 4 + grp), "r"(__float_as_uint(s) | tag16) : "memory");
                    const float m_new = fmaxf(m_run, s);
                    l_run = l_run * __expf(m_run - m_new) + __expf(s - m_new);
                    m_run = m_new;
                }
                const float m = warp_max(m_run);
                const float l = warp_sum(l_run * __expf(m_run - m));
                if (lane == 0)
                    asm volatile("st.relaxed.gpu.global.u64 [%0], %1;" ::"l"(g_stat + item),
                                 "l"(((unsigned long long)__float_as_uint(l) << 32) | (__float_as_uint(m) | tag16)) : "memory");
            } else {
                float pr[2 * TPI];
                {
                    const unsigned int* gs = g_s + (size_t)(item - NITEM_K) * ITEM_KEYS + lane;
                    uint2 st2;
                    long long t0 = 0;
                    for (;;) {
                        st2 = ll_ld1(g_stat + bh * CHUNKS + lane);
                        bool ok = (st2.x & 0xffffu) == tag16;
#pragma unroll
                        for (int hh = 0; hh < 2 * TPI; ++hh) {
                            unsigned int w;
                            asm volatile("ld.relaxed.gpu.global.u32 %0, [%1];" : "=r"(w) : "l"(gs + hh * 32) : "memory");
                            ok = ok && (w & 0xffffu) == tag16;
                            pr[hh] = bf_hi(w);
                        }
                        if (__all_sync(0xffffffffu, ok)) break;
                        if (t0 == 0) t0 = clock64();
                        else if (clock64() - t0 > WAIT_LIMIT_CYCLES) __trap();
                    }
                    const float mi = bf_hi(st2.x);
                    const float mm = warp_max(mi);
                    const float ll = warp_sum(__uint_as_float(st2.y) * __expf(mi - mm));
#pragma unroll
                    for (int hh = 0; hh < 2 * TPI; ++hh) pr[hh] = bf16r(__fdiv_rn(__expf(pr[hh] - mm), ll));
                }
                float acc[3][8];
#pragma unroll
                for (int j = 0; j < 3; ++j)
#pragma unroll
                    for (int e = 0; e < 8; ++e) acc[j][e] = 0.f;
#pragma unroll
                for (int hh = 0; hh < 2 * TPI; ++hh) {
                    const int u = u0 + (hh >> 1), st = u % NST;
                    if (!(hh & 1)) stage_wait(bar_full, s_tag, u);
                    const uint4* tile = (const uint4*)(smem + SM_RING + st * STAGE_BYTES) + (hh & 1) * (32 * 24);
#pragma unroll
                    for (int it = 0; it < 8; ++it) {
                        const uint4* row = tile + (it * 4 + grp) * 24 + sub;
                        const uint4 a = row[0], b = row[8], c = row[16];
                        const float p = __shfl_sync(0xffffffffu, pr[hh], it * 4 + grp);
                        fma8(acc[0], a, p);
                        fma8(acc[1], b, p);
                        fma8(acc[2], c, p);
                    }
                    if (hh & 1) {
                        __syncwarp();
                        if (lane == 0) mbar_arrive(bar_empty + st * 8);
                    }
                }
                float* go = acc_o + (bh >> 5) * QN + (bh & 31) * DH + sub * 8;
#pragma unroll
                for (int j = 0; j < 3; ++j) {
#pragma unroll
                    for (int e = 0; e < 8; ++e) {
                        float v = acc[j][e];
                        v += __shfl_xor_sync(0xffffffffu, v, 8);
                        v += __shfl_xor_sync(0xffffffffu, v, 16);
                        acc[j][e] = v;
                    }
                    if (grp == 0) {
                        red_add_v4(go + j * 64, acc[j][0], acc[j][1], acc[j][2], acc[j][3]);
                        red_add_v4(go + j * 64 + 4, acc[j][4], acc[j][5], acc[j][6], acc[j][7]);
                    }
                }
            }
        }
    }
    PROF(5);
    grid_arrive(&g_bar[2], tid);
    PROF(6);
    const int ks = cta >> 3, ns = cta & 7;
    if (cta < 128 && tid < 240) {
        const int r0 = tid / 10, c = tid - r0 * 10;
        const unsigned char* src = (const unsigned char*)(wo + ((size_t)ks * WO_ROWS + r0) * DM + ns * 80) + c * 16;
        const uint32_t dst = sbase + SM_WO + r0 * P80 + c * 16;
#pragma unroll
        for (int i = 0; i < WO_ROWS / 24; ++i) cp_async16(dst + i * 24 * P80, src + (size_t)i * 24 * DM * 2);
    }
    grid_wait(&g_bar[2], target, tid);
    if (cta == 0 && tid == 0) { g_work = 0u; g_epoch = ep; }
    PROF(7);

    if (cta < 128) {
#pragma unroll
        for (int r = 0; r < 2; ++r) {
            const int i = tid + r * NCONS;
            if (i < NB * WO_ROWS / 4) {
                const int b = i / 96, c4 = i - b * 96;
                const float4 v = __ldcg((const float4*)(acc_o + b * QN + ks * WO_ROWS) + c4);
                __nv_bfloat162 p0 = __floats2bfloat162_rn(v.x, v.y), p1 = __floats2bfloat162_rn(v.z, v.w);
                uint2 w2;
                w2.x = *(uint32_t*)&p0; w2.y = *(uint32_t*)&p1;
                *(uint2*)(smem + SM_A + b * A_PITCH + c4 * 8) = w2;
            }
        }
        cp_async_wait_all();
        cons_sync();
        gemv_mma<3, 5>(sbase + SM_WO + warp * 48 * P80, P80, sbase + SM_A + warp * 96, A_PITCH, s_part + warp * 320, lane);
        cons_sync();
        if (tid < 80) {
            const int b = tid / 20, n4 = tid - b * 20;
            float4 s4 = make_float4(0.f, 0.f, 0.f, 0.f);
#pragma unroll
            for (int w = 0; w < 8; ++w) {
                const float4 v = *(const float4*)(s_part + (w * 4 + b) * 80 + n4 * 4);
                s4.x += v.x; s4.y += v.y; s4.z += v.z; s4.w += v.w;
            }
            red_add_v4(acc_attn + b * DM + ns * 80 + n4 * 4, s4.x, s4.y, s4.z, s4.w);
        }
    }
    PROF(8);
    grid_arrive(&g_bar[3], tid);
    const bool has_e = cta < FF / 16;
    if (!has_e && fcta < 0) return;
    if (fcta >= 0) {
        const unsigned char* src = (const unsigned char*)(w_down + (size_t)(tid >> 2) * DM + fcta * 32) + (tid & 3) * 16;
        const uint32_t dst = sbase + SM_WD + (tid >> 2) * P32 + (tid & 3) * 16;
#pragma unroll
        for (int i = 0; i < FF / 64; ++i) cp_async16(dst + i * 64 * P32, src + (size_t)i * 64 * DM * 2);
    }
    if (has_e) {
        uint32_t fe[5][2][4];
        frag_load<5, 2>(fe, sbase + SM_W32 + warp * 80 * P32, P32, lane);
        grid_wait(&g_bar[3], target, tid);
        PROF(9);
        {
            float4 v[3];
#pragma unroll
            for (int r = 0; r < 3; ++r)
                if (tid + r * NCONS < NB * DM / 4) v[r] = __ldcg((const float4*)acc_attn + tid + r * NCONS);
#pragma unroll
            for (int r = 0; r < 3; ++r)
                if (tid + r * NCONS < NB * DM / 4) ((float4*)s_part)[tid + r * NCONS] = v[r];
        }
        cons_sync();
#pragma unroll
        for (int i = 0; i < 5; ++i) {
            const float2 av = *((const float2*)(s_part + lrow * DM + lcol) + i);
            const float2 xv = *((const float2*)(s_xp + lrow * DM + lcol) + i);
            nv[2 * i] = bf16r(xv.x + bf16r(bf_lo(m_ga[i]) * bf16r(av.x)));
            nv[2 * i + 1] = bf16r(xv.y + bf16r(bf_hi(m_ga[i]) * bf16r(av.y)));
        }
        ln_norm(nv, s_red, tid);
        modulate(nv, m_sb, m_cb, h_dst);
        cons_sync();
        frag_mma<5, 2>(fe, sbase + SM_A + warp * 160, A_PITCH, s_part + warp * 320, lane);
        cons_sync();
        if (tid < 32) {
            const int b = tid >> 3, n = (tid & 7) * 2;
            const float g0 = bf16r(tall_sum(s_part, b, n)), g1 = bf16r(tall_sum(s_part, b, n + 1));
            const float u0 = bf16r(tall_sum(s_part, b, 16 + n)), u1 = bf16r(tall_sum(s_part, b, 17 + n));
            ll_store(g_act + (b * FF + cta * 16 + n) / 2, bf16r(gelu_tanh(g0)) * u0, bf16r(gelu_tanh(g1)) * u1, ep);
        }
        PROF(10);
        if (fcta < 0) return;
    } else {
        grid_wait(&g_bar[3], target, tid);
    }
    {
        float x10 = 0.f, x11 = 0.f;
        if (tid < 64) {
            const int b = tid >> 4, col = fcta * 32 + (tid & 15) * 2;
            const float2 av = __ldcg((const float2*)(acc_attn + b * DM + col));
            x10 = bf16r(s_xp[b * DM + col] + bf16r(bf_lo(m_fa[0]) * bf16r(av.x)));
            x11 = bf16r(s_xp[b * DM + col + 1] + bf16r(bf_hi(m_fa[0]) * bf16r(av.y)));
        }
        cp_async_wait_all();
        cons_sync();
        uint32_t ff[12][2][4];
        frag_load<12, 2>(ff, sbase + SM_WD + warp * 192 * P32, P32, lane);
        long long t0 = 0;
        for (;;) {
            bool ok = true;
#pragma unroll
            for (int r = 0; r < 6; ++r) {
                const int i = tid + r * NCONS, b = i / 384, c4 = i - b * 384;
                const uint4 v = ll_ld2(g_act + 2 * i);
                *(uint2*)(smem + SM_ACT + b * ACT_PITCH + c4 * 8) = make_uint2(v.x, v.z);
                ok = ok && v.y == ep && v.w == ep;
            }
            if (ok) break;
            if (t0 == 0) t0 = clock64();
            else if (clock64() - t0 > WAIT_LIMIT_CYCLES) __trap();
        }
        cons_sync();
        PROF(11);
        frag_mma<12, 2>(ff, sbase + SM_ACT + warp * 384, ACT_PITCH, s_part + warp * 320, lane);
        cons_sync();
        if (tid < 64) {
            const int b = tid >> 4, n = (tid & 15) * 2;
            const float f0 = bf16r(tall_sum(s_part, b, n)), f1 = bf16r(tall_sum(s_part, b, n + 1));
            *(__nv_bfloat162*)(out + b * DM + fcta * 32 + n) =
                __floats2bfloat162_rn(x10 + bf16r(bf_lo(m_fb[0]) * f0), x11 + bf16r(bf_hi(m_fb[0]) * f1));
        }
    }
    PROF(12);
}

}

extern "C" void kernel_launch(void* const* d_in, const int* in_sizes, int n_in, void* d_out, int out_size) {
    (void)in_sizes; (void)n_in; (void)out_size;
    const __nv_bfloat16* A_x = (const __nv_bfloat16*)d_in[0];
    const __nv_bfloat16* A_k = (const __nv_bfloat16*)d_in[1];
    const __nv_bfloat16* A_v = (const __nv_bfloat16*)d_in[2];
    const __nv_bfloat16* A_wq = (const __nv_bfloat16*)d_in[3];
    const __nv_bfloat16* A_wo = (const __nv_bfloat16*)d_in[4];
    const __nv_bfloat16* B_wg = (const __nv_bfloat16*)d_in[6];
    const __nv_bfloat16* B_wu = (const __nv_bfloat16*)d_in[7];
    const __nv_bfloat16* B_wd = (const __nv_bfloat16*)d_in[8];
    const __nv_bfloat16* c = (const __nv_bfloat16*)d_in[9];
    const __nv_bfloat16* w_mod = (const __nv_bfloat16*)d_in[10];
    static int grid = 0;
    if (grid == 0) {
        cudaFuncSetAttribute(decode_block_kernel, cudaFuncAttributeMaxDynamicSharedMemorySize, SM_TOTAL);
        int dev = 0, sms = 0;
        cudaGetDevice(&dev);
        cudaDeviceGetAttribute(&sms, cudaDevAttrMultiProcessorCount, dev);
        grid = sms < 132 ? sms : 132;
    }
    decode_block_kernel<<<grid, NTHREADS, SM_TOTAL>>>(A_x, A_k, A_v, A_wq, A_wo, B_wg, B_wu, B_wd, c, w_mod,
                                                      (__nv_bfloat16*)d_out);
}
```

```cpp
#include <cuda_runtime.h>
#include <cuda_bf16.h>
#include <stdint.h>

namespace {

constexpr int NB = 4;
constexpr int DM = 640;
constexpr int NH = 32;
constexpr int SK = 4096;
constexpr int DH = 192;
constexpr int FF = 1536;
constexpr int MODN = 6 * DM;
constexpr int QN = NH * DH;
constexpr int NBH = NB * NH;

constexpr int NCONS = 256;
constexpr int NTHREADS = NCONS + 32;
constexpr int TILE_KEYS = 64;
constexpr int TILE_BYTES = TILE_KEYS * DH * 2;
constexpr int STAGE_BYTES = TILE_BYTES;
constexpr int NST = 6;
constexpr int PRE = 3;
constexpr int TPI = 2;
constexpr int ITEM_KEYS = TPI * TILE_KEYS;
constexpr int CHUNKS = SK / ITEM_KEYS;
constexpr int NITEM_K = NBH * CHUNKS;
constexpr int NITEM = 2 * NITEM_K;

constexpr int A_PITCH = 1296;
constexpr int ACT_PITCH = FF * 2 + 16;
constexpr int P32 = 80;
constexpr int P48 = 112;
constexpr int P80 = 176;
constexpr int WO_ROWS = 384;

constexpr int SM_RING = 0;
constexpr int SM_WQ = PRE * STAGE_BYTES;
constexpr int SM_WO = 0;
constexpr int SM_WD = 0;
constexpr int SM_W32 = NST * STAGE_BYTES;
constexpr int SM_ACT = SM_W32;
constexpr int SM_A = SM_W32 + DM * P32;
constexpr int SM_PART = SM_A + NB * A_PITCH;
constexpr int SM_XP = SM_PART + 8 * 4 * 80 * 4;
constexpr int SM_RED = SM_XP + NB * DM * 4;
constexpr int SM_ITEM = SM_RED + 16 * 4;
constexpr int SM_TAG = SM_ITEM + 16 * 4;
constexpr int SM_BAR = SM_TAG + 16 * 4;
constexpr int SM_TOTAL = SM_BAR + (2 * NST + 1) * 8;
static_assert(SM_WQ + DM * P48 <= NST * STAGE_BYTES, "prologue overlay");
static_assert(SM_WD + FF * P32 <= NST * STAGE_BYTES && WO_ROWS * P80 <= NST * STAGE_BYTES, "tail overlay");
static_assert(SM_TOTAL <= 232448, "smem");
#define THR_ITEMS 6
#define THR_DEPTH 3
#define PSTART 0

__device__ __align__(128) unsigned long long g_mod[NB * MODN / 2];
__device__ __align__(128) unsigned long long g_q[NB * QN / 2];
__device__ __align__(128) unsigned long long g_act[NB * FF / 2];
__device__ __align__(128) unsigned int g_s[NBH * SK];
__device__ __align__(128) unsigned long long g_stat[NBH * CHUNKS];
__device__ __align__(128) float g_o[2][NB * QN];
__device__ __align__(128) float g_attn[2][NB * DM];
__device__ __align__(128) unsigned int g_bar[8];
__device__ unsigned int g_work;
__device__ unsigned int g_epoch;

#define PROF(k) do { } while (0)
#define PROFP(k) do { } while (0)

__device__ __forceinline__ float bf16r(float x) { return __bfloat162float(__float2bfloat16_rn(x)); }
__device__ __forceinline__ float bf_lo(uint32_t u) { return __uint_as_float(u << 16); }
__device__ __forceinline__ float bf_hi(uint32_t u) { return __uint_as_float(u & 0xffff0000u); }

__device__ __forceinline__ uint32_t smem_u32(const void* p) { return (uint32_t)__cvta_generic_to_shared(p); }
__device__ __forceinline__ void mbar_init(uint32_t bar, uint32_t count) {
    asm volatile("mbarrier.init.shared::cta.b64 [%0], %1;" ::"r"(bar), "r"(count) : "memory");
}
__device__ __forceinline__ void mbar_expect_tx(uint32_t bar, uint32_t bytes) {
    asm volatile("mbarrier.arrive.expect_tx.shared::cta.b64 _, [%0], %1;" ::"r"(bar), "r"(bytes) : "memory");
}
__device__ __forceinline__ void mbar_arrive(uint32_t bar) {
    asm volatile("mbarrier.arrive.shared::cta.b64 _, [%0];" ::"r"(bar) : "memory");
}
constexpr long long WAIT_LIMIT_CYCLES = 200000000LL;
__device__ __forceinline__ uint32_t mbar_try(uint32_t bar, uint32_t parity) {
    uint32_t done;
    asm volatile(
        "{\n\t.reg .pred p;\n\t"
        "mbarrier.try_wait.parity.shared::cta.b64 p, [%1], %2;\n\t"
        "selp.u32 %0, 1, 0, p;\n\t}"
        : "=r"(done) : "r"(bar), "r"(parity) : "memory");
    return done;
}
__device__ __noinline__ void mbar_wait_slow(uint32_t bar, uint32_t parity) {
    const long long t0 = clock64();
    while (!mbar_try(bar, parity)) {
        if (clock64() - t0 > WAIT_LIMIT_CYCLES) __trap();
    }
}
__device__ __forceinline__ void mbar_wait(uint32_t bar, uint32_t parity) {
    if (!mbar_try(bar, parity)) mbar_wait_slow(bar, parity);
}
__device__ __noinline__ void tag_wait_slow(volatile int* tag, int u) {
    const long long t0 = clock64();
    while (*tag != u) {
        __nanosleep(32);
        if (clock64() - t0 > WAIT_LIMIT_CYCLES) __trap();
    }
}
__device__ __forceinline__ void stage_wait(uint32_t bar_full, volatile int* s_tag, int u) {
    const int st = u % NST;
    if (s_tag[st] != u) tag_wait_slow(s_tag + st, u);
    mbar_wait(bar_full + st * 8, (u / NST) & 1);
}
__device__ __forceinline__ void bulk_g2s(uint32_t dst, const void* src, uint32_t bytes, uint32_t bar, uint64_t pol) {
    asm volatile(
        "cp.async.bulk.shared::cluster.global.mbarrier::complete_tx::bytes.L2::cache_hint [%0], [%1], %2, [%3], %4;"
        ::"r"(dst), "l"(src), "r"(bytes), "r"(bar), "l"(pol) : "memory");
}
__device__ __forceinline__ void cp_async16(uint32_t dst, const void* src) {
    asm volatile("cp.async.cg.shared.global [%0], [%1], 16;" ::"r"(dst), "l"(src) : "memory");
}
__device__ __forceinline__ void cp_async_wait_all() { asm volatile("cp.async.wait_all;" ::: "memory"); }
__device__ __forceinline__ void cp_async_commit() { asm volatile("cp.async.commit_group;" ::: "memory"); }
__device__ __forceinline__ void cp_async_wait1() { asm volatile("cp.async.wait_group 1;" ::: "memory"); }
__device__ __forceinline__ void red_release_add(unsigned int* p, unsigned int v) {
    asm volatile("red.release.gpu.global.add.u32 [%0], %1;" ::"l"(p), "r"(v) : "memory");
}
__device__ __forceinline__ void cons_sync() { asm volatile("bar.sync 1, 256;" ::: "memory"); }

__device__ __forceinline__ void red_add_v4(float* p, float a, float b, float c, float d) {
    asm volatile("red.global.add.v4.f32 [%0], {%1, %2, %3, %4};" ::"l"(p), "f"(a), "f"(b), "f"(c), "f"(d) : "memory");
}
__device__ __forceinline__ unsigned int ld_acquire(const unsigned int* p) {
    unsigned int v;
    asm volatile("ld.acquire.gpu.global.u32 %0, [%1];" : "=r"(v) : "l"(p) : "memory");
    return v;
}
__device__ __forceinline__ void ll_store(unsigned long long* p, float a, float b, unsigned int ep) {
    __nv_bfloat162 v = __floats2bfloat162_rn(a, b);
    const unsigned long long w = ((unsigned long long)ep << 32) | *(uint32_t*)&v;
    asm volatile("st.relaxed.gpu.global.u64 [%0], %1;" ::"l"(p), "l"(w) : "memory");
}
__device__ __forceinline__ uint2 ll_ld1(const unsigned long long* p) {
    unsigned long long w;
    asm volatile("ld.relaxed.gpu.global.u64 %0, [%1];" : "=l"(w) : "l"(p) : "memory");
    return make_uint2((uint32_t)w, (uint32_t)(w >> 32));
}
__device__ __forceinline__ uint4 ll_ld2(const unsigned long long* p) {
    unsigned long long a, b;
    asm volatile("ld.relaxed.gpu.global.v2.u64 {%0, %1}, [%2];" : "=l"(a), "=l"(b) : "l"(p) : "memory");
    return make_uint4((uint32_t)a, (uint32_t)(a >> 32), (uint32_t)b, (uint32_t)(b >> 32));
}
template <int N>
__device__ __forceinline__ void ll_get(const unsigned long long* p, uint32_t (&d)[N], unsigned int ep) {
    long long t0 = 0;
    for (;;) {
        bool ok = true;
#pragma unroll
        for (int i = 0; i < N; ++i) {
            const uint2 v = ll_ld1(p + i);
            d[i] = v.x;
            ok = ok && (v.y == ep);
        }
        if (ok) break;
        if (t0 == 0) t0 = clock64();
        else if (clock64() - t0 > WAIT_LIMIT_CYCLES) __trap();
    }
}

__device__ __forceinline__ void grid_arrive(unsigned int* ctr, int tid) {
    cons_sync();
    if (tid == 0) red_release_add(ctr, 1u);
}
__device__ __noinline__ void grid_wait(const unsigned int* ctr, unsigned int target, int tid) {
    if (tid == 0) {
        const long long t0 = clock64();
        while ((int)(ld_acquire(ctr) - target) < 0) {
            if (clock64() - t0 > WAIT_LIMIT_CYCLES) __trap();
        }
    }
    cons_sync();
}

__device__ __forceinline__ float warp_sum(float v) {
#pragma unroll
    for (int o = 16; o > 0; o >>= 1) v += __shfl_xor_sync(0xffffffffu, v, o);
    return v;
}
__device__ __forceinline__ float warp_max(float v) {
#pragma unroll
    for (int o = 16; o > 0; o >>= 1) v = fmaxf(v, __shfl_xor_sync(0xffffffffu, v, o));
    return v;
}

__device__ __forceinline__ void fma8(float (&acc)[8], const uint4& w, float s) {
    acc[0] = fmaf(s, bf_lo(w.x), acc[0]);
    acc[1] = fmaf(s, bf_hi(w.x), acc[1]);
    acc[2] = fmaf(s, bf_lo(w.y), acc[2]);
    acc[3] = fmaf(s, bf_hi(w.y), acc[3]);
    acc[4] = fmaf(s, bf_lo(w.z), acc[4]);
    acc[5] = fmaf(s, bf_hi(w.z), acc[5]);
    acc[6] = fmaf(s, bf_lo(w.w), acc[6]);
    acc[7] = fmaf(s, bf_hi(w.w), acc[7]);
}
__device__ __forceinline__ float dot8(const uint4& w, const float* q) {
    float s = q[0] * bf_lo(w.x);
    s = fmaf(q[1], bf_hi(w.x), s);
    s = fmaf(q[2], bf_lo(w.y), s);
    s = fmaf(q[3], bf_hi(w.y), s);
    s = fmaf(q[4], bf_lo(w.z), s);
    s = fmaf(q[5], bf_hi(w.z), s);
    s = fmaf(q[6], bf_lo(w.w), s);
    s = fmaf(q[7], bf_hi(w.w), s);
    return s;
}

__device__ __noinline__ void stage_rows(uint32_t dst, int dst_pitch, const void* src, int src_stride, int rows,
                                        int cpr, int tid, int nthr) {
    const int n = rows * cpr;
#pragma unroll 1
    for (int i = tid; i < n; i += nthr) {
        const int r = i / cpr, c = i - r * cpr;
        cp_async16(dst + r * dst_pitch + c * 16, (const unsigned char*)src + (size_t)r * src_stride + c * 16);
    }
}

template <int KS, int NT>
__device__ __noinline__ void gemv_mma(uint32_t w, int w_pitch, uint32_t a, int a_pitch, float* part, int lane) {
    float c[NT][4];
#pragma unroll
    for (int nt = 0; nt < NT; ++nt) { c[nt][0] = 0.f; c[nt][1] = 0.f; c[nt][2] = 0.f; c[nt][3] = 0.f; }
    const uint32_t ap = a + (lane >> 2) * a_pitch + (lane & 3) * 4;
    const uint32_t wp = w + ((lane & 7) + ((lane >> 4) << 3)) * w_pitch + ((lane >> 3) & 1) * 16;
#pragma unroll
    for (int ks = 0; ks < KS; ++ks) {
        uint32_t b0 = 0, b1 = 0;
        if (lane < 16) {
            asm("ld.shared.u32 %0, [%1];" : "=r"(b0) : "r"(ap + ks * 32));
            asm("ld.shared.u32 %0, [%1];" : "=r"(b1) : "r"(ap + ks * 32 + 16));
        }
#pragma unroll
        for (int nt = 0; nt < NT; ++nt) {
            uint32_t a0, a1, a2, a3;
            asm("ldmatrix.sync.aligned.m8n8.x4.trans.shared.b16 {%0, %1, %2, %3}, [%4];"
                         : "=r"(a0), "=r"(a1), "=r"(a2), "=r"(a3) : "r"(wp + ks * 16 * w_pitch + nt * 32));
            asm("mma.sync.aligned.m16n8k16.row.col.f32.bf16.bf16.f32 {%0, %1, %2, %3}, {%4, %5, %6, %7}, "
                "{%8, %9}, {%0, %1, %2, %3};"
                : "+f"(c[nt][0]), "+f"(c[nt][1]), "+f"(c[nt][2]), "+f"(c[nt][3])
                : "r"(a0), "r"(a1), "r"(a2), "r"(a3), "r"(b0), "r"(b1));
        }
    }
    if ((lane & 3) < 2) {
        float* pp = part + (lane & 3) * 160 + (lane >> 2);
#pragma unroll
        for (int nt = 0; nt < NT; ++nt) {
            pp[nt * 16] = c[nt][0];
            pp[nt * 16 + 80] = c[nt][1];
            pp[nt * 16 + 8] = c[nt][2];
            pp[nt * 16 + 88] = c[nt][3];
        }
    }
}

template <int KS, int NT>
__device__ __forceinline__ void frag_load(uint32_t (&f)[KS][NT][4], uint32_t w, int w_pitch, int lane) {
    const uint32_t wp = w + ((lane & 7) + ((lane >> 4) << 3)) * w_pitch + ((lane >> 3) & 1) * 16;
#pragma unroll
    for (int ks = 0; ks < KS; ++ks)
#pragma unroll
        for (int nt = 0; nt < NT; ++nt)
            asm volatile("ldmatrix.sync.aligned.m8n8.x4.trans.shared.b16 {%0, %1, %2, %3}, [%4];"
                         : "=r"(f[ks][nt][0]), "=r"(f[ks][nt][1]), "=r"(f[ks][nt][2]), "=r"(f[ks][nt][3])
                         : "r"(wp + ks * 16 * w_pitch + nt * 32) : "memory");
}
template <int KS, int NT>
__device__ __forceinline__ void frag_mma(const uint32_t (&f)[KS][NT][4], uint32_t a, int a_pitch, float* part, int lane) {
    float c[NT][4];
#pragma unroll
    for (int nt = 0; nt < NT; ++nt) { c[nt][0] = 0.f; c[nt][1] = 0.f; c[nt][2] = 0.f; c[nt][3] = 0.f; }
    const uint32_t ap = a + (lane >> 2) * a_pitch + (lane & 3) * 4;
    uint32_t b[KS][2];
#pragma unroll
    for (int ks = 0; ks < KS; ++ks) {
        b[ks][0] = 0; b[ks][1] = 0;
        if (lane < 16) {
            asm volatile("ld.shared.u32 %0, [%1];" : "=r"(b[ks][0]) : "r"(ap + ks * 32) : "memory");
            asm volatile("ld.shared.u32 %0, [%1];" : "=r"(b[ks][1]) : "r"(ap + ks * 32 + 16) : "memory");
        }
    }
#pragma unroll
    for (int ks = 0; ks < KS; ++ks)
#pragma unroll
        for (int nt = 0; nt < NT; ++nt)
            asm("mma.sync.aligned.m16n8k16.row.col.f32.bf16.bf16.f32 {%0, %1, %2, %3}, {%4, %5, %6, %7}, "
                "{%8, %9}, {%0, %1, %2, %3};"
                : "+f"(c[nt][0]), "+f"(c[nt][1]), "+f"(c[nt][2]), "+f"(c[nt][3])
                : "r"(f[ks][nt][0]), "r"(f[ks][nt][1]), "r"(f[ks][nt][2]), "r"(f[ks][nt][3]), "r"(b[ks][0]), "r"(b[ks][1]));
    if ((lane & 3) < 2) {
        float* pp = part + (lane & 3) * 160 + (lane >> 2);
#pragma unroll
        for (int nt = 0; nt < NT; ++nt) {
            pp[nt * 16] = c[nt][0];
            pp[nt * 16 + 80] = c[nt][1];
            pp[nt * 16 + 8] = c[nt][2];
            pp[nt * 16 + 88] = c[nt][3];
        }
    }
}

__device__ __forceinline__ float tall_sum(const float* part, int b, int n) {
    float s = 0.f;
#pragma unroll
    for (int w = 0; w < 8; ++w) s += part[(w * 4 + b) * 80 + n];
    return s;
}

__device__ __forceinline__ void ln_norm(float (&v)[10], float* s_red, int tid) {
    const int warp = tid >> 5;
    const float pv = __shfl_sync(0xffffffffu, v[0], 0);
    float s = 0.f, q = 0.f;
#pragma unroll
    for (int i = 0; i < 10; ++i) { const float d = v[i] - pv; s += d; q = fmaf(d, d, q); }
#pragma unroll
    for (int o = 16; o > 0; o >>= 1) {
        s += __shfl_xor_sync(0xffffffffu, s, o);
        q += __shfl_xor_sync(0xffffffffu, q, o);
    }
    const float md = s * (2.0f / DM);
    if ((tid & 31) == 0) *(float2*)(s_red + 2 * warp) = make_float2(pv + md, fmaxf(q - s * md, 0.f));
    cons_sync();
    const float4 r = *(const float4*)(s_red + 4 * (warp >> 1));
    const float dm = r.x - r.z;
    const float var = (r.y + r.w + dm * dm * (DM / 4)) * (1.0f / DM);
    const float mean = bf16r(0.5f * (r.x + r.z));
    const float inv = __fdiv_rn(1.0f, bf16r(sqrtf(bf16r(bf16r(var) + 1e-5f))));
#pragma unroll
    for (int i = 0; i < 10; ++i) v[i] = bf16r(bf16r(v[i] - mean) * inv);
}
__device__ __forceinline__ void modulate(const float (&n)[10], const uint32_t (&sh)[5], const uint32_t (&sc)[5], uint32_t* dst) {
#pragma unroll
    for (int i = 0; i < 5; ++i) {
        const float h0 = bf16r(n[2 * i] * bf16r(1.0f + bf_lo(sc[i]))) + bf_lo(sh[i]);
        const float h1 = bf16r(n[2 * i + 1] * bf16r(1.0f + bf_hi(sc[i]))) + bf_hi(sh[i]);
        __nv_bfloat162 p = __floats2bfloat162_rn(h0, h1);
        dst[i] = *(uint32_t*)&p;
    }
}

__device__ __forceinline__ float gelu_tanh(float x) {
    const float kBeta = 0.7978845608028654f;
    const float inner = kBeta * (x + 0.044715f * x * x * x);
    return 0.5f * x * (1.0f + tanhf(inner));
}

__global__ void __launch_bounds__(NTHREADS, 1)
decode_block_kernel(const __nv_bfloat16* __restrict__ x_in, const __nv_bfloat16* __restrict__ k_cache,
                    const __nv_bfloat16* __restrict__ v_cache, const __nv_bfloat16* __restrict__ wq,
                    const __nv_bfloat16* __restrict__ wo, const __nv_bfloat16* __restrict__ w_gate,
                    const __nv_bfloat16* __restrict__ w_up, const __nv_bfloat16* __restrict__ w_down,
                    const __nv_bfloat16* __restrict__ cvec, const __nv_bfloat16* __restrict__ w_mod,
                    __nv_bfloat16* __restrict__ out) {
    extern __shared__ __align__(128) unsigned char smem[];
    const int tid = threadIdx.x;
    const int cta = blockIdx.x;

    const uint32_t sbase = smem_u32(smem);
    const uint32_t bar_full = sbase + SM_BAR;
    const uint32_t bar_empty = bar_full + NST * 8;
    volatile int* s_item = (volatile int*)(smem + SM_ITEM);
    volatile int* s_tag = (volatile int*)(smem + SM_TAG);

    const uint32_t bar_go = bar_empty + NST * 8;
    if (tid < NST) s_tag[tid] = -1;
    if (tid == 0) {
#pragma unroll 1
        for (int s = 0; s < 2 * NST + 1; ++s) mbar_init(bar_full + s * 8, 1);
        asm volatile("fence.mbarrier_init.release.cluster;" ::: "memory");
        asm volatile("fence.proxy.async.shared::cta;" ::: "memory");
#pragma unroll 1
        for (int s = 0; s < PRE; ++s) mbar_arrive(bar_empty + s * 8);
    }
    __syncthreads();

    if (tid >= NCONS) {
        if (tid == NCONS) {
            int u = 0;
            const int G = (int)gridDim.x;
            uint64_t pol;
            asm volatile("createpolicy.fractional.L2::evict_first.b64 %0, 1.0;" : "=l"(pol));
            auto produce = [&](const int item) {
                const int it = item & (NITEM_K - 1);
                const bool is_v = item >= NITEM_K;
                const unsigned char* src = (const unsigned char*)(is_v ? v_cache : k_cache) + (size_t)it * (ITEM_KEYS * DH * 2);
#pragma unroll 1
                for (int t = 0; t < TPI; ++t, ++u) {
                    const int st = u % NST;
                    const uint32_t fb = bar_full + st * 8;
                    mbar_wait(bar_empty + st * 8, (u / NST) & 1);
                    if (item >= NITEM - THR_ITEMS * G) mbar_wait(bar_empty + ((u - THR_DEPTH) % NST) * 8, ((u - THR_DEPTH) / NST + 1) & 1);
                    s_item[st] = item;
                    s_tag[st] = u;
                    mbar_expect_tx(fb, TILE_BYTES);
                    bulk_g2s(sbase + SM_RING + st * STAGE_BYTES, src + t * TILE_BYTES, TILE_BYTES, fb, pol);
                }
            };
            if (PSTART != 3) mbar_wait(bar_go, 0);
            int item = cta;
#pragma unroll 1
            while (item < NITEM) {
                const int next = (int)atomicAdd(&g_work, 1u) + G;
                produce(item);
                item = next;
            }
#pragma unroll 1
            for (int j = 0; j < 8; ++j, u += TPI) {
                const int st = u % NST;
                mbar_wait(bar_empty + st * 8, (u / NST) & 1);
                s_item[st] = -1;
                s_tag[st] = u;
                mbar_arrive(bar_full + st * 8);
            }
            PROFP(13);
        }
        return;
    }

    const int lane = tid & 31, warp = tid >> 5;
    float* s_part = (float*)(smem + SM_PART);
    float* s_xp = (float*)(smem + SM_XP);
    float* s_red = (float*)(smem + SM_RED);
    const int lrow = tid >> 6, lcol = (tid & 63) * 10;
    uint32_t* h_dst = (uint32_t*)(smem + SM_A + lrow * A_PITCH + lcol * 2);

    PROF(0);
    const unsigned int ep = ld_acquire(&g_epoch) + 1u;
    const unsigned int target = ep * gridDim.x, tag16 = ep & 0xffffu;
    const unsigned long long* mod_row = g_mod + (lrow * MODN + lcol) / 2;
    float nv[10];
    {
        const int i1 = tid + NCONS;
        const uint4 c0 = __ldg((const uint4*)cvec + tid);
        uint4 c1 = c0;
        if (i1 < 320) c1 = __ldg((const uint4*)cvec + i1);
        uint32_t xw[5];
#pragma unroll
        for (int i = 0; i < 5; ++i) xw[i] = __ldg((const uint32_t*)(x_in + lrow * DM + lcol) + i);
        if (cta < MODN / 32) stage_rows(sbase + SM_W32, P32, w_mod + cta * 32, MODN * 2, DM, 4, tid, NCONS);
        cp_async_commit();
        if (cta < QN / 48) stage_rows(sbase + SM_WQ, P48, wq + cta * 48, QN * 2, DM, 6, tid, NCONS);
        cp_async_commit();
        if (PSTART == 1 && tid == 0) mbar_arrive(bar_go);
#pragma unroll 1
        for (int r = 0; r < 2; ++r) {
            const int i = r ? i1 : tid;
            if (i < 320) {
                const uint4 cc = r ? c1 : c0;
                const uint32_t cw[4] = {cc.x, cc.y, cc.z, cc.w};
                uint32_t ow[4];
#pragma unroll
                for (int k = 0; k < 4; ++k) {
                    const float a = bf_lo(cw[k]), b = bf_hi(cw[k]);
                    __nv_bfloat162 p = __floats2bfloat162_rn(__fdiv_rn(a, 1.0f + __expf(-a)), __fdiv_rn(b, 1.0f + __expf(-b)));
                    ow[k] = *(uint32_t*)&p;
                }
                const int b = i / 80, c8 = i - b * 80;
                *(uint4*)(smem + SM_A + b * A_PITCH + c8 * 16) = make_uint4(ow[0], ow[1], ow[2], ow[3]);
            }
        }
#pragma unroll
        for (int i = 0; i < 5; ++i) {
            nv[2 * i] = bf_lo(xw[i]);
            nv[2 * i + 1] = bf_hi(xw[i]);
            *(float2*)(s_xp + lrow * DM + lcol + 2 * i) = make_float2(nv[2 * i], nv[2 * i + 1]);
        }
    }
    float* acc_o = g_o[ep & 1];
    float* acc_attn = g_attn[ep & 1];
    if (cta == gridDim.x - 1) {
#pragma unroll 1
        for (int i = tid; i < NB * QN / 4; i += NCONS) ((float4*)g_o[~ep & 1])[i] = make_float4(0.f, 0.f, 0.f, 0.f);
#pragma unroll 1
        for (int i = tid; i < NB * DM; i += NCONS) g_attn[~ep & 1][i] = 0.f;
    }
    ln_norm(nv, s_red, tid);
    cp_async_wait1();
    cons_sync();
    if (PSTART == 0 && tid == 0) mbar_arrive(bar_go);
    if (cta < MODN / 32) {
        gemv_mma<5, 2>(sbase + SM_W32 + warp * 80 * P32, P32, sbase + SM_A + warp * 160, A_PITCH, s_part + warp * 320, lane);
        cons_sync();
        if (tid < 64) {
            const int b = tid >> 4, n = (tid & 15) * 2;
            ll_store(g_mod + (b * MODN + cta * 32 + n) / 2, tall_sum(s_part, b, n), tall_sum(s_part, b, n + 1), ep);
        }
    }
    PROF(1);

    if (cta < QN / 48) {
        cons_sync();
        {
            long long t0 = 0;
            for (;;) {
                bool ok = true;
#pragma unroll
                for (int r = 0; r < 5; ++r) {
                    const int i = tid + r * NCONS, b = i / 320, c4 = i - b * 320;
                    const uint4 v = ll_ld2(g_mod + b * (MODN / 2) + 2 * c4);
                    *(uint2*)(s_part + b * DM + 2 * c4) = make_uint2(v.x, v.z);
                    ok = ok && v.y == ep && v.w == ep;
                }
                if (ok) break;
                if (t0 == 0) t0 = clock64();
                else if (clock64() - t0 > WAIT_LIMIT_CYCLES) __trap();
            }
        }
        cons_sync();
        PROF(2);
        uint32_t sh[5], sc[5];
#pragma unroll
        for (int i = 0; i < 5; ++i) {
            sh[i] = ((const uint32_t*)s_part)[lrow * DM + lcol / 2 + i];
            sc[i] = ((const uint32_t*)s_part)[lrow * DM + DM / 2 + lcol / 2 + i];
        }
        modulate(nv, sh, sc, h_dst);
        cp_async_wait_all();
        cons_sync();
        if (PSTART == 2 && tid == 0) mbar_arrive(bar_go);
        gemv_mma<5, 3>(sbase + SM_WQ + warp * 80 * P48, P48, sbase + SM_A + warp * 160, A_PITCH, s_part + warp * 320, lane);
        cons_sync();
        if (tid < 96) {
            const int b = tid / 24, n = (tid - b * 24) * 2;
            ll_store(g_q + (b * QN + cta * 48 + n) / 2, tall_sum(s_part, b, n), tall_sum(s_part, b, n + 1), ep);
        }
    } else if (PSTART == 2 && tid == 0) {
        mbar_arrive(bar_go);
    }
    PROF(3);
    if (tid == 0) {
#pragma unroll 1
        for (int s = PRE; s < NST; ++s) mbar_arrive(bar_empty + s * 8);
    }
    uint32_t m_ga[5], m_sb[5], m_cb[5], m_fa[1] = {0u}, m_fb[1] = {0u};
    const int fcta = cta - ((int)gridDim.x - DM / 32);
    if (cta < FF / 16) {
        if (warp == 7) {
            stage_rows(sbase + SM_W32, P32, w_gate + cta * 16, FF * 2, DM, 2, lane, 32);
            stage_rows(sbase + SM_W32 + 32, P32, w_up + cta * 16, FF * 2, DM, 2, lane, 32);
        }
    }
    PROF(4);

    {
        const int sub = lane & 7, grp = lane >> 3;
        for (int u0 = warp * TPI;; u0 += 8 * TPI) {
            if (u0 == (8 + 6) * TPI) {
                if (cta < QN / 48) {
#pragma unroll 1
                    for (int i = lane; i < 48 * DM * 2 / 128; i += 32) {
                        unsigned int v;
                        asm volatile("ld.global.L2::128B.u32 %0, [%1];" : "=r"(v) : "l"((const unsigned char*)(wo + (size_t)cta * 48 * DM) + i * 128));
                    }
                }
                if (cta < FF / 16) {
#pragma unroll 1
                    for (int i = lane; i < 16 * DM * 2 / 128; i += 32) {
                        unsigned int v;
                        asm volatile("ld.global.L2::128B.u32 %0, [%1];" : "=r"(v) : "l"((const unsigned char*)(w_down + (size_t)cta * 16 * DM) + i * 128));
                    }
                }
            }
            if (s_tag[u0 % NST] != u0) tag_wait_slow(s_tag + u0 % NST, u0);
            const int item = s_item[u0 % NST];
            if ((u0 >= 8 * TPI && u0 < 16 * TPI) || (item < 0 && u0 < 8 * TPI)) {
                if (cta < FF / 16) {
                    ll_get(mod_row + DM, m_ga, ep);
                    ll_get(mod_row + 3 * DM / 2, m_sb, ep);
                    ll_get(mod_row + 2 * DM, m_cb, ep);
                }
                if (tid < 64 && fcta >= 0) {
                    ll_get(g_mod + ((tid >> 4) * MODN + 2 * DM + fcta * 32) / 2 + (tid & 15), m_fa, ep);
                    ll_get(g_mod + ((tid >> 4) * MODN + 5 * DM + fcta * 32) / 2 + (tid & 15), m_fb, ep);
                }
            }
            if (item < 0) {
                mbar_wait(bar_full + (u0 % NST) * 8, (u0 / NST) & 1);
                __syncwarp();
                if (lane == 0) mbar_arrive(bar_empty + (u0 % NST) * 8);
                break;
            }
            const int bh = (item & (NITEM_K - 1)) / CHUNKS;
            if (item < NITEM_K) {
                unsigned int* gs = g_s + (size_t)item * ITEM_KEYS;
                float qr[24];
                {
                    const unsigned long long* qp = g_q + ((bh >> 5) * QN + (bh & 31) * DH) / 2 + sub * 4;
                    long long t0 = 0;
                    for (;;) {
                        bool ok = true;
#pragma unroll
                        for (int j = 0; j < 6; ++j) {
                            const uint4 v = ll_ld2(qp + (j >> 1) * 32 + (j & 1) * 2);
                            qr[j * 4 + 0] = bf_lo(v.x); qr[j * 4 + 1] = bf_hi(v.x);
                            qr[j * 4 + 2] = bf_lo(v.z); qr[j * 4 + 3] = bf_hi(v.z);
                            ok = ok && v.y == ep && v.w == ep;
                        }
                        if (ok) break;
                        if (t0 == 0) t0 = clock64();
                        else if (clock64() - t0 > WAIT_LIMIT_CYCLES) __trap();
                    }
                }
                float m_run = -INFINITY, l_run = 0.f;
#pragma unroll 1
                for (int hh = 0; hh < 2 * TPI; ++hh) {
                    const int u = u0 + (hh >> 1), st = u % NST;
                    if (!(hh & 1)) stage_wait(bar_full, s_tag, u);
                    const uint4* tile = (const uint4*)(smem + SM_RING + st * STAGE_BYTES) + (hh & 1) * (32 * 24);
                    float part[8];
#pragma unroll
                    for (int it = 0; it < 8; ++it) {
                        const uint4* row = tile + (it * 4 + grp) * 24 + sub;
                        const uint4 a = row[0], b = row[8], c = row[16];
                        part[it] = dot8(a, qr) + dot8(b, qr + 8) + dot8(c, qr + 16);
                    }
                    if (hh & 1) {
                        __syncwarp();
                        if (lane == 0) mbar_arrive(bar_empty + st * 8);
                    }
#pragma unroll
                    for (int j = 0; j < 4; ++j) {
                        const float send = (sub & 4) ? part[j] : part[j + 4];
                        const float keep = (sub & 4) ? part[j + 4] : part[j];
                        part[j] = keep + __shfl_xor_sync(0xffffffffu, send, 4);
                    }
#pragma unroll
                    for (int j = 0; j < 2; ++j) {
                        const float send = (sub & 2) ? part[j] : part[j + 2];
                        const float keep = (sub & 2) ? part[j + 2] : part[j];
                        part[j] = keep + __shfl_xor_sync(0xffffffffu, send, 2);
                    }
                    {
                        const float send = (sub & 1) ? part[0] : part[1];
                        const float keep = (sub & 1) ? part[1] : part[0];
                        part[0] = keep + __shfl_xor_sync(0xffffffffu, send, 1);
                    }
                    const float s = bf16r(bf16r(part[0]) * 0.07216878364870323f);
                    asm volatile("st.relaxed.gpu.global.u32 [%0], %1;" ::"l"(gs + hh * 32 + sub * 4 + grp), "r"(__float_as_uint(s) | tag16) : "memory");
                    const float m_new = fmaxf(m_run, s);
                    l_run = l_run * __expf(m_run - m_new) + __expf(s - m_new);
                    m_run = m_new;
                }
                const float m = warp_max(m_run);
                const float l = warp_sum(l_run * __expf(m_run - m));
                if (lane == 0)
                    asm volatile("st.relaxed.gpu.global.u64 [%0], %1;" ::"l"(g_stat + item),
                                 "l"(((unsigned long long)__float_as_uint(l) << 32) | (__float_as_uint(m) | tag16)) : "memory");
            } else {
                float pr[2 * TPI];
                {
                    const unsigned int* gs = g_s + (size_t)(item - NITEM_K) * ITEM_KEYS + lane;
                    uint2 st2;
                    long long t0 = 0;
                    for (;;) {
                        st2 = ll_ld1(g_stat + bh * CHUNKS + lane);
                        bool ok = (st2.x & 0xffffu) == tag16;
#pragma unroll
                        for (int hh = 0; hh < 2 * TPI; ++hh) {
                            unsigned int w;
                            asm volatile("ld.relaxed.gpu.global.u32 %0, [%1];" : "=r"(w) : "l"(gs + hh * 32) : "memory");
                            ok = ok && (w & 0xffffu) == tag16;
                            pr[hh] = bf_hi(w);
                        }
                        if (__all_sync(0xffffffffu, ok)) break;
                        if (t0 == 0) t0 = clock64();
                        else if (clock64() - t0 > WAIT_LIMIT_CYCLES) __trap();
                    }
                    const float mi = bf_hi(st2.x);
                    const float mm = warp_max(mi);
                    const float ll = warp_sum(__uint_as_float(st2.y) * __expf(mi - mm));
#pragma unroll
                    for (int hh = 0; hh < 2 * TPI; ++hh) pr[hh] = bf16r(__fdiv_rn(__expf(pr[hh] - mm), ll));
                }
                float acc[3][8];
#pragma unroll
                for (int j = 0; j < 3; ++j)
#pragma unroll
                    for (int e = 0; e < 8; ++e) acc[j][e] = 0.f;
#pragma unroll
                for (int hh = 0; hh < 2 * TPI; ++hh) {
                    const int u = u0 + (hh >> 1), st = u % NST;
                    if (!(hh & 1)) stage_wait(bar_full, s_tag, u);
                    const uint4* tile = (const uint4*)(smem + SM_RING + st * STAGE_BYTES) + (hh & 1) * (32 * 24);
#pragma unroll
                    for (int it = 0; it < 8; ++it) {
                        const uint4* row = tile + (it * 4 + grp) * 24 + sub;
                        const uint4 a = row[0], b = row[8], c = row[16];
                        const float p = __shfl_sync(0xffffffffu, pr[hh], it * 4 + grp);
                        fma8(acc[0], a, p);
                        fma8(acc[1], b, p);
                        fma8(acc[2], c, p);
                    }
                    if (hh & 1) {
                        __syncwarp();
                        if (lane == 0) mbar_arrive(bar_empty + st * 8);
                    }
                }
                float* go = acc_o + (bh >> 5) * QN + (bh & 31) * DH + sub * 8;
#pragma unroll
                for (int j = 0; j < 3; ++j) {
#pragma unroll
                    for (int e = 0; e < 8; ++e) {
                        float v = acc[j][e];
                        v += __shfl_xor_sync(0xffffffffu, v, 8);
                        v += __shfl_xor_sync(0xffffffffu, v, 16);
                        acc[j][e] = v;
                    }
                    if (grp == 0) {
                        red_add_v4(go + j * 64, acc[j][0], acc[j][1], acc[j][2], acc[j][3]);
                        red_add_v4(go + j * 64 + 4, acc[j][4], acc[j][5], acc[j][6], acc[j][7]);
                    }
                }
            }
        }
    }
    PROF(5);
    grid_arrive(&g_bar[2], tid);
    PROF(6);
    const int ks = cta >> 3, ns = cta & 7;
    if (cta < 128 && tid < 240) {
        const int r0 = tid / 10, c = tid - r0 * 10;
        const unsigned char* src = (const unsigned char*)(wo + ((size_t)ks * WO_ROWS + r0) * DM + ns * 80) + c * 16;
        const uint32_t dst = sbase + SM_WO + r0 * P80 + c * 16;
#pragma unroll
        for (int i = 0; i < WO_ROWS / 24; ++i) cp_async16(dst + i * 24 * P80, src + (size_t)i * 24 * DM * 2);
    }
    uint32_t fd[3][5][4];
    cp_async_wait_all();
    cons_sync();
    frag_load<3, 5>(fd, sbase + SM_WO + warp * 48 * P80, P80, lane);
    grid_wait(&g_bar[2], target, tid);
    if (cta == 0 && tid == 0) { g_work = 0u; g_epoch = ep; }
    PROF(7);

    if (cta < 128) {
#pragma unroll
        for (int r = 0; r < 2; ++r) {
            const int i = tid + r * NCONS;
            if (i < NB * WO_ROWS / 4) {
                const int b = i / 96, c4 = i - b * 96;
                const float4 v = __ldcg((const float4*)(acc_o + b * QN + ks * WO_ROWS) + c4);
                __nv_bfloat162 p0 = __floats2bfloat162_rn(v.x, v.y), p1 = __floats2bfloat162_rn(v.z, v.w);
                uint2 w2;
                w2.x = *(uint32_t*)&p0; w2.y = *(uint32_t*)&p1;
                *(uint2*)(smem + SM_A + b * A_PITCH + c4 * 8) = w2;
            }
        }
        cons_sync();
        frag_mma<3, 5>(fd, sbase + SM_A + warp * 96, A_PITCH, s_part + warp * 320, lane);
        cons_sync();
        if (tid < 80) {
            const int b = tid / 20, n4 = tid - b * 20;
            float4 s4 = make_float4(0.f, 0.f, 0.f, 0.f);
#pragma unroll
            for (int w = 0; w < 8; ++w) {
                const float4 v = *(const float4*)(s_part + (w * 4 + b) * 80 + n4 * 4);
                s4.x += v.x; s4.y += v.y; s4.z += v.z; s4.w += v.w;
            }
            red_add_v4(acc_attn + b * DM + ns * 80 + n4 * 4, s4.x, s4.y, s4.z, s4.w);
        }
    }
    PROF(8);
    grid_arrive(&g_bar[3], tid);
    const bool has_e = cta < FF / 16;
    if (!has_e && fcta < 0) return;
    if (fcta >= 0) {
        const unsigned char* src = (const unsigned char*)(w_down + (size_t)(tid >> 2) * DM + fcta * 32) + (tid & 3) * 16;
        const uint32_t dst = sbase + SM_WD + (tid >> 2) * P32 + (tid & 3) * 16;
#pragma unroll
        for (int i = 0; i < FF / 64; ++i) cp_async16(dst + i * 64 * P32, src + (size_t)i * 64 * DM * 2);
    }
    if (has_e) {
        uint32_t fe[5][2][4];
        frag_load<5, 2>(fe, sbase + SM_W32 + warp * 80 * P32, P32, lane);
        grid_wait(&g_bar[3], target, tid);
        PROF(9);
        {
            float4 v[3];
#pragma unroll
            for (int r = 0; r < 3; ++r)
                if (tid + r * NCONS < NB * DM / 4) v[r] = __ldcg((const float4*)acc_attn + tid + r * NCONS);
#pragma unroll
            for (int r = 0; r < 3; ++r)
                if (tid + r * NCONS < NB * DM / 4) ((float4*)s_part)[tid + r * NCONS] = v[r];
        }
        cons_sync();
#pragma unroll
        for (int i = 0; i < 5; ++i) {
            const float2 av = *((const float2*)(s_part + lrow * DM + lcol) + i);
            const float2 xv = *((const float2*)(s_xp + lrow * DM + lcol) + i);
            nv[2 * i] = bf16r(xv.x + bf16r(bf_lo(m_ga[i]) * bf16r(av.x)));
            nv[2 * i + 1] = bf16r(xv.y + bf16r(bf_hi(m_ga[i]) * bf16r(av.y)));
        }
        ln_norm(nv, s_red, tid);
        modulate(nv, m_sb, m_cb, h_dst);
        cons_sync();
        frag_mma<5, 2>(fe, sbase + SM_A + warp * 160, A_PITCH, s_part + warp * 320, lane);
        cons_sync();
        if (tid < 32) {
            const int b = tid >> 3, n = (tid & 7) * 2;
            const float g0 = bf16r(tall_sum(s_part, b, n)), g1 = bf16r(tall_sum(s_part, b, n + 1));
            const float u0 = bf16r(tall_sum(s_part, b, 16 + n)), u1 = bf16r(tall_sum(s_part, b, 17 + n));
            ll_store(g_act + (b * FF + cta * 16 + n) / 2, bf16r(gelu_tanh(g0)) * u0, bf16r(gelu_tanh(g1)) * u1, ep);
        }
        PROF(10);
        if (fcta < 0) return;
    } else {
        grid_wait(&g_bar[3], target, tid);
    }
    {
        float x10 = 0.f, x11 = 0.f;
        if (tid < 64) {
            const int b = tid >> 4, col = fcta * 32 + (tid & 15) * 2;
            const float2 av = __ldcg((const float2*)(acc_attn + b * DM + col));
            x10 = bf16r(s_xp[b * DM + col] + bf16r(bf_lo(m_fa[0]) * bf16r(av.x)));
            x11 = bf16r(s_xp[b * DM + col + 1] + bf16r(bf_hi(m_fa[0]) * bf16r(av.y)));
        }
        cp_async_wait_all();
        cons_sync();
        uint32_t ff[12][2][4];
        frag_load<12, 2>(ff, sbase + SM_WD + warp * 192 * P32, P32, lane);
        long long t0 = 0;
        for (;;) {
            bool ok = true;
#pragma unroll
            for (int r = 0; r < 6; ++r) {
                const int i = tid + r * NCONS, b = i / 384, c4 = i - b * 384;
                const uint4 v = ll_ld2(g_act + 2 * i);
                *(uint2*)(smem + SM_ACT + b * ACT_PITCH + c4 * 8) = make_uint2(v.x, v.z);
                ok = ok && v.y == ep && v.w == ep;
            }
            if (ok) break;
            if (t0 == 0) t0 = clock64();
            else if (clock64() - t0 > WAIT_LIMIT_CYCLES) __trap();
        }
        cons_sync();
        PROF(11);
        frag_mma<12, 2>(ff, sbase + SM_ACT + warp * 384, ACT_PITCH, s_part + warp * 320, lane);
        cons_sync();
        if (tid < 64) {
            const int b = tid >> 4, n = (tid & 15) * 2;
            const float f0 = bf16r(tall_sum(s_part, b, n)), f1 = bf16r(tall_sum(s_part, b, n + 1));
            *(__nv_bfloat162*)(out + b * DM + fcta * 32 + n) =
                __floats2bfloat162_rn(x10 + bf16r(bf_lo(m_fb[0]) * f0), x11 + bf16r(bf_hi(m_fb[0]) * f1));
        }
    }
    PROF(12);
}

}

extern "C" void kernel_launch(void* const* d_in, const int* in_sizes, int n_in, void* d_out, int out_size) {
    (void)in_sizes; (void)n_in; (void)out_size;
    const __nv_bfloat16* A_x = (const __nv_bfloat16*)d_in[0];
    const __nv_bfloat16* A_k = (const __nv_bfloat16*)d_in[1];
    const __nv_bfloat16* A_v = (const __nv_bfloat16*)d_in[2];
    const __nv_bfloat16* A_wq = (const __nv_bfloat16*)d_in[3];
    const __nv_bfloat16* A_wo = (const __nv_bfloat16*)d_in[4];
    const __nv_bfloat16* B_wg = (const __nv_bfloat16*)d_in[6];
    const __nv_bfloat16* B_wu = (const __nv_bfloat16*)d_in[7];
    const __nv_bfloat16* B_wd = (const __nv_bfloat16*)d_in[8];
    const __nv_bfloat16* c = (const __nv_bfloat16*)d_in[9];
    const __nv_bfloat16* w_mod = (const __nv_bfloat16*)d_in[10];
    static int grid = 0;
    if (grid == 0) {
        cudaFuncSetAttribute(decode_block_kernel, cudaFuncAttributeMaxDynamicSharedMemorySize, SM_TOTAL);
        int dev = 0, sms = 0;
        cudaGetDevice(&dev);
        cudaDeviceGetAttribute(&sms, cudaDevAttrMultiProcessorCount, dev);
        grid = sms < 132 ? sms : 132;
    }
    decode_block_kernel<<<grid, NTHREADS, SM_TOTAL>>>(A_x, A_k, A_v, A_wq, A_wo, B_wg, B_wu, B_wd, c, w_mod,
                                                      (__nv_bfloat16*)d_out);
}
```

```cpp
#include <cuda_runtime.h>
#include <cuda_bf16.h>
#include <stdint.h>

namespace {

constexpr int NB = 4;
constexpr int DM = 640;
constexpr int NH = 32;
constexpr int SK = 4096;
constexpr int DH = 192;
constexpr int FF = 1536;
constexpr int MODN = 6 * DM;
constexpr int QN = NH * DH;
constexpr int NBH = NB * NH;

constexpr int NCONS = 256;
constexpr int NTHREADS = NCONS + 32;
constexpr int TILE_KEYS = 64;
constexpr int TILE_BYTES = TILE_KEYS * DH * 2;
constexpr int STAGE_BYTES = TILE_BYTES;
constexpr int NST = 6;
constexpr int PRE = 3;
constexpr int TPI = 2;
constexpr int ITEM_KEYS = TPI * TILE_KEYS;
constexpr int CHUNKS = SK / ITEM_KEYS;
constexpr int NITEM_K = NBH * CHUNKS;
constexpr int NITEM = 2 * NITEM_K;

constexpr int A_PITCH = 1296;
constexpr int ACT_PITCH = FF * 2 + 16;
constexpr int P32 = 80;
constexpr int P48 = 112;
constexpr int P80 = 176;
constexpr int WO_ROWS = 384;

constexpr int SM_RING = 0;
constexpr int SM_WQ = PRE * STAGE_BYTES;
constexpr int SM_WO = 0;
constexpr int SM_WD = 0;
constexpr int SM_W32 = NST * STAGE_BYTES;
constexpr int SM_ACT = SM_W32;
constexpr int SM_A = SM_W32 + DM * P32;
constexpr int SM_PART = SM_A + NB * A_PITCH;
constexpr int SM_XP = SM_PART + 8 * 4 * 80 * 4;
constexpr int SM_RED = SM_XP + NB * DM * 4;
constexpr int SM_ITEM = SM_RED + 16 * 4;
constexpr int SM_TAG = SM_ITEM + 16 * 4;
constexpr int SM_BAR = SM_TAG + 16 * 4;
constexpr int SM_TOTAL = SM_BAR + (2 * NST + 1) * 8;
static_assert(SM_WQ + DM * P48 <= NST * STAGE_BYTES, "prologue overlay");
static_assert(SM_WD + FF * P32 <= NST * STAGE_BYTES && WO_ROWS * P80 <= NST * STAGE_BYTES, "tail overlay");
static_assert(SM_TOTAL <= 232448, "smem");
#define THR_ITEMS 6
#define THR_DEPTH 3
#define HAND_EARLY 0
#define PSTART 0

__device__ __align__(128) unsigned long long g_mod[NB * MODN / 2];
__device__ __align__(128) unsigned long long g_q[NB * QN / 2];
__device__ __align__(128) unsigned long long g_act[NB * FF / 2];
__device__ __align__(128) unsigned int g_s[NBH * SK];
__device__ __align__(128) unsigned long long g_stat[NBH * CHUNKS];
__device__ __align__(128) float g_o[2][NB * QN];
__device__ __align__(128) float g_attn[2][NB * DM];
__device__ __align__(128) unsigned int g_bar[8];
__device__ unsigned int g_work;
__device__ unsigned int g_epoch;

#define PROF(k) do { } while (0)
#define PROFP(k) do { } while (0)

__device__ __forceinline__ float bf16r(float x) { return __bfloat162float(__float2bfloat16_rn(x)); }
__device__ __forceinline__ float bf_lo(uint32_t u) { return __uint_as_float(u << 16); }
__device__ __forceinline__ float bf_hi(uint32_t u) { return __uint_as_float(u & 0xffff0000u); }

__device__ __forceinline__ uint32_t smem_u32(const void* p) { return (uint32_t)__cvta_generic_to_shared(p); }
__device__ __forceinline__ void mbar_init(uint32_t bar, uint32_t count) {
    asm volatile("mbarrier.init.shared::cta.b64 [%0], %1;" ::"r"(bar), "r"(count) : "memory");
}
__device__ __forceinline__ void mbar_expect_tx(uint32_t bar, uint32_t bytes) {
    asm volatile("mbarrier.arrive.expect_tx.shared::cta.b64 _, [%0], %1;" ::"r"(bar), "r"(bytes) : "memory");
}
__device__ __forceinline__ void mbar_arrive(uint32_t bar) {
    asm volatile("mbarrier.arrive.shared::cta.b64 _, [%0];" ::"r"(bar) : "memory");
}
constexpr long long WAIT_LIMIT_CYCLES = 200000000LL;
__device__ __forceinline__ uint32_t mbar_try(uint32_t bar, uint32_t parity) {
    uint32_t done;
    asm volatile(
        "{\n\t.reg .pred p;\n\t"
        "mbarrier.try_wait.parity.shared::cta.b64 p, [%1], %2;\n\t"
        "selp.u32 %0, 1, 0, p;\n\t}"
        : "=r"(done) : "r"(bar), "r"(parity) : "memory");
    return done;
}
__device__ __noinline__ void mbar_wait_slow(uint32_t bar, uint32_t parity) {
    const long long t0 = clock64();
    while (!mbar_try(bar, parity)) {
        if (clock64() - t0 > WAIT_LIMIT_CYCLES) __trap();
    }
}
__device__ __forceinline__ void mbar_wait(uint32_t bar, uint32_t parity) {
    if (!mbar_try(bar, parity)) mbar_wait_slow(bar, parity);
}
__device__ __noinline__ void tag_wait_slow(volatile int* tag, int u) {
    const long long t0 = clock64();
    while (*tag != u) {
        __nanosleep(32);
        if (clock64() - t0 > WAIT_LIMIT_CYCLES) __trap();
    }
}
__device__ __forceinline__ void stage_wait(uint32_t bar_full, volatile int* s_tag, int u) {
    const int st = u % NST;
    if (s_tag[st] != u) tag_wait_slow(s_tag + st, u);
    mbar_wait(bar_full + st * 8, (u / NST) & 1);
}
__device__ __forceinline__ void bulk_g2s(uint32_t dst, const void* src, uint32_t bytes, uint32_t bar, uint64_t pol) {
    asm volatile(
        "cp.async.bulk.shared::cluster.global.mbarrier::complete_tx::bytes.L2::cache_hint [%0], [%1], %2, [%3], %4;"
        ::"r"(dst), "l"(src), "r"(bytes), "r"(bar), "l"(pol) : "memory");
}
__device__ __forceinline__ void cp_async16(uint32_t dst, const void* src) {
    asm volatile("cp.async.cg.shared.global [%0], [%1], 16;" ::"r"(dst), "l"(src) : "memory");
}
__device__ __forceinline__ void cp_async_wait_all() { asm volatile("cp.async.wait_all;" ::: "memory"); }
__device__ __forceinline__ void cp_async_commit() { asm volatile("cp.async.commit_group;" ::: "memory"); }
__device__ __forceinline__ void cp_async_wait1() { asm volatile("cp.async.wait_group 1;" ::: "memory"); }
__device__ __forceinline__ void red_release_add(unsigned int* p, unsigned int v) {
    asm volatile("red.release.gpu.global.add.u32 [%0], %1;" ::"l"(p), "r"(v) : "memory");
}
__device__ __forceinline__ void cons_sync() { asm volatile("bar.sync 1, 256;" ::: "memory"); }

__device__ __forceinline__ void red_add_v4(float* p, float a, float b, float c, float d) {
    asm volatile("red.global.add.v4.f32 [%0], {%1, %2, %3, %4};" ::"l"(p), "f"(a), "f"(b), "f"(c), "f"(d) : "memory");
}
__device__ __forceinline__ unsigned int ld_acquire(const unsigned int* p) {
    unsigned int v;
    asm volatile("ld.acquire.gpu.global.u32 %0, [%1];" : "=r"(v) : "l"(p) : "memory");
    return v;
}
__device__ __forceinline__ void ll_store(unsigned long long* p, float a, float b, unsigned int ep) {
    __nv_bfloat162 v = __floats2bfloat162_rn(a, b);
    const unsigned long long w = ((unsigned long long)ep << 32) | *(uint32_t*)&v;
    asm volatile("st.relaxed.gpu.global.u64 [%0], %1;" ::"l"(p), "l"(w) : "memory");
}
__device__ __forceinline__ uint2 ll_ld1(const unsigned long long* p) {
    unsigned long long w;
    asm volatile("ld.relaxed.gpu.global.u64 %0, [%1];" : "=l"(w) : "l"(p) : "memory");
    return make_uint2((uint32_t)w, (uint32_t)(w >> 32));
}
__device__ __forceinline__ uint4 ll_ld2(const unsigned long long* p) {
    unsigned long long a, b;
    asm volatile("ld.relaxed.gpu.global.v2.u64 {%0, %1}, [%2];" : "=l"(a), "=l"(b) : "l"(p) : "memory");
    return make_uint4((uint32_t)a, (uint32_t)(a >> 32), (uint32_t)b, (uint32_t)(b >> 32));
}
template <int N>
__device__ __forceinline__ void ll_get(const unsigned long long* p, uint32_t (&d)[N], unsigned int ep) {
    long long t0 = 0;
    for (;;) {
        bool ok = true;
#pragma unroll
        for (int i = 0; i < N; ++i) {
            const uint2 v = ll_ld1(p + i);
            d[i] = v.x;
            ok = ok && (v.y == ep);
        }
        if (ok) break;
        if (t0 == 0) t0 = clock64();
        else if (clock64() - t0 > WAIT_LIMIT_CYCLES) __trap();
    }
}

__device__ __forceinline__ void grid_arrive(unsigned int* ctr, int tid) {
    cons_sync();
    if (tid == 0) red_release_add(ctr, 1u);
}
__device__ __noinline__ void grid_wait(const unsigned int* ctr, unsigned int target, int tid) {
    if (tid == 0) {
        const long long t0 = clock64();
        while ((int)(ld_acquire(ctr) - target) < 0) {
            if (clock64() - t0 > WAIT_LIMIT_CYCLES) __trap();
        }
    }
    cons_sync();
}

__device__ __forceinline__ float warp_sum(float v) {
#pragma unroll
    for (int o = 16; o > 0; o >>= 1) v += __shfl_xor_sync(0xffffffffu, v, o);
    return v;
}
__device__ __forceinline__ float warp_max(float v) {
#pragma unroll
    for (int o = 16; o > 0; o >>= 1) v = fmaxf(v, __shfl_xor_sync(0xffffffffu, v, o));
    return v;
}

__device__ __forceinline__ void fma8(float (&acc)[8], const uint4& w, float s) {
    acc[0] = fmaf(s, bf_lo(w.x), acc[0]);
    acc[1] = fmaf(s, bf_hi(w.x), acc[1]);
    acc[2] = fmaf(s, bf_lo(w.y), acc[2]);
    acc[3] = fmaf(s, bf_hi(w.y), acc[3]);
    acc[4] = fmaf(s, bf_lo(w.z), acc[4]);
    acc[5] = fmaf(s, bf_hi(w.z), acc[5]);
    acc[6] = fmaf(s, bf_lo(w.w), acc[6]);
    acc[7] = fmaf(s, bf_hi(w.w), acc[7]);
}
__device__ __forceinline__ float dot8(const uint4& w, const float* q) {
    float s = q[0] * bf_lo(w.x);
    s = fmaf(q[1], bf_hi(w.x), s);
    s = fmaf(q[2], bf_lo(w.y), s);
    s = fmaf(q[3], bf_hi(w.y), s);
    s = fmaf(q[4], bf_lo(w.z), s);
    s = fmaf(q[5], bf_hi(w.z), s);
    s = fmaf(q[6], bf_lo(w.w), s);
    s = fmaf(q[7], bf_hi(w.w), s);
    return s;
}

__device__ __noinline__ void stage_rows(uint32_t dst, int dst_pitch, const void* src, int src_stride, int rows,
                                        int cpr, int tid, int nthr) {
    const int n = rows * cpr;
#pragma unroll 1
    for (int i = tid; i < n; i += nthr) {
        const int r = i / cpr, c = i - r * cpr;
        cp_async16(dst + r * dst_pitch + c * 16, (const unsigned char*)src + (size_t)r * src_stride + c * 16);
    }
}

template <int KS, int NT>
__device__ __noinline__ void gemv_mma(uint32_t w, int w_pitch, uint32_t a, int a_pitch, float* part, int lane) {
    float c[NT][4];
#pragma unroll
    for (int nt = 0; nt < NT; ++nt) { c[nt][0] = 0.f; c[nt][1] = 0.f; c[nt][2] = 0.f; c[nt][3] = 0.f; }
    const uint32_t ap = a + (lane >> 2) * a_pitch + (lane & 3) * 4;
    const uint32_t wp = w + ((lane & 7) + ((lane >> 4) << 3)) * w_pitch + ((lane >> 3) & 1) * 16;
#pragma unroll
    for (int ks = 0; ks < KS; ++ks) {
        uint32_t b0 = 0, b1 = 0;
        if (lane < 16) {
            asm("ld.shared.u32 %0, [%1];" : "=r"(b0) : "r"(ap + ks * 32));
            asm("ld.shared.u32 %0, [%1];" : "=r"(b1) : "r"(ap + ks * 32 + 16));
        }
#pragma unroll
        for (int nt = 0; nt < NT; ++nt) {
            uint32_t a0, a1, a2, a3;
            asm("ldmatrix.sync.aligned.m8n8.x4.trans.shared.b16 {%0, %1, %2, %3}, [%4];"
                         : "=r"(a0), "=r"(a1), "=r"(a2), "=r"(a3) : "r"(wp + ks * 16 * w_pitch + nt * 32));
            asm("mma.sync.aligned.m16n8k16.row.col.f32.bf16.bf16.f32 {%0, %1, %2, %3}, {%4, %5, %6, %7}, "
                "{%8, %9}, {%0, %1, %2, %3};"
                : "+f"(c[nt][0]), "+f"(c[nt][1]), "+f"(c[nt][2]), "+f"(c[nt][3])
                : "r"(a0), "r"(a1), "r"(a2), "r"(a3), "r"(b0), "r"(b1));
        }
    }
    if ((lane & 3) < 2) {
        float* pp = part + (lane & 3) * 160 + (lane >> 2);
#pragma unroll
        for (int nt = 0; nt < NT; ++nt) {
            pp[nt * 16] = c[nt][0];
            pp[nt * 16 + 80] = c[nt][1];
            pp[nt * 16 + 8] = c[nt][2];
            pp[nt * 16 + 88] = c[nt][3];
        }
    }
}

template <int KS, int NT>
__device__ __forceinline__ void frag_load(uint32_t (&f)[KS][NT][4], uint32_t w, int w_pitch, int lane) {
    const uint32_t wp = w + ((lane & 7) + ((lane >> 4) << 3)) * w_pitch + ((lane >> 3) & 1) * 16;
#pragma unroll
    for (int ks = 0; ks < KS; ++ks)
#pragma unroll
        for (int nt = 0; nt < NT; ++nt)
            asm volatile("ldmatrix.sync.aligned.m8n8.x4.trans.shared.b16 {%0, %1, %2, %3}, [%4];"
                         : "=r"(f[ks][nt][0]), "=r"(f[ks][nt][1]), "=r"(f[ks][nt][2]), "=r"(f[ks][nt][3])
                         : "r"(wp + ks * 16 * w_pitch + nt * 32) : "memory");
}
template <int KS, int NT>
__device__ __forceinline__ void frag_mma(const uint32_t (&f)[KS][NT][4], uint32_t a, int a_pitch, float* part, int lane) {
    float c[NT][4];
#pragma unroll
    for (int nt = 0; nt < NT; ++nt) { c[nt][0] = 0.f; c[nt][1] = 0.f; c[nt][2] = 0.f; c[nt][3] = 0.f; }
    const uint32_t ap = a + (lane >> 2) * a_pitch + (lane & 3) * 4;
    uint32_t b[KS][2];
#pragma unroll
    for (int ks = 0; ks < KS; ++ks) {
        b[ks][0] = 0; b[ks][1] = 0;
        if (lane < 16) {
            asm volatile("ld.shared.u32 %0, [%1];" : "=r"(b[ks][0]) : "r"(ap + ks * 32) : "memory");
            asm volatile("ld.shared.u32 %0, [%1];" : "=r"(b[ks][1]) : "r"(ap + ks * 32 + 16) : "memory");
        }
    }
#pragma unroll
    for (int ks = 0; ks < KS; ++ks)
#pragma unroll
        for (int nt = 0; nt < NT; ++nt)
            asm("mma.sync.aligned.m16n8k16.row.col.f32.bf16.bf16.f32 {%0, %1, %2, %3}, {%4, %5, %6, %7}, "
                "{%8, %9}, {%0, %1, %2, %3};"
                : "+f"(c[nt][0]), "+f"(c[nt][1]), "+f"(c[nt][2]), "+f"(c[nt][3])
                : "r"(f[ks][nt][0]), "r"(f[ks][nt][1]), "r"(f[ks][nt][2]), "r"(f[ks][nt][3]), "r"(b[ks][0]), "r"(b[ks][1]));
    if ((lane & 3) < 2) {
        float* pp = part + (lane & 3) * 160 + (lane >> 2);
#pragma unroll
        for (int nt = 0; nt < NT; ++nt) {
            pp[nt * 16] = c[nt][0];
            pp[nt * 16 + 80] = c[nt][1];
            pp[nt * 16 + 8] = c[nt][2];
            pp[nt * 16 + 88] = c[nt][3];
        }
    }
}

__device__ __forceinline__ float tall_sum(const float* part, int b, int n) {
    float s = 0.f;
#pragma unroll
    for (int w = 0; w < 8; ++w) s += part[(w * 4 + b) * 80 + n];
    return s;
}

__device__ __forceinline__ void ln_norm(float (&v)[10], float* s_red, int tid) {
    const int warp = tid >> 5;
    const float pv = __shfl_sync(0xffffffffu, v[0], 0);
    float s = 0.f, q = 0.f;
#pragma unroll
    for (int i = 0; i < 10; ++i) { const float d = v[i] - pv; s += d; q = fmaf(d, d, q); }
#pragma unroll
    for (int o = 16; o > 0; o >>= 1) {
        s += __shfl_xor_sync(0xffffffffu, s, o);
        q += __shfl_xor_sync(0xffffffffu, q, o);
    }
    const float md = s * (2.0f / DM);
    if ((tid & 31) == 0) *(float2*)(s_red + 2 * warp) = make_float2(pv + md, fmaxf(q - s * md, 0.f));
    cons_sync();
    const float4 r = *(const float4*)(s_red + 4 * (warp >> 1));
    const float dm = r.x - r.z;
    const float var = (r.y + r.w + dm * dm * (DM / 4)) * (1.0f / DM);
    const float mean = bf16r(0.5f * (r.x + r.z));
    const float inv = __fdiv_rn(1.0f, bf16r(sqrtf(bf16r(bf16r(var) + 1e-5f))));
#pragma unroll
    for (int i = 0; i < 10; ++i) v[i] = bf16r(bf16r(v[i] - mean) * inv);
}
__device__ __forceinline__ void modulate(const float (&n)[10], const uint32_t (&sh)[5], const uint32_t (&sc)[5], uint32_t* dst) {
#pragma unroll
    for (int i = 0; i < 5; ++i) {
        const float h0 = bf16r(n[2 * i] * bf16r(1.0f + bf_lo(sc[i]))) + bf_lo(sh[i]);
        const float h1 = bf16r(n[2 * i + 1] * bf16r(1.0f + bf_hi(sc[i]))) + bf_hi(sh[i]);
        __nv_bfloat162 p = __floats2bfloat162_rn(h0, h1);
        dst[i] = *(uint32_t*)&p;
    }
}

__device__ __forceinline__ float gelu_tanh(float x) {
    const float kBeta = 0.7978845608028654f;
    const float inner = kBeta * (x + 0.044715f * x * x * x);
    return 0.5f * x * (1.0f + tanhf(inner));
}

__global__ void __launch_bounds__(NTHREADS, 1)
decode_block_kernel(const __nv_bfloat16* __restrict__ x_in, const __nv_bfloat16* __restrict__ k_cache,
                    const __nv_bfloat16* __restrict__ v_cache, const __nv_bfloat16* __restrict__ wq,
                    const __nv_bfloat16* __restrict__ wo, const __nv_bfloat16* __restrict__ w_gate,
                    const __nv_bfloat16* __restrict__ w_up, const __nv_bfloat16* __restrict__ w_down,
                    const __nv_bfloat16* __restrict__ cvec, const __nv_bfloat16* __restrict__ w_mod,
                    __nv_bfloat16* __restrict__ out) {
    extern __shared__ __align__(128) unsigned char smem[];
    const int tid = threadIdx.x;
    const int cta = blockIdx.x;

    const uint32_t sbase = smem_u32(smem);
    const uint32_t bar_full = sbase + SM_BAR;
    const uint32_t bar_empty = bar_full + NST * 8;
    volatile int* s_item = (volatile int*)(smem + SM_ITEM);
    volatile int* s_tag = (volatile int*)(smem + SM_TAG);

    const uint32_t bar_go = bar_empty + NST * 8;
    if (tid < NST) s_tag[tid] = -1;
    if (tid == 0) {
#pragma unroll 1
        for (int s = 0; s < 2 * NST + 1; ++s) mbar_init(bar_full + s * 8, 1);
        asm volatile("fence.mbarrier_init.release.cluster;" ::: "memory");
        asm volatile("fence.proxy.async.shared::cta;" ::: "memory");
#pragma unroll 1
        for (int s = 0; s < PRE; ++s) mbar_arrive(bar_empty + s * 8);
    }
    __syncthreads();

    if (tid >= NCONS) {
        if (tid == NCONS) {
            int u = 0;
            const int G = (int)gridDim.x;
            uint64_t pol;
            asm volatile("createpolicy.fractional.L2::evict_first.b64 %0, 1.0;" : "=l"(pol));
            auto produce = [&](const int item) {
                const int it = item & (NITEM_K - 1);
                const bool is_v = item >= NITEM_K;
                const unsigned char* src = (const unsigned char*)(is_v ? v_cache : k_cache) + (size_t)it * (ITEM_KEYS * DH * 2);
#pragma unroll 1
                for (int t = 0; t < TPI; ++t, ++u) {
                    const int st = u % NST;
                    const uint32_t fb = bar_full + st * 8;
                    mbar_wait(bar_empty + st * 8, (u / NST) & 1);
                    if (item >= NITEM - THR_ITEMS * G) mbar_wait(bar_empty + ((u - THR_DEPTH) % NST) * 8, ((u - THR_DEPTH) / NST + 1) & 1);
                    s_item[st] = item;
                    s_tag[st] = u;
                    mbar_expect_tx(fb, TILE_BYTES);
                    bulk_g2s(sbase + SM_RING + st * STAGE_BYTES, src + t * TILE_BYTES, TILE_BYTES, fb, pol);
                }
            };
            if (PSTART != 3) mbar_wait(bar_go, 0);
            int item = cta;
#pragma unroll 1
            while (item < NITEM) {
                const int next = (int)atomicAdd(&g_work, 1u) + G;
                produce(item);
                item = next;
            }
#pragma unroll 1
            for (int j = 0; j < 8; ++j, u += TPI) {
                const int st = u % NST;
                mbar_wait(bar_empty + st * 8, (u / NST) & 1);
                s_item[st] = -1;
                s_tag[st] = u;
                mbar_arrive(bar_full + st * 8);
            }
            PROFP(13);
        }
        return;
    }

    const int lane = tid & 31, warp = tid >> 5;
    float* s_part = (float*)(smem + SM_PART);
    float* s_xp = (float*)(smem + SM_XP);
    float* s_red = (float*)(smem + SM_RED);
    const int lrow = tid >> 6, lcol = (tid & 63) * 10;
    uint32_t* h_dst = (uint32_t*)(smem + SM_A + lrow * A_PITCH + lcol * 2);

    PROF(0);
    const unsigned int ep = ld_acquire(&g_epoch) + 1u;
    const unsigned int target = ep * gridDim.x, tag16 = ep & 0xffffu;
    const unsigned long long* mod_row = g_mod + (lrow * MODN + lcol) / 2;
    float nv[10];
    {
        const int i1 = tid + NCONS;
        const uint4 c0 = __ldg((const uint4*)cvec + tid);
        uint4 c1 = c0;
        if (i1 < 320) c1 = __ldg((const uint4*)cvec + i1);
        uint32_t xw[5];
#pragma unroll
        for (int i = 0; i < 5; ++i) xw[i] = __ldg((const uint32_t*)(x_in + lrow * DM + lcol) + i);
        if (cta < MODN / 32) stage_rows(sbase + SM_W32, P32, w_mod + cta * 32, MODN * 2, DM, 4, tid, NCONS);
        cp_async_commit();
        if (cta < QN / 48) stage_rows(sbase + SM_WQ, P48, wq + cta * 48, QN * 2, DM, 6, tid, NCONS);
        cp_async_commit();
        if (PSTART == 1 && tid == 0) mbar_arrive(bar_go);
#pragma unroll 1
        for (int r = 0; r < 2; ++r) {
            const int i = r ? i1 : tid;
            if (i < 320) {
                const uint4 cc = r ? c1 : c0;
                const uint32_t cw[4] = {cc.x, cc.y, cc.z, cc.w};
                uint32_t ow[4];
#pragma unroll
                for (int k = 0; k < 4; ++k) {
                    const float a = bf_lo(cw[k]), b = bf_hi(cw[k]);
                    __nv_bfloat162 p = __floats2bfloat162_rn(__fdiv_rn(a, 1.0f + __expf(-a)), __fdiv_rn(b, 1.0f + __expf(-b)));
                    ow[k] = *(uint32_t*)&p;
                }
                const int b = i / 80, c8 = i - b * 80;
                *(uint4*)(smem + SM_A + b * A_PITCH + c8 * 16) = make_uint4(ow[0], ow[1], ow[2], ow[3]);
            }
        }
#pragma unroll
        for (int i = 0; i < 5; ++i) {
            nv[2 * i] = bf_lo(xw[i]);
            nv[2 * i + 1] = bf_hi(xw[i]);
            *(float2*)(s_xp + lrow * DM + lcol + 2 * i) = make_float2(nv[2 * i], nv[2 * i + 1]);
        }
    }
    float* acc_o = g_o[ep & 1];
    float* acc_attn = g_attn[ep & 1];
    if (cta == gridDim.x - 1) {
#pragma unroll 1
        for (int i = tid; i < NB * QN / 4; i += NCONS) ((float4*)g_o[~ep & 1])[i] = make_float4(0.f, 0.f, 0.f, 0.f);
#pragma unroll 1
        for (int i = tid; i < NB * DM; i += NCONS) g_attn[~ep & 1][i] = 0.f;
    }
    ln_norm(nv, s_red, tid);
    cp_async_wait1();
    cons_sync();
    if (PSTART == 0 && tid == 0) mbar_arrive(bar_go);
    if (cta < MODN / 32) {
        gemv_mma<5, 2>(sbase + SM_W32 + warp * 80 * P32, P32, sbase + SM_A + warp * 160, A_PITCH, s_part + warp * 320, lane);
        cons_sync();
        if (tid < 64) {
            const int b = tid >> 4, n = (tid & 15) * 2;
            ll_store(g_mod + (b * MODN + cta * 32 + n) / 2, tall_sum(s_part, b, n), tall_sum(s_part, b, n + 1), ep);
        }
    }
    PROF(1);

    if (cta < QN / 48) {
        cp_async_wait_all();
        cons_sync();
        if (PSTART == 2 && tid == 0) mbar_arrive(bar_go);
        uint32_t fq[5][3][4];
        frag_load<5, 3>(fq, sbase + SM_WQ + warp * 80 * P48, P48, lane);
        {
            long long t0 = 0;
            for (;;) {
                bool ok = true;
#pragma unroll
                for (int r = 0; r < 5; ++r) {
                    const int i = tid + r * NCONS, b = i / 320, c4 = i - b * 320;
                    const uint4 v = ll_ld2(g_mod + b * (MODN / 2) + 2 * c4);
                    *(uint2*)(s_part + b * DM + 2 * c4) = make_uint2(v.x, v.z);
                    ok = ok && v.y == ep && v.w == ep;
                }
                if (ok) break;
                if (t0 == 0) t0 = clock64();
                else if (clock64() - t0 > WAIT_LIMIT_CYCLES) __trap();
            }
        }
        cons_sync();
        PROF(2);
        uint32_t sh[5], sc[5];
#pragma unroll
        for (int i = 0; i < 5; ++i) {
            sh[i] = ((const uint32_t*)s_part)[lrow * DM + lcol / 2 + i];
            sc[i] = ((const uint32_t*)s_part)[lrow * DM + DM / 2 + lcol / 2 + i];
        }
        modulate(nv, sh, sc, h_dst);
        cons_sync();
        frag_mma<5, 3>(fq, sbase + SM_A + warp * 160, A_PITCH, s_part + warp * 320, lane);
        cons_sync();
        if (tid < 96) {
            const int b = tid / 24, n = (tid - b * 24) * 2;
            ll_store(g_q + (b * QN + cta * 48 + n) / 2, tall_sum(s_part, b, n), tall_sum(s_part, b, n + 1), ep);
        }
    } else if (PSTART == 2 && tid == 0) {
        mbar_arrive(bar_go);
    }
    PROF(3);
    if (tid == 0 && (!HAND_EARLY || cta >= QN / 48)) {
#pragma unroll 1
        for (int s = PRE; s < NST; ++s) mbar_arrive(bar_empty + s * 8);
    }
    uint32_t m_ga[5], m_sb[5], m_cb[5], m_fa[1] = {0u}, m_fb[1] = {0u};
    const int fcta = cta - ((int)gridDim.x - DM / 32);
    if (cta < FF / 16) {
        if (warp == 7) {
            stage_rows(sbase + SM_W32, P32, w_gate + cta * 16, FF * 2, DM, 2, lane, 32);
            stage_rows(sbase + SM_W32 + 32, P32, w_up + cta * 16, FF * 2, DM, 2, lane, 32);
        }
    }
    PROF(4);

    {
        const int sub = lane & 7, grp = lane >> 3;
        for (int u0 = warp * TPI;; u0 += 8 * TPI) {
            if (u0 == (8 + 6) * TPI) {
                if (cta < QN / 48) {
#pragma unroll 1
                    for (int i = lane; i < 48 * DM * 2 / 128; i += 32) {
                        unsigned int v;
                        asm volatile("ld.global.L2::128B.u32 %0, [%1];" : "=r"(v) : "l"((const unsigned char*)(wo + (size_t)cta * 48 * DM) + i * 128));
                    }
                }
                if (cta < FF / 16) {
#pragma unroll 1
                    for (int i = lane; i < 16 * DM * 2 / 128; i += 32) {
                        unsigned int v;
                        asm volatile("ld.global.L2::128B.u32 %0, [%1];" : "=r"(v) : "l"((const unsigned char*)(w_down + (size_t)cta * 16 * DM) + i * 128));
                    }
                }
            }
            if (s_tag[u0 % NST] != u0) tag_wait_slow(s_tag + u0 % NST, u0);
            const int item = s_item[u0 % NST];
            if ((u0 >= 8 * TPI && u0 < 16 * TPI) || (item < 0 && u0 < 8 * TPI)) {
                if (cta < FF / 16) {
                    ll_get(mod_row + DM, m_ga, ep);
                    ll_get(mod_row + 3 * DM / 2, m_sb, ep);
                    ll_get(mod_row + 2 * DM, m_cb, ep);
                }
                if (tid < 64 && fcta >= 0) {
                    ll_get(g_mod + ((tid >> 4) * MODN + 2 * DM + fcta * 32) / 2 + (tid & 15), m_fa, ep);
                    ll_get(g_mod + ((tid >> 4) * MODN + 5 * DM + fcta * 32) / 2 + (tid & 15), m_fb, ep);
                }
            }
            if (item < 0) {
                mbar_wait(bar_full + (u0 % NST) * 8, (u0 / NST) & 1);
                __syncwarp();
                if (lane == 0) mbar_arrive(bar_empty + (u0 % NST) * 8);
                break;
            }
            const int bh = (item & (NITEM_K - 1)) / CHUNKS;
            if (item < NITEM_K) {
                unsigned int* gs = g_s + (size_t)item * ITEM_KEYS;
                float qr[24];
                {
                    const unsigned long long* qp = g_q + ((bh >> 5) * QN + (bh & 31) * DH) / 2 + sub * 4;
                    long long t0 = 0;
                    for (;;) {
                        bool ok = true;
#pragma unroll
                        for (int j = 0; j < 6; ++j) {
                            const uint4 v = ll_ld2(qp + (j >> 1) * 32 + (j & 1) * 2);
                            qr[j * 4 + 0] = bf_lo(v.x); qr[j * 4 + 1] = bf_hi(v.x);
                            qr[j * 4 + 2] = bf_lo(v.z); qr[j * 4 + 3] = bf_hi(v.z);
                            ok = ok && v.y == ep && v.w == ep;
                        }
                        if (ok) break;
                        if (t0 == 0) t0 = clock64();
                        else if (clock64() - t0 > WAIT_LIMIT_CYCLES) __trap();
                    }
                }
                float m_run = -INFINITY, l_run = 0.f;
#pragma unroll 1
                for (int hh = 0; hh < 2 * TPI; ++hh) {
                    const int u = u0 + (hh >> 1), st = u % NST;
                    if (!(hh & 1)) stage_wait(bar_full, s_tag, u);
                    const uint4* tile = (const uint4*)(smem + SM_RING + st * STAGE_BYTES) + (hh & 1) * (32 * 24);
                    float part[8];
#pragma unroll
                    for (int it = 0; it < 8; ++it) {
                        const uint4* row = tile + (it * 4 + grp) * 24 + sub;
                        const uint4 a = row[0], b = row[8], c = row[16];
                        part[it] = dot8(a, qr) + dot8(b, qr + 8) + dot8(c, qr + 16);
                    }
                    if (hh & 1) {
                        __syncwarp();
                        if (lane == 0) mbar_arrive(bar_empty + st * 8);
                    }
#pragma unroll
                    for (int j = 0; j < 4; ++j) {
                        const float send = (sub & 4) ? part[j] : part[j + 4];
                        const float keep = (sub & 4) ? part[j + 4] : part[j];
                        part[j] = keep + __shfl_xor_sync(0xffffffffu, send, 4);
                    }
#pragma unroll
                    for (int j = 0; j < 2; ++j) {
                        const float send = (sub & 2) ? part[j] : part[j + 2];
                        const float keep = (sub & 2) ? part[j + 2] : part[j];
                        part[j] = keep + __shfl_xor_sync(0xffffffffu, send, 2);
                    }
                    {
                        const float send = (sub & 1) ? part[0] : part[1];
                        const float keep = (sub & 1) ? part[1] : part[0];
                        part[0] = keep + __shfl_xor_sync(0xffffffffu, send, 1);
                    }
                    const float s = bf16r(bf16r(part[0]) * 0.07216878364870323f);
                    asm volatile("st.relaxed.gpu.global.u32 [%0], %1;" ::"l"(gs + hh * 32 + sub * 4 + grp), "r"(__float_as_uint(s) | tag16) : "memory");
                    const float m_new = fmaxf(m_run, s);
                    l_run = l_run * __expf(m_run - m_new) + __expf(s - m_new);
                    m_run = m_new;
                }
                const float m = warp_max(m_run);
                const float l = warp_sum(l_run * __expf(m_run - m));
                if (lane == 0)
                    asm volatile("st.relaxed.gpu.global.u64 [%0], %1;" ::"l"(g_stat + item),
                                 "l"(((unsigned long long)__float_as_uint(l) << 32) | (__float_as_uint(m) | tag16)) : "memory");
            } else {
                float pr[2 * TPI];
                {
                    const unsigned int* gs = g_s + (size_t)(item - NITEM_K) * ITEM_KEYS + lane;
                    uint2 st2;
                    long long t0 = 0;
                    for (;;) {
                        st2 = ll_ld1(g_stat + bh * CHUNKS + lane);
                        bool ok = (st2.x & 0xffffu) == tag16;
#pragma unroll
                        for (int hh = 0; hh < 2 * TPI; ++hh) {
                            unsigned int w;
                            asm volatile("ld.relaxed.gpu.global.u32 %0, [%1];" : "=r"(w) : "l"(gs + hh * 32) : "memory");
                            ok = ok && (w & 0xffffu) == tag16;
                            pr[hh] = bf_hi(w);
                        }
                        if (__all_sync(0xffffffffu, ok)) break;
                        if (t0 == 0) t0 = clock64();
                        else if (clock64() - t0 > WAIT_LIMIT_CYCLES) __trap();
                    }
                    const float mi = bf_hi(st2.x);
                    const float mm = warp_max(mi);
                    const float ll = warp_sum(__uint_as_float(st2.y) * __expf(mi - mm));
#pragma unroll
                    for (int hh = 0; hh < 2 * TPI; ++hh) pr[hh] = bf16r(__fdiv_rn(__expf(pr[hh] - mm), ll));
                }
                float acc[3][8];
#pragma unroll
                for (int j = 0; j < 3; ++j)
#pragma unroll
                    for (int e = 0; e < 8; ++e) acc[j][e] = 0.f;
#pragma unroll
                for (int hh = 0; hh < 2 * TPI; ++hh) {
                    const int u = u0 + (hh >> 1), st = u % NST;
                    if (!(hh & 1)) stage_wait(bar_full, s_tag, u);
                    const uint4* tile = (const uint4*)(smem + SM_RING + st * STAGE_BYTES) + (hh & 1) * (32 * 24);
#pragma unroll
                    for (int it = 0; it < 8; ++it) {
                        const uint4* row = tile + (it * 4 + grp) * 24 + sub;
                        const uint4 a = row[0], b = row[8], c = row[16];
                        const float p = __shfl_sync(0xffffffffu, pr[hh], it * 4 + grp);
                        fma8(acc[0], a, p);
                        fma8(acc[1], b, p);
                        fma8(acc[2], c, p);
                    }
                    if (hh & 1) {
                        __syncwarp();
                        if (lane == 0) mbar_arrive(bar_empty + st * 8);
                    }
                }
                float* go = acc_o + (bh >> 5) * QN + (bh & 31) * DH + sub * 8;
#pragma unroll
                for (int j = 0; j < 3; ++j) {
#pragma unroll
                    for (int e = 0; e < 8; ++e) {
                        float v = acc[j][e];
                        v += __shfl_xor_sync(0xffffffffu, v, 8);
                        v += __shfl_xor_sync(0xffffffffu, v, 16);
                        acc[j][e] = v;
                    }
                    if (grp == 0) {
                        red_add_v4(go + j * 64, acc[j][0], acc[j][1], acc[j][2], acc[j][3]);
                        red_add_v4(go + j * 64 + 4, acc[j][4], acc[j][5], acc[j][6], acc[j][7]);
                    }
                }
            }
        }
    }
    PROF(5);
    grid_arrive(&g_bar[2], tid);
    PROF(6);
    const int ks = cta >> 3, ns = cta & 7;
    if (cta < 128 && tid < 240) {
        const int r0 = tid / 10, c = tid - r0 * 10;
        const unsigned char* src = (const unsigned char*)(wo + ((size_t)ks * WO_ROWS + r0) * DM + ns * 80) + c * 16;
        const uint32_t dst = sbase + SM_WO + r0 * P80 + c * 16;
#pragma unroll
        for (int i = 0; i < WO_ROWS / 24; ++i) cp_async16(dst + i * 24 * P80, src + (size_t)i * 24 * DM * 2);
    }
    uint32_t fd[3][5][4];
    cp_async_wait_all();
    cons_sync();
    frag_load<3, 5>(fd, sbase + SM_WO + warp * 48 * P80, P80, lane);
    grid_wait(&g_bar[2], target, tid);
    if (cta == 0 && tid == 0) { g_work = 0u; g_epoch = ep; }
    PROF(7);

    if (cta < 128) {
#pragma unroll
        for (int r = 0; r < 2; ++r) {
            const int i = tid + r * NCONS;
            if (i < NB * WO_ROWS / 4) {
                const int b = i / 96, c4 = i - b * 96;
                const float4 v = __ldcg((const float4*)(acc_o + b * QN + ks * WO_ROWS) + c4);
                __nv_bfloat162 p0 = __floats2bfloat162_rn(v.x, v.y), p1 = __floats2bfloat162_rn(v.z, v.w);
                uint2 w2;
                w2.x = *(uint32_t*)&p0; w2.y = *(uint32_t*)&p1;
                *(uint2*)(smem + SM_A + b * A_PITCH + c4 * 8) = w2;
            }
        }
        cons_sync();
        frag_mma<3, 5>(fd, sbase + SM_A + warp * 96, A_PITCH, s_part + warp * 320, lane);
        cons_sync();
        if (tid < 80) {
            const int b = tid / 20, n4 = tid - b * 20;
            float4 s4 = make_float4(0.f, 0.f, 0.f, 0.f);
#pragma unroll
            for (int w = 0; w < 8; ++w) {
                const float4 v = *(const float4*)(s_part + (w * 4 + b) * 80 + n4 * 4);
                s4.x += v.x; s4.y += v.y; s4.z += v.z; s4.w += v.w;
            }
            red_add_v4(acc_attn + b * DM + ns * 80 + n4 * 4, s4.x, s4.y, s4.z, s4.w);
        }
    }
    PROF(8);
    grid_arrive(&g_bar[3], tid);
    const bool has_e = cta < FF / 16;
    if (!has_e && fcta < 0) return;
    if (fcta >= 0) {
        const unsigned char* src = (const unsigned char*)(w_down + (size_t)(tid >> 2) * DM + fcta * 32) + (tid & 3) * 16;
        const uint32_t dst = sbase + SM_WD + (tid >> 2) * P32 + (tid & 3) * 16;
#pragma unroll
        for (int i = 0; i < FF / 64; ++i) cp_async16(dst + i * 64 * P32, src + (size_t)i * 64 * DM * 2);
    }
    if (has_e) {
        uint32_t fe[5][2][4];
        frag_load<5, 2>(fe, sbase + SM_W32 + warp * 80 * P32, P32, lane);
        grid_wait(&g_bar[3], target, tid);
        PROF(9);
        {
            float4 v[3];
#pragma unroll
            for (int r = 0; r < 3; ++r)
                if (tid + r * NCONS < NB * DM / 4) v[r] = __ldcg((const float4*)acc_attn + tid + r * NCONS);
#pragma unroll
            for (int r = 0; r < 3; ++r)
                if (tid + r * NCONS < NB * DM / 4) ((float4*)s_part)[tid + r * NCONS] = v[r];
        }
        cons_sync();
#pragma unroll
        for (int i = 0; i < 5; ++i) {
            const float2 av = *((const float2*)(s_part + lrow * DM + lcol) + i);
            const float2 xv = *((const float2*)(s_xp + lrow * DM + lcol) + i);
            nv[2 * i] = bf16r(xv.x + bf16r(bf_lo(m_ga[i]) * bf16r(av.x)));
            nv[2 * i + 1] = bf16r(xv.y + bf16r(bf_hi(m_ga[i]) * bf16r(av.y)));
        }
        ln_norm(nv, s_red, tid);
        modulate(nv, m_sb, m_cb, h_dst);
        cons_sync();
        frag_mma<5, 2>(fe, sbase + SM_A + warp * 160, A_PITCH, s_part + warp * 320, lane);
        cons_sync();
        if (tid < 32) {
            const int b = tid >> 3, n = (tid & 7) * 2;
            const float g0 = bf16r(tall_sum(s_part, b, n)), g1 = bf16r(tall_sum(s_part, b, n + 1));
            const float u0 = bf16r(tall_sum(s_part, b, 16 + n)), u1 = bf16r(tall_sum(s_part, b, 17 + n));
            ll_store(g_act + (b * FF + cta * 16 + n) / 2, bf16r(gelu_tanh(g0)) * u0, bf16r(gelu_tanh(g1)) * u1, ep);
        }
        PROF(10);
        if (fcta < 0) return;
    } else {
        grid_wait(&g_bar[3], target, tid);
    }
    {
        float x10 = 0.f, x11 = 0.f;
        if (tid < 64) {
            const int b = tid >> 4, col = fcta * 32 + (tid & 15) * 2;
            const float2 av = __ldcg((const float2*)(acc_attn + b * DM + col));
            x10 = bf16r(s_xp[b * DM + col] + bf16r(bf_lo(m_fa[0]) * bf16r(av.x)));
            x11 = bf16r(s_xp[b * DM + col + 1] + bf16r(bf_hi(m_fa[0]) * bf16r(av.y)));
        }
        cp_async_wait_all();
        cons_sync();
        uint32_t ff[12][2][4];
        frag_load<12, 2>(ff, sbase + SM_WD + warp * 192 * P32, P32, lane);
        long long t0 = 0;
        for (;;) {
            bool ok = true;
#pragma unroll
            for (int r = 0; r < 6; ++r) {
                const int i = tid + r * NCONS, b = i / 384, c4 = i - b * 384;
                const uint4 v = ll_ld2(g_act + 2 * i);
                *(uint2*)(smem + SM_ACT + b * ACT_PITCH + c4 * 8) = make_uint2(v.x, v.z);
                ok = ok && v.y == ep && v.w == ep;
            }
            if (ok) break;
            if (t0 == 0) t0 = clock64();
            else if (clock64() - t0 > WAIT_LIMIT_CYCLES) __trap();
        }
        cons_sync();
        PROF(11);
        frag_mma<12, 2>(ff, sbase + SM_ACT + warp * 384, ACT_PITCH, s_part + warp * 320, lane);
        cons_sync();
        if (tid < 64) {
            const int b = tid >> 4, n = (tid & 15) * 2;
            const float f0 = bf16r(tall_sum(s_part, b, n)), f1 = bf16r(tall_sum(s_part, b, n + 1));
            *(__nv_bfloat162*)(out + b * DM + fcta * 32 + n) =
                __floats2bfloat162_rn(x10 + bf16r(bf_lo(m_fb[0]) * f0), x11 + bf16r(bf_hi(m_fb[0]) * f1));
        }
    }
    PROF(12);
}

}

extern "C" void kernel_launch(void* const* d_in, const int* in_sizes, int n_in, void* d_out, int out_size) {
    (void)in_sizes; (void)n_in; (void)out_size;
    const __nv_bfloat16* A_x = (const __nv_bfloat16*)d_in[0];
    const __nv_bfloat16* A_k = (const __nv_bfloat16*)d_in[1];
    const __nv_bfloat16* A_v = (const __nv_bfloat16*)d_in[2];
    const __nv_bfloat16* A_wq = (const __nv_bfloat16*)d_in[3];
    const __nv_bfloat16* A_wo = (const __nv_bfloat16*)d_in[4];
    const __nv_bfloat16* B_wg = (const __nv_bfloat16*)d_in[6];
    const __nv_bfloat16* B_wu = (const __nv_bfloat16*)d_in[7];
    const __nv_bfloat16* B_wd = (const __nv_bfloat16*)d_in[8];
    const __nv_bfloat16* c = (const __nv_bfloat16*)d_in[9];
    const __nv_bfloat16* w_mod = (const __nv_bfloat16*)d_in[10];
    static int grid = 0;
    if (grid == 0) {
        cudaFuncSetAttribute(decode_block_kernel, cudaFuncAttributeMaxDynamicSharedMemorySize, SM_TOTAL);
        int dev = 0, sms = 0;
        cudaGetDevice(&dev);
        cudaDeviceGetAttribute(&sms, cudaDevAttrMultiProcessorCount, dev);
        grid = sms < 132 ? sms : 132;
    }
    decode_block_kernel<<<grid, NTHREADS, SM_TOTAL>>>(A_x, A_k, A_v, A_wq, A_wo, B_wg, B_wu, B_wd, c, w_mod,
                                                      (__nv_bfloat16*)d_out);
}
```

```cpp
#include <cuda_runtime.h>
#include <cuda_bf16.h>
#include <stdint.h>

namespace {

constexpr int NB = 4;
constexpr int DM = 640;
constexpr int NH = 32;
constexpr int SK = 4096;
constexpr int DH = 192;
constexpr int FF = 1536;
constexpr int MODN = 6 * DM;
constexpr int QN = NH * DH;
constexpr int NBH = NB * NH;

constexpr int NCONS = 256;
constexpr int NTHREADS = NCONS + 64;
constexpr int TILE_KEYS = 64;
constexpr int TILE_BYTES = TILE_KEYS * DH * 2;
constexpr int STAGE_BYTES = TILE_BYTES;
constexpr int NST = 6;
constexpr int PRE = 3;
constexpr int TPI = 2;
constexpr int ITEM_KEYS = TPI * TILE_KEYS;
constexpr int CHUNKS = SK / ITEM_KEYS;
constexpr int NITEM_K = NBH * CHUNKS;
constexpr int NITEM = 2 * NITEM_K;

constexpr int A_PITCH = 1296;
constexpr int ACT_PITCH = FF * 2 + 16;
constexpr int P32 = 80;
constexpr int P48 = 112;
constexpr int P80 = 176;
constexpr int P64 = 144;
constexpr int WO_ROWS = 768;
constexpr int ND = 64;
constexpr int NE = FF / 32;
constexpr int NF = DM / 32;

constexpr int SM_RING = 0;
constexpr int SM_WQ = PRE * STAGE_BYTES;
constexpr int SM_WO = 0;
constexpr int SM_WD = 0;
constexpr int SM_WG = 0;
constexpr int SM_W32 = NST * STAGE_BYTES;
constexpr int SM_ACT = SM_W32;
constexpr int SM_A = SM_W32 + DM * P32;
constexpr int SM_PART = SM_A + NB * A_PITCH;
constexpr int SM_XP = SM_PART + 8 * 4 * 80 * 4;
constexpr int SM_RED = SM_XP + NB * DM * 4;
constexpr int SM_ITEM = SM_RED + 16 * 4;
constexpr int SM_TAG = SM_ITEM + 16 * 4;
constexpr int SM_JUNK = SM_TAG + 16 * 4;
constexpr int SM_BAR = SM_JUNK + 512;
constexpr int SM_TOTAL = SM_BAR + (2 * NST + 2) * 8;
static_assert(SM_WQ + DM * P48 <= NST * STAGE_BYTES, "prologue overlay");
static_assert(FF * P32 <= NST * STAGE_BYTES && WO_ROWS * P80 <= NST * STAGE_BYTES && DM * P64 <= NST * STAGE_BYTES, "tail overlay");
static_assert(SM_TOTAL <= 232448, "smem");
#define THR_ITEMS 6
#define THR_DEPTH 3
#define HAND_EARLY 0
#define PSTART 0
#define SMALL_R 0
#define THR_DEPTH_S 4
#define AUXW 1

__device__ __align__(128) unsigned long long g_mod[NB * MODN / 2];
__device__ __align__(128) unsigned long long g_q[NB * QN / 2];
__device__ __align__(128) unsigned long long g_act[NB * FF / 2];
__device__ __align__(128) unsigned int g_s[NBH * SK];
__device__ __align__(128) unsigned long long g_stat[NBH * CHUNKS];
__device__ __align__(128) float g_o[2][NB * QN];
__device__ __align__(128) float g_attn[2][NB * DM];
__device__ __align__(128) unsigned int g_bar[8];
__device__ unsigned int g_work;
__device__ unsigned int g_epoch;

#define PROF(k) do { } while (0)
#define PROFP(k) do { } while (0)

__device__ __forceinline__ float bf16r(float x) { return __bfloat162float(__float2bfloat16_rn(x)); }
__device__ __forceinline__ float bf_lo(uint32_t u) { return __uint_as_float(u << 16); }
__device__ __forceinline__ float bf_hi(uint32_t u) { return __uint_as_float(u & 0xffff0000u); }

__device__ __forceinline__ uint32_t smem_u32(const void* p) { return (uint32_t)__cvta_generic_to_shared(p); }
__device__ __forceinline__ void mbar_init(uint32_t bar, uint32_t count) {
    asm volatile("mbarrier.init.shared::cta.b64 [%0], %1;" ::"r"(bar), "r"(count) : "memory");
}
__device__ __forceinline__ void mbar_expect_tx(uint32_t bar, uint32_t bytes) {
    asm volatile("mbarrier.arrive.expect_tx.shared::cta.b64 _, [%0], %1;" ::"r"(bar), "r"(bytes) : "memory");
}
__device__ __forceinline__ void mbar_arrive(uint32_t bar) {
    asm volatile("mbarrier.arrive.shared::cta.b64 _, [%0];" ::"r"(bar) : "memory");
}
constexpr long long WAIT_LIMIT_CYCLES = 200000000LL;
__device__ __forceinline__ uint32_t mbar_try(uint32_t bar, uint32_t parity) {
    uint32_t done;
    asm volatile(
        "{\n\t.reg .pred p;\n\t"
        "mbarrier.try_wait.parity.shared::cta.b64 p, [%1], %2;\n\t"
        "selp.u32 %0, 1, 0, p;\n\t}"
        : "=r"(done) : "r"(bar), "r"(parity) : "memory");
    return done;
}
__device__ __noinline__ void mbar_wait_slow(uint32_t bar, uint32_t parity) {
    const long long t0 = clock64();
    while (!mbar_try(bar, parity)) {
        if (clock64() - t0 > WAIT_LIMIT_CYCLES) __trap();
    }
}
__device__ __forceinline__ void mbar_wait(uint32_t bar, uint32_t parity) {
    if (!mbar_try(bar, parity)) mbar_wait_slow(bar, parity);
}
__device__ __noinline__ void tag_wait_slow(volatile int* tag, int u) {
    const long long t0 = clock64();
    while (*tag != u) {
        __nanosleep(32);
        if (clock64() - t0 > WAIT_LIMIT_CYCLES) __trap();
    }
}
__device__ __forceinline__ void stage_wait(uint32_t bar_full, volatile int* s_tag, int u) {
    const int st = u % NST;
    if (s_tag[st] != u) tag_wait_slow(s_tag + st, u);
    mbar_wait(bar_full + st * 8, (u / NST) & 1);
}
__device__ __forceinline__ void bulk_g2s(uint32_t dst, const void* src, uint32_t bytes, uint32_t bar, uint64_t pol) {
    asm volatile(
        "cp.async.bulk.shared::cluster.global.mbarrier::complete_tx::bytes.L2::cache_hint [%0], [%1], %2, [%3], %4;"
        ::"r"(dst), "l"(src), "r"(bytes), "r"(bar), "l"(pol) : "memory");
}
__device__ __forceinline__ void cp_async16(uint32_t dst, const void* src) {
    asm volatile("cp.async.cg.shared.global [%0], [%1], 16;" ::"r"(dst), "l"(src) : "memory");
}
__device__ __forceinline__ void l2_warm(uint32_t dst, const void* p) {
    asm volatile("cp.async.cg.shared.global.L2::128B [%0], [%1], 16;" ::"r"(dst), "l"(p) : "memory");
}
__device__ __forceinline__ void cp_async_wait_all() { asm volatile("cp.async.wait_all;" ::: "memory"); }
__device__ __forceinline__ void cp_async_commit() { asm volatile("cp.async.commit_group;" ::: "memory"); }
__device__ __forceinline__ void cp_async_wait1() { asm volatile("cp.async.wait_group 1;" ::: "memory"); }
__device__ __forceinline__ void red_release_add(unsigned int* p, unsigned int v) {
    asm volatile("red.release.gpu.global.add.u32 [%0], %1;" ::"l"(p), "r"(v) : "memory");
}
__device__ __forceinline__ void cons_sync() { asm volatile("bar.sync 1, 256;" ::: "memory"); }

__device__ __forceinline__ void red_add_v4(float* p, float a, float b, float c, float d) {
    asm volatile("red.global.add.v4.f32 [%0], {%1, %2, %3, %4};" ::"l"(p), "f"(a), "f"(b), "f"(c), "f"(d) : "memory");
}
__device__ __forceinline__ unsigned int ld_acquire(const unsigned int* p) {
    unsigned int v;
    asm volatile("ld.acquire.gpu.global.u32 %0, [%1];" : "=r"(v) : "l"(p) : "memory");
    return v;
}
__device__ __forceinline__ void ll_store(unsigned long long* p, float a, float b, unsigned int ep) {
    __nv_bfloat162 v = __floats2bfloat162_rn(a, b);
    const unsigned long long w = ((unsigned long long)ep << 32) | *(uint32_t*)&v;
    asm volatile("st.relaxed.gpu.global.u64 [%0], %1;" ::"l"(p), "l"(w) : "memory");
}
__device__ __forceinline__ uint2 ll_ld1(const unsigned long long* p) {
    unsigned long long w;
    asm volatile("ld.relaxed.gpu.global.u64 %0, [%1];" : "=l"(w) : "l"(p) : "memory");
    return make_uint2((uint32_t)w, (uint32_t)(w >> 32));
}
__device__ __forceinline__ uint4 ll_ld2(const unsigned long long* p) {
    unsigned long long a, b;
    asm volatile("ld.relaxed.gpu.global.v2.u64 {%0, %1}, [%2];" : "=l"(a), "=l"(b) : "l"(p) : "memory");
    return make_uint4((uint32_t)a, (uint32_t)(a >> 32), (uint32_t)b, (uint32_t)(b >> 32));
}
template <int N>
__device__ __forceinline__ void ll_get(const unsigned long long* p, uint32_t (&d)[N], unsigned int ep) {
    long long t0 = 0;
    for (;;) {
        bool ok = true;
#pragma unroll
        for (int i = 0; i < N; ++i) {
            const uint2 v = ll_ld1(p + i);
            d[i] = v.x;
            ok = ok && (v.y == ep);
        }
        if (ok) break;
        if (t0 == 0) t0 = clock64();
        else if (clock64() - t0 > WAIT_LIMIT_CYCLES) __trap();
    }
}

__device__ __forceinline__ void grid_arrive(unsigned int* ctr, int tid) {
    cons_sync();
    if (tid == 0) red_release_add(ctr, 1u);
}
__device__ __noinline__ void grid_wait(const unsigned int* ctr, unsigned int target, int tid) {
    if (tid == 0) {
        const long long t0 = clock64();
        while ((int)(ld_acquire(ctr) - target) < 0) {
            if (clock64() - t0 > WAIT_LIMIT_CYCLES) __trap();
        }
    }
    cons_sync();
}

__device__ __forceinline__ float warp_sum(float v) {
#pragma unroll
    for (int o = 16; o > 0; o >>= 1) v += __shfl_xor_sync(0xffffffffu, v, o);
    return v;
}
__device__ __forceinline__ float warp_max(float v) {
#pragma unroll
    for (int o = 16; o > 0; o >>= 1) v = fmaxf(v, __shfl_xor_sync(0xffffffffu, v, o));
    return v;
}

__device__ __forceinline__ void fma8(float (&acc)[8], const uint4& w, float s) {
    acc[0] = fmaf(s, bf_lo(w.x), acc[0]);
    acc[1] = fmaf(s, bf_hi(w.x), acc[1]);
    acc[2] = fmaf(s, bf_lo(w.y), acc[2]);
    acc[3] = fmaf(s, bf_hi(w.y), acc[3]);
    acc[4] = fmaf(s, bf_lo(w.z), acc[4]);
    acc[5] = fmaf(s, bf_hi(w.z), acc[5]);
    acc[6] = fmaf(s, bf_lo(w.w), acc[6]);
    acc[7] = fmaf(s, bf_hi(w.w), acc[7]);
}
__device__ __forceinline__ float dot8(const uint4& w, const float* q) {
    float s = q[0] * bf_lo(w.x);
    s = fmaf(q[1], bf_hi(w.x), s);
    s = fmaf(q[2], bf_lo(w.y), s);
    s = fmaf(q[3], bf_hi(w.y), s);
    s = fmaf(q[4], bf_lo(w.z), s);
    s = fmaf(q[5], bf_hi(w.z), s);
    s = fmaf(q[6], bf_lo(w.w), s);
    s = fmaf(q[7], bf_hi(w.w), s);
    return s;
}

__device__ __noinline__ void stage_rows(uint32_t dst, int dst_pitch, const void* src, int src_stride, int rows,
                                        int cpr, int tid, int nthr) {
    const int n = rows * cpr;
#pragma unroll 1
    for (int i = tid; i < n; i += nthr) {
        const int r = i / cpr, c = i - r * cpr;
        cp_async16(dst + r * dst_pitch + c * 16, (const unsigned char*)src + (size_t)r * src_stride + c * 16);
    }
}

template <int KS, int NT>
__device__ __noinline__ void gemv_mma(uint32_t w, int w_pitch, uint32_t a, int a_pitch, float* part, int lane) {
    float c[NT][4];
#pragma unroll
    for (int nt = 0; nt < NT; ++nt) { c[nt][0] = 0.f; c[nt][1] = 0.f; c[nt][2] = 0.f; c[nt][3] = 0.f; }
    const uint32_t ap = a + (lane >> 2) * a_pitch + (lane & 3) * 4;
    const uint32_t wp = w + ((lane & 7) + ((lane >> 4) << 3)) * w_pitch + ((lane >> 3) & 1) * 16;
#pragma unroll
    for (int ks = 0; ks < KS; ++ks) {
        uint32_t b0 = 0, b1 = 0;
        if (lane < 16) {
            asm("ld.shared.u32 %0, [%1];" : "=r"(b0) : "r"(ap + ks * 32));
            asm("ld.shared.u32 %0, [%1];" : "=r"(b1) : "r"(ap + ks * 32 + 16));
        }
#pragma unroll
        for (int nt = 0; nt < NT; ++nt) {
            uint32_t a0, a1, a2, a3;
            asm("ldmatrix.sync.aligned.m8n8.x4.trans.shared.b16 {%0, %1, %2, %3}, [%4];"
                         : "=r"(a0), "=r"(a1), "=r"(a2), "=r"(a3) : "r"(wp + ks * 16 * w_pitch + nt * 32));
            asm("mma.sync.aligned.m16n8k16.row.col.f32.bf16.bf16.f32 {%0, %1, %2, %3}, {%4, %5, %6, %7}, "
                "{%8, %9}, {%0, %1, %2, %3};"
                : "+f"(c[nt][0]), "+f"(c[nt][1]), "+f"(c[nt][2]), "+f"(c[nt][3])
                : "r"(a0), "r"(a1), "r"(a2), "r"(a3), "r"(b0), "r"(b1));
        }
    }
    if ((lane & 3) < 2) {
        float* pp = part + (lane & 3) * 160 + (lane >> 2);
#pragma unroll
        for (int nt = 0; nt < NT; ++nt) {
            pp[nt * 16] = c[nt][0];
            pp[nt * 16 + 80] = c[nt][1];
            pp[nt * 16 + 8] = c[nt][2];
            pp[nt * 16 + 88] = c[nt][3];
        }
    }
}

template <int KS, int NT>
__device__ __forceinline__ void frag_load(uint32_t (&f)[KS][NT][4], uint32_t w, int w_pitch, int lane) {
    const uint32_t wp = w + ((lane & 7) + ((lane >> 4) << 3)) * w_pitch + ((lane >> 3) & 1) * 16;
#pragma unroll
    for (int ks = 0; ks < KS; ++ks)
#pragma unroll
        for (int nt = 0; nt < NT; ++nt)
            asm volatile("ldmatrix.sync.aligned.m8n8.x4.trans.shared.b16 {%0, %1, %2, %3}, [%4];"
                         : "=r"(f[ks][nt][0]), "=r"(f[ks][nt][1]), "=r"(f[ks][nt][2]), "=r"(f[ks][nt][3])
                         : "r"(wp + ks * 16 * w_pitch + nt * 32) : "memory");
}
template <int KS, int NT>
__device__ __forceinline__ void frag_mma(const uint32_t (&f)[KS][NT][4], uint32_t a, int a_pitch, float* part, int lane) {
    float c[NT][4];
#pragma unroll
    for (int nt = 0; nt < NT; ++nt) { c[nt][0] = 0.f; c[nt][1] = 0.f; c[nt][2] = 0.f; c[nt][3] = 0.f; }
    const uint32_t ap = a + (lane >> 2) * a_pitch + (lane & 3) * 4;
    uint32_t b[KS][2];
#pragma unroll
    for (int ks = 0; ks < KS; ++ks) {
        b[ks][0] = 0; b[ks][1] = 0;
        if (lane < 16) {
            asm volatile("ld.shared.u32 %0, [%1];" : "=r"(b[ks][0]) : "r"(ap + ks * 32) : "memory");
            asm volatile("ld.shared.u32 %0, [%1];" : "=r"(b[ks][1]) : "r"(ap + ks * 32 + 16) : "memory");
        }
    }
#pragma unroll
    for (int ks = 0; ks < KS; ++ks)
#pragma unroll
        for (int nt = 0; nt < NT; ++nt)
            asm("mma.sync.aligned.m16n8k16.row.col.f32.bf16.bf16.f32 {%0, %1, %2, %3}, {%4, %5, %6, %7}, "
                "{%8, %9}, {%0, %1, %2, %3};"
                : "+f"(c[nt][0]), "+f"(c[nt][1]), "+f"(c[nt][2]), "+f"(c[nt][3])
                : "r"(f[ks][nt][0]), "r"(f[ks][nt][1]), "r"(f[ks][nt][2]), "r"(f[ks][nt][3]), "r"(b[ks][0]), "r"(b[ks][1]));
    if ((lane & 3) < 2) {
        float* pp = part + (lane & 3) * 160 + (lane >> 2);
#pragma unroll
        for (int nt = 0; nt < NT; ++nt) {
            pp[nt * 16] = c[nt][0];
            pp[nt * 16 + 80] = c[nt][1];
            pp[nt * 16 + 8] = c[nt][2];
            pp[nt * 16 + 88] = c[nt][3];
        }
    }
}

__device__ __forceinline__ float tall_sum(const float* part, int b, int n) {
    float s = 0.f;
#pragma unroll
    for (int w = 0; w < 8; ++w) s += part[(w * 4 + b) * 80 + n];
    return s;
}

__device__ __forceinline__ void ln_norm(float (&v)[10], float* s_red, int tid) {
    const int warp = tid >> 5;
    const float pv = __shfl_sync(0xffffffffu, v[0], 0);
    float s = 0.f, q = 0.f;
#pragma unroll
    for (int i = 0; i < 10; ++i) { const float d = v[i] - pv; s += d; q = fmaf(d, d, q); }
#pragma unroll
    for (int o = 16; o > 0; o >>= 1) {
        s += __shfl_xor_sync(0xffffffffu, s, o);
        q += __shfl_xor_sync(0xffffffffu, q, o);
    }
    const float md = s * (2.0f / DM);
    if ((tid & 31) == 0) *(float2*)(s_red + 2 * warp) = make_float2(pv + md, fmaxf(q - s * md, 0.f));
    cons_sync();
    const float4 r = *(const float4*)(s_red + 4 * (warp >> 1));
    const float dm = r.x - r.z;
    const float var = (r.y + r.w + dm * dm * (DM / 4)) * (1.0f / DM);
    const float mean = bf16r(0.5f * (r.x + r.z));
    const float inv = __fdiv_rn(1.0f, bf16r(sqrtf(bf16r(bf16r(var) + 1e-5f))));
#pragma unroll
    for (int i = 0; i < 10; ++i) v[i] = bf16r(bf16r(v[i] - mean) * inv);
}
__device__ __forceinline__ void modulate(const float (&n)[10], const uint32_t (&sh)[5], const uint32_t (&sc)[5], uint32_t* dst) {
#pragma unroll
    for (int i = 0; i < 5; ++i) {
        const float h0 = bf16r(n[2 * i] * bf16r(1.0f + bf_lo(sc[i]))) + bf_lo(sh[i]);
        const float h1 = bf16r(n[2 * i + 1] * bf16r(1.0f + bf_hi(sc[i]))) + bf_hi(sh[i]);
        __nv_bfloat162 p = __floats2bfloat162_rn(h0, h1);
        dst[i] = *(uint32_t*)&p;
    }
}

__device__ __forceinline__ float gelu_tanh(float x) {
    const float kBeta = 0.7978845608028654f;
    const float inner = kBeta * (x + 0.044715f * x * x * x);
    return 0.5f * x * (1.0f + tanhf(inner));
}

__global__ void __launch_bounds__(NTHREADS, 1)
decode_block_kernel(const __nv_bfloat16* __restrict__ x_in, const __nv_bfloat16* __restrict__ k_cache,
                    const __nv_bfloat16* __restrict__ v_cache, const __nv_bfloat16* __restrict__ wq,
                    const __nv_bfloat16* __restrict__ wo, const __nv_bfloat16* __restrict__ w_gate,
                    const __nv_bfloat16* __restrict__ w_up, const __nv_bfloat16* __restrict__ w_down,
                    const __nv_bfloat16* __restrict__ cvec, const __nv_bfloat16* __restrict__ w_mod,
                    __nv_bfloat16* __restrict__ out) {
    extern __shared__ __align__(128) unsigned char smem[];
    const int tid = threadIdx.x;
    const int cta = blockIdx.x;

    const uint32_t sbase = smem_u32(smem);
    const uint32_t bar_full = sbase + SM_BAR;
    const uint32_t bar_empty = bar_full + NST * 8;
    volatile int* s_item = (volatile int*)(smem + SM_ITEM);
    volatile int* s_tag = (volatile int*)(smem + SM_TAG);

    const uint32_t bar_go = bar_empty + NST * 8;
    if (tid < NST) s_tag[tid] = -1;
    if (tid == 0) {
#pragma unroll 1
        for (int s = 0; s < 2 * NST + 2; ++s) mbar_init(bar_full + s * 8, 1);
        asm volatile("fence.mbarrier_init.release.cluster;" ::: "memory");
        asm volatile("fence.proxy.async.shared::cta;" ::: "memory");
#pragma unroll 1
        for (int s = 0; s < PRE; ++s) mbar_arrive(bar_empty + s * 8);
    }
    __syncthreads();

    if (tid >= NCONS) {
        const int G = (int)gridDim.x;
        if (tid == NCONS) {
            int u = 0;
            uint64_t pol;
            asm volatile("createpolicy.fractional.L2::evict_first.b64 %0, 1.0;" : "=l"(pol));
            auto produce = [&](const int idx) {
                const int j = idx - (NITEM - SMALL_R);
                const int item = j < 0 ? idx : NITEM - SMALL_R + (j >> 1);
                const uint32_t bytes = j < 0 ? TILE_BYTES : TILE_BYTES / 2;
                const unsigned char* src = (const unsigned char*)(item >= NITEM_K ? v_cache : k_cache) +
                                           (size_t)(item & (NITEM_K - 1)) * (ITEM_KEYS * DH * 2) + (j < 0 ? 0 : (j & 1) * TILE_BYTES);
#pragma unroll 1
                for (int t = 0; t < TPI; ++t, ++u) {
                    const int st = u % NST;
                    const uint32_t fb = bar_full + st * 8;
                    mbar_wait(bar_empty + st * 8, (u / NST) & 1);
                    if (idx >= NITEM - THR_ITEMS * G) {
                        const int ud = u - (j < 0 ? THR_DEPTH : THR_DEPTH_S);
                        mbar_wait(bar_empty + (ud % NST) * 8, (ud / NST + 1) & 1);
                    }
                    s_item[st] = idx;
                    s_tag[st] = u;
                    mbar_expect_tx(fb, bytes);
                    bulk_g2s(sbase + SM_RING + st * STAGE_BYTES, src + t * bytes, bytes, fb, pol);
                }
            };
            if (PSTART != 3) mbar_wait(bar_go, 0);
            int item = cta;
#pragma unroll 1
            while (item < NITEM + SMALL_R) {
                const int next = (int)atomicAdd(&g_work, 1u) + G;
                if (next >= NITEM + SMALL_R) {
                    s_item[NST] = next - (NITEM + SMALL_R);
                    mbar_arrive(bar_go + 8);
                }
                produce(item);
                item = next;
            }
#pragma unroll 1
            for (int j = 0; j < 8; ++j, u += TPI) {
                const int st = u % NST;
                mbar_wait(bar_empty + st * 8, (u / NST) & 1);
                s_item[st] = -1;
                s_tag[st] = u;
                mbar_arrive(bar_full + st * 8);
            }
            PROFP(13);
        } else if (AUXW && tid >= NCONS + 32) {
            const int pl = tid & 31;
            const uint32_t junk = sbase + SM_JUNK + pl * 16;
            if (pl == 0) mbar_wait(bar_go + 8, 0);
            __syncwarp();
            const int role = s_item[NST];
            if (role < ND) {
                const unsigned char* src = (const unsigned char*)(wo + (size_t)(role >> 3) * WO_ROWS * DM + (role & 7) * 80) + (pl & 1) * 128;
                if (AUXW & 1) {
#pragma unroll 4
                    for (int r = pl >> 1; r < WO_ROWS; r += 16) l2_warm(junk, src + (size_t)r * (DM * 2));
                }
            } else if (role < ND + NE) {
                const unsigned char* src = (const unsigned char*)(((pl & 1) ? w_up : w_gate) + (role - ND) * 32);
                if (AUXW & 2) {
#pragma unroll 4
                    for (int r = pl >> 1; r < DM; r += 16) l2_warm(junk, src + (size_t)r * (FF * 2));
                }
            } else if (role < ND + NE + NF) {
                const unsigned char* src = (const unsigned char*)(w_down + (role - ND - NE) * 32);
                if (AUXW & 4) {
#pragma unroll 4
                    for (int r = pl; r < FF; r += 32) l2_warm(junk, src + (size_t)r * (DM * 2));
                }
            }
            cp_async_wait_all();
        }
        return;
    }

    const int lane = tid & 31, warp = tid >> 5;
    float* s_part = (float*)(smem + SM_PART);
    float* s_xp = (float*)(smem + SM_XP);
    float* s_red = (float*)(smem + SM_RED);
    const int lrow = tid >> 6, lcol = (tid & 63) * 10;
    uint32_t* h_dst = (uint32_t*)(smem + SM_A + lrow * A_PITCH + lcol * 2);

    PROF(0);
    const unsigned int ep = ld_acquire(&g_epoch) + 1u;
    const unsigned int target = ep * gridDim.x, tag16 = ep & 0xffffu;
    const unsigned long long* mod_row = g_mod + (lrow * MODN + lcol) / 2;
    float nv[10];
    {
        const int i1 = tid + NCONS;
        const uint4 c0 = __ldg((const uint4*)cvec + tid);
        uint4 c1 = c0;
        if (i1 < 320) c1 = __ldg((const uint4*)cvec + i1);
        uint32_t xw[5];
#pragma unroll
        for (int i = 0; i < 5; ++i) xw[i] = __ldg((const uint32_t*)(x_in + lrow * DM + lcol) + i);
        if (cta < MODN / 32) stage_rows(sbase + SM_W32, P32, w_mod + cta * 32, MODN * 2, DM, 4, tid, NCONS);
        cp_async_commit();
        if (cta < QN / 48) stage_rows(sbase + SM_WQ, P48, wq + cta * 48, QN * 2, DM, 6, tid, NCONS);
        cp_async_commit();
        if (PSTART == 1 && tid == 0) mbar_arrive(bar_go);
#pragma unroll 1
        for (int r = 0; r < 2; ++r) {
            const int i = r ? i1 : tid;
            if (i < 320) {
                const uint4 cc = r ? c1 : c0;
                const uint32_t cw[4] = {cc.x, cc.y, cc.z, cc.w};
                uint32_t ow[4];
#pragma unroll
                for (int k = 0; k < 4; ++k) {
                    const float a = bf_lo(cw[k]), b = bf_hi(cw[k]);
                    __nv_bfloat162 p = __floats2bfloat162_rn(__fdiv_rn(a, 1.0f + __expf(-a)), __fdiv_rn(b, 1.0f + __expf(-b)));
                    ow[k] = *(uint32_t*)&p;
                }
                const int b = i / 80, c8 = i - b * 80;
                *(uint4*)(smem + SM_A + b * A_PITCH + c8 * 16) = make_uint4(ow[0], ow[1], ow[2], ow[3]);
            }
        }
#pragma unroll
        for (int i = 0; i < 5; ++i) {
            nv[2 * i] = bf_lo(xw[i]);
            nv[2 * i + 1] = bf_hi(xw[i]);
            *(float2*)(s_xp + lrow * DM + lcol + 2 * i) = make_float2(nv[2 * i], nv[2 * i + 1]);
        }
    }
    float* acc_o = g_o[ep & 1];
    float* acc_attn = g_attn[ep & 1];
    if (cta == gridDim.x - 1) {
#pragma unroll 1
        for (int i = tid; i < NB * QN / 4; i += NCONS) ((float4*)g_o[~ep & 1])[i] = make_float4(0.f, 0.f, 0.f, 0.f);
#pragma unroll 1
        for (int i = tid; i < NB * DM; i += NCONS) g_attn[~ep & 1][i] = 0.f;
    }
    ln_norm(nv, s_red, tid);
    cp_async_wait1();
    cons_sync();
    if (PSTART == 0 && tid == 0) mbar_arrive(bar_go);
    if (cta < MODN / 32) {
        gemv_mma<5, 2>(sbase + SM_W32 + warp * 80 * P32, P32, sbase + SM_A + warp * 160, A_PITCH, s_part + warp * 320, lane);
        cons_sync();
        if (tid < 64) {
            const int b = tid >> 4, n = (tid & 15) * 2;
            ll_store(g_mod + (b * MODN + cta * 32 + n) / 2, tall_sum(s_part, b, n), tall_sum(s_part, b, n + 1), ep);
        }
    }
    PROF(1);

    if (cta < QN / 48) {
        cp_async_wait_all();
        cons_sync();
        if (PSTART == 2 && tid == 0) mbar_arrive(bar_go);
        uint32_t fq[5][3][4];
        frag_load<5, 3>(fq, sbase + SM_WQ + warp * 80 * P48, P48, lane);
        {
            long long t0 = 0;
            for (;;) {
                bool ok = true;
#pragma unroll
                for (int r = 0; r < 5; ++r) {
                    const int i = tid + r * NCONS, b = i / 320, c4 = i - b * 320;
                    const uint4 v = ll_ld2(g_mod + b * (MODN / 2) + 2 * c4);
                    *(uint2*)(s_part + b * DM + 2 * c4) = make_uint2(v.x, v.z);
                    ok = ok && v.y == ep && v.w == ep;
                }
                if (ok) break;
                if (t0 == 0) t0 = clock64();
                else if (clock64() - t0 > WAIT_LIMIT_CYCLES) __trap();
            }
        }
        cons_sync();
        PROF(2);
        uint32_t sh[5], sc[5];
#pragma unroll
        for (int i = 0; i < 5; ++i) {
            sh[i] = ((const uint32_t*)s_part)[lrow * DM + lcol / 2 + i];
            sc[i] = ((const uint32_t*)s_part)[lrow * DM + DM / 2 + lcol / 2 + i];
        }
        modulate(nv, sh, sc, h_dst);
        cons_sync();
        frag_mma<5, 3>(fq, sbase + SM_A + warp * 160, A_PITCH, s_part + warp * 320, lane);
        cons_sync();
        if (tid < 96) {
            const int b = tid / 24, n = (tid - b * 24) * 2;
            ll_store(g_q + (b * QN + cta * 48 + n) / 2, tall_sum(s_part, b, n), tall_sum(s_part, b, n + 1), ep);
        }
    } else if (PSTART == 2 && tid == 0) {
        mbar_arrive(bar_go);
    }
    PROF(3);
    if (tid == 0 && (!HAND_EARLY || cta >= QN / 48)) {
#pragma unroll 1
        for (int s = PRE; s < NST; ++s) mbar_arrive(bar_empty + s * 8);
    }
    uint32_t m_ga[5], m_sb[5], m_cb[5];
    PROF(4);

    {
        const int sub = lane & 7, grp = lane >> 3;
        for (int u0 = warp * TPI;; u0 += 8 * TPI) {
            if (s_tag[u0 % NST] != u0) tag_wait_slow(s_tag + u0 % NST, u0);
            const int idx = s_item[u0 % NST];
            const int jsm = idx - (NITEM - SMALL_R);
            const bool small = jsm >= 0;
            const int item = small ? NITEM - SMALL_R + (jsm >> 1) : idx;
            if ((u0 >= 8 * TPI && u0 < 16 * TPI) || (item < 0 && u0 < 8 * TPI)) {
                ll_get(mod_row + DM, m_ga, ep);
                ll_get(mod_row + 3 * DM / 2, m_sb, ep);
                ll_get(mod_row + 2 * DM, m_cb, ep);
            }
            if (item < 0) {
                mbar_wait(bar_full + (u0 % NST) * 8, (u0 / NST) & 1);
                __syncwarp();
                if (lane == 0) mbar_arrive(bar_empty + (u0 % NST) * 8);
                break;
            }
            const int bh = (item & (NITEM_K - 1)) / CHUNKS;
            if (item < NITEM_K) {
                unsigned int* gs = g_s + (size_t)item * ITEM_KEYS;
                float qr[24];
                {
                    const unsigned long long* qp = g_q + ((bh >> 5) * QN + (bh & 31) * DH) / 2 + sub * 4;
                    long long t0 = 0;
                    for (;;) {
                        bool ok = true;
#pragma unroll
                        for (int j = 0; j < 6; ++j) {
                            const uint4 v = ll_ld2(qp + (j >> 1) * 32 + (j & 1) * 2);
                            qr[j * 4 + 0] = bf_lo(v.x); qr[j * 4 + 1] = bf_hi(v.x);
                            qr[j * 4 + 2] = bf_lo(v.z); qr[j * 4 + 3] = bf_hi(v.z);
                            ok = ok && v.y == ep && v.w == ep;
                        }
                        if (ok) break;
                        if (t0 == 0) t0 = clock64();
                        else if (clock64() - t0 > WAIT_LIMIT_CYCLES) __trap();
                    }
                }
                float m_run = -INFINITY, l_run = 0.f;
#pragma unroll 1
                for (int hh = 0; hh < 2 * TPI; ++hh) {
                    const int u = u0 + (hh >> 1), st = u % NST;
                    if (!(hh & 1)) stage_wait(bar_full, s_tag, u);
                    const uint4* tile = (const uint4*)(smem + SM_RING + st * STAGE_BYTES) + (hh & 1) * (32 * 24);
                    float part[8];
#pragma unroll
                    for (int it = 0; it < 8; ++it) {
                        const uint4* row = tile + (it * 4 + grp) * 24 + sub;
                        const uint4 a = row[0], b = row[8], c = row[16];
                        part[it] = dot8(a, qr) + dot8(b, qr + 8) + dot8(c, qr + 16);
                    }
                    if (hh & 1) {
                        __syncwarp();
                        if (lane == 0) mbar_arrive(bar_empty + st * 8);
                    }
#pragma unroll
                    for (int j = 0; j < 4; ++j) {
                        const float send = (sub & 4) ? part[j] : part[j + 4];
                        const float keep = (sub & 4) ? part[j + 4] : part[j];
                        part[j] = keep + __shfl_xor_sync(0xffffffffu, send, 4);
                    }
#pragma unroll
                    for (int j = 0; j < 2; ++j) {
                        const float send = (sub & 2) ? part[j] : part[j + 2];
                        const float keep = (sub & 2) ? part[j + 2] : part[j];
                        part[j] = keep + __shfl_xor_sync(0xffffffffu, send, 2);
                    }
                    {
                        const float send = (sub & 1) ? part[0] : part[1];
                        const float keep = (sub & 1) ? part[1] : part[0];
                        part[0] = keep + __shfl_xor_sync(0xffffffffu, send, 1);
                    }
                    const float s = bf16r(bf16r(part[0]) * 0.07216878364870323f);
                    asm volatile("st.relaxed.gpu.global.u32 [%0], %1;" ::"l"(gs + hh * 32 + sub * 4 + grp), "r"(__float_as_uint(s) | tag16) : "memory");
                    const float m_new = fmaxf(m_run, s);
                    l_run = l_run * __expf(m_run - m_new) + __expf(s - m_new);
                    m_run = m_new;
                }
                const float m = warp_max(m_run);
                const float l = warp_sum(l_run * __expf(m_run - m));
                if (lane == 0)
                    asm volatile("st.relaxed.gpu.global.u64 [%0], %1;" ::"l"(g_stat + item),
                                 "l"(((unsigned long long)__float_as_uint(l) << 32) | (__float_as_uint(m) | tag16)) : "memory");
            } else {
                float pr[2 * TPI];
                {
                    const unsigned int* gs = g_s + (size_t)(item - NITEM_K) * ITEM_KEYS + lane + (small ? (jsm & 1) * TILE_KEYS : 0);
                    uint2 st2;
                    long long t0 = 0;
                    for (;;) {
                        st2 = ll_ld1(g_stat + bh * CHUNKS + lane);
                        bool ok = (st2.x & 0xffffu) == tag16;
#pragma unroll
                        for (int hh = 0; hh < 2 * TPI; ++hh) {
                            unsigned int w;
                            asm volatile("ld.relaxed.gpu.global.u32 %0, [%1];" : "=r"(w) : "l"(gs + (small ? (hh >> 1) * 32 : hh * 32)) : "memory");
                            ok = ok && (w & 0xffffu) == tag16;
                            pr[hh] = bf_hi(w);
                        }
                        if (__all_sync(0xffffffffu, ok)) break;
                        if (t0 == 0) t0 = clock64();
                        else if (clock64() - t0 > WAIT_LIMIT_CYCLES) __trap();
                    }
                    const float mi = bf_hi(st2.x);
                    const float mm = warp_max(mi);
                    const float ll = warp_sum(__uint_as_float(st2.y) * __expf(mi - mm));
#pragma unroll
                    for (int hh = 0; hh < 2 * TPI; ++hh) pr[hh] = bf16r(__fdiv_rn(__expf(pr[hh] - mm), ll));
                }
                float acc[3][8];
#pragma unroll
                for (int j = 0; j < 3; ++j)
#pragma unroll
                    for (int e = 0; e < 8; ++e) acc[j][e] = 0.f;
#pragma unroll
                for (int hh = 0; hh < 2 * TPI; ++hh) {
                    const int u = u0 + (hh >> 1), st = u % NST;
                    if (!(hh & 1)) stage_wait(bar_full, s_tag, u);
                    const uint4* tile = (const uint4*)(smem + SM_RING + st * STAGE_BYTES) + (hh & 1) * (32 * 24);
                    if (!(small && (hh & 1))) {
#pragma unroll
                        for (int it = 0; it < 8; ++it) {
                            const uint4* row = tile + (it * 4 + grp) * 24 + sub;
                            const uint4 a = row[0], b = row[8], c = row[16];
                            const float p = __shfl_sync(0xffffffffu, pr[hh], it * 4 + grp);
                            fma8(acc[0], a, p);
                            fma8(acc[1], b, p);
                            fma8(acc[2], c, p);
                        }
                    }
                    if (hh & 1) {
                        __syncwarp();
                        if (lane == 0) mbar_arrive(bar_empty + st * 8);
                    }
                }
                float* go = acc_o + (bh >> 5) * QN + (bh & 31) * DH + sub * 8;
#pragma unroll
                for (int j = 0; j < 3; ++j) {
#pragma unroll
                    for (int e = 0; e < 8; ++e) {
                        float v = acc[j][e];
                        v += __shfl_xor_sync(0xffffffffu, v, 8);
                        v += __shfl_xor_sync(0xffffffffu, v, 16);
                        acc[j][e] = v;
                    }
                    if (grp == 0) {
                        red_add_v4(go + j * 64, acc[j][0], acc[j][1], acc[j][2], acc[j][3]);
                        red_add_v4(go + j * 64 + 4, acc[j][4], acc[j][5], acc[j][6], acc[j][7]);
                    }
                }
            }
        }
    }
    PROF(5);
    grid_arrive(&g_bar[2], tid);
    PROF(6);
#pragma unroll 1
    for (int role = s_item[NST]; role < ND + NE + NF; role += (int)gridDim.x) {
        if (role < ND) {
            const int ks = role >> 3, ns = role & 7;
            if (tid < 240) {
                const int r0 = tid / 10, c = tid - r0 * 10;
                const unsigned char* src = (const unsigned char*)(wo + ((size_t)ks * WO_ROWS + r0) * DM + ns * 80) + c * 16;
                const uint32_t dst = sbase + SM_WO + r0 * P80 + c * 16;
#pragma unroll
                for (int i = 0; i < WO_ROWS / 24; ++i) cp_async16(dst + i * 24 * P80, src + (size_t)i * 24 * DM * 2);
            }
            uint32_t fd[6][5][4];
            cp_async_wait_all();
            cons_sync();
            frag_load<6, 5>(fd, sbase + SM_WO + warp * 96 * P80, P80, lane);
            grid_wait(&g_bar[2], target, tid);
            if (role == 0 && tid == 0) { g_work = 0u; g_epoch = ep; }
            PROF(7);
            {
                float4 v[3];
#pragma unroll
                for (int r = 0; r < 3; ++r) {
                    const int i = tid + r * NCONS, b = i / 192, c4 = i - b * 192;
                    v[r] = __ldcg((const float4*)(acc_o + b * QN + ks * WO_ROWS) + c4);
                }
#pragma unroll
                for (int r = 0; r < 3; ++r) {
                    const int i = tid + r * NCONS, b = i / 192, c4 = i - b * 192;
                    __nv_bfloat162 p0 = __floats2bfloat162_rn(v[r].x, v[r].y), p1 = __floats2bfloat162_rn(v[r].z, v[r].w);
                    *(uint2*)(smem + SM_ACT + b * ACT_PITCH + c4 * 8) = make_uint2(*(uint32_t*)&p0, *(uint32_t*)&p1);
                }
            }
            cons_sync();
            frag_mma<6, 5>(fd, sbase + SM_ACT + warp * 192, ACT_PITCH, s_part + warp * 320, lane);
            cons_sync();
            if (tid < 80) {
                const int b = tid / 20, n4 = tid - b * 20;
                float4 s4 = make_float4(0.f, 0.f, 0.f, 0.f);
#pragma unroll
                for (int w = 0; w < 8; ++w) {
                    const float4 v = *(const float4*)(s_part + (w * 4 + b) * 80 + n4 * 4);
                    s4.x += v.x; s4.y += v.y; s4.z += v.z; s4.w += v.w;
                }
                red_add_v4(acc_attn + b * DM + ns * 80 + n4 * 4, s4.x, s4.y, s4.z, s4.w);
            }
            PROF(8);
            grid_arrive(&g_bar[3], tid);
        } else if (role < ND + NE) {
            const int ec = (role - ND) * 32;
            {
                const unsigned char* src = (const unsigned char*)(((tid & 4) ? w_up : w_gate) + (size_t)(tid >> 3) * FF + ec) + (tid & 3) * 16;
                const uint32_t dst = sbase + SM_WG + (tid >> 3) * P64 + (tid & 7) * 16;
#pragma unroll
                for (int i = 0; i < DM / 32; ++i) cp_async16(dst + i * 32 * P64, src + (size_t)i * 32 * FF * 2);
            }
            uint32_t fe[5][4][4];
            cp_async_wait_all();
            cons_sync();
            frag_load<5, 4>(fe, sbase + SM_WG + warp * 80 * P64, P64, lane);
            grid_wait(&g_bar[3], ep * ND, tid);
            PROF(9);
            {
                float4 v[3];
#pragma unroll
                for (int r = 0; r < 3; ++r)
                    if (tid + r * NCONS < NB * DM / 4) v[r] = __ldcg((const float4*)acc_attn + tid + r * NCONS);
#pragma unroll
                for (int r = 0; r < 3; ++r)
                    if (tid + r * NCONS < NB * DM / 4) ((float4*)s_part)[tid + r * NCONS] = v[r];
            }
            cons_sync();
#pragma unroll
            for (int i = 0; i < 5; ++i) {
                const float2 av = *((const float2*)(s_part + lrow * DM + lcol) + i);
                const float2 xv = *((const float2*)(s_xp + lrow * DM + lcol) + i);
                nv[2 * i] = bf16r(xv.x + bf16r(bf_lo(m_ga[i]) * bf16r(av.x)));
                nv[2 * i + 1] = bf16r(xv.y + bf16r(bf_hi(m_ga[i]) * bf16r(av.y)));
            }
            ln_norm(nv, s_red, tid);
            modulate(nv, m_sb, m_cb, h_dst);
            cons_sync();
            frag_mma<5, 4>(fe, sbase + SM_A + warp * 160, A_PITCH, s_part + warp * 320, lane);
            cons_sync();
            if (tid < 64) {
                const int b = tid >> 4, n = (tid & 15) * 2;
                const float g0 = bf16r(tall_sum(s_part, b, n)), g1 = bf16r(tall_sum(s_part, b, n + 1));
                const float u0 = bf16r(tall_sum(s_part, b, 32 + n)), u1 = bf16r(tall_sum(s_part, b, 33 + n));
                ll_store(g_act + (b * FF + ec + n) / 2, bf16r(gelu_tanh(g0)) * u0, bf16r(gelu_tanh(g1)) * u1, ep);
            }
            PROF(10);
        } else {
            const int fc = (role - ND - NE) * 32;
            {
                const unsigned char* src = (const unsigned char*)(w_down + (size_t)(tid >> 2) * DM + fc) + (tid & 3) * 16;
                const uint32_t dst = sbase + SM_WD + (tid >> 2) * P32 + (tid & 3) * 16;
#pragma unroll
                for (int i = 0; i < FF / 64; ++i) cp_async16(dst + i * 64 * P32, src + (size_t)i * 64 * DM * 2);
            }
            uint32_t m_fa[1] = {0u}, m_fb[1] = {0u};
            if (tid < 64) {
                ll_get(g_mod + ((tid >> 4) * MODN + 2 * DM + fc) / 2 + (tid & 15), m_fa, ep);
                ll_get(g_mod + ((tid >> 4) * MODN + 5 * DM + fc) / 2 + (tid & 15), m_fb, ep);
            }
            uint32_t ff[12][2][4];
            cp_async_wait_all();
            cons_sync();
            frag_load<12, 2>(ff, sbase + SM_WD + warp * 192 * P32, P32, lane);
            grid_wait(&g_bar[3], ep * ND, tid);
            float x10 = 0.f, x11 = 0.f;
            if (tid < 64) {
                const int b = tid >> 4, col = fc + (tid & 15) * 2;
                const float2 av = __ldcg((const float2*)(acc_attn + b * DM + col));
                x10 = bf16r(s_xp[b * DM + col] + bf16r(bf_lo(m_fa[0]) * bf16r(av.x)));
                x11 = bf16r(s_xp[b * DM + col + 1] + bf16r(bf_hi(m_fa[0]) * bf16r(av.y)));
            }
            long long t0 = 0;
            for (;;) {
                bool ok = true;
#pragma unroll
                for (int r = 0; r < 6; ++r) {
                    const int i = tid + r * NCONS, b = i / 384, c4 = i - b * 384;
                    const uint4 v = ll_ld2(g_act + 2 * i);
                    *(uint2*)(smem + SM_ACT + b * ACT_PITCH + c4 * 8) = make_uint2(v.x, v.z);
                    ok = ok && v.y == ep && v.w == ep;
                }
                if (ok) break;
                if (t0 == 0) t0 = clock64();
                else if (clock64() - t0 > WAIT_LIMIT_CYCLES) __trap();
            }
            cons_sync();
            PROF(11);
            frag_mma<12, 2>(ff, sbase + SM_ACT + warp * 384, ACT_PITCH, s_part + warp * 320, lane);
            cons_sync();
            if (tid < 64) {
                const int b = tid >> 4, n = (tid & 15) * 2;
                const float f0 = bf16r(tall_sum(s_part, b, n)), f1 = bf16r(tall_sum(s_part, b, n + 1));
                *(__nv_bfloat162*)(out + b * DM + fc + n) =
                    __floats2bfloat162_rn(x10 + bf16r(bf_lo(m_fb[0]) * f0), x11 + bf16r(bf_hi(m_fb[0]) * f1));
            }
            PROF(12);
        }
        cons_sync();
    }
}

}

extern "C" void kernel_launch(void* const* d_in, const int* in_sizes, int n_in, void* d_out, int out_size) {
    (void)in_sizes; (void)n_in; (void)out_size;
    const __nv_bfloat16* A_x = (const __nv_bfloat16*)d_in[0];
    const __nv_bfloat16* A_k = (const __nv_bfloat16*)d_in[1];
    const __nv_bfloat16* A_v = (const __nv_bfloat16*)d_in[2];
    const __nv_bfloat16* A_wq = (const __nv_bfloat16*)d_in[3];
    const __nv_bfloat16* A_wo = (const __nv_bfloat16*)d_in[4];
    const __nv_bfloat16* B_wg = (const __nv_bfloat16*)d_in[6];
    const __nv_bfloat16* B_wu = (const __nv_bfloat16*)d_in[7];
    const __nv_bfloat16* B_wd = (const __nv_bfloat16*)d_in[8];
    const __nv_bfloat16* c = (const __nv_bfloat16*)d_in[9];
    const __nv_bfloat16* w_mod = (const __nv_bfloat16*)d_in[10];
    static int grid = 0;
    if (grid == 0) {
        cudaFuncSetAttribute(decode_block_kernel, cudaFuncAttributeMaxDynamicSharedMemorySize, SM_TOTAL);
        int dev = 0, sms = 0;
        cudaGetDevice(&dev);
        cudaDeviceGetAttribute(&sms, cudaDevAttrMultiProcessorCount, dev);
        grid = sms < 132 ? sms : 132;
    }
    decode_block_kernel<<<grid, NTHREADS, SM_TOTAL>>>(A_x, A_k, A_v, A_wq, A_wo, B_wg, B_wu, B_wd, c, w_mod,
                                                      (__nv_bfloat16*)d_out);
}
```

```cpp
#include <cuda_runtime.h>
#include <cuda_bf16.h>
#include <stdint.h>

namespace {

constexpr int NB = 4;
constexpr int DM = 640;
constexpr int NH = 32;
constexpr int SK = 4096;
constexpr int DH = 192;
constexpr int FF = 1536;
constexpr int MODN = 6 * DM;
constexpr int QN = NH * DH;
constexpr int NBH = NB * NH;

constexpr int NCONS = 256;
constexpr int NTHREADS = NCONS + 32;
constexpr int TILE_KEYS = 64;
constexpr int TILE_BYTES = TILE_KEYS * DH * 2;
constexpr int STAGE_BYTES = TILE_BYTES;
constexpr int NST = 6;
constexpr int PRE = 3;
constexpr int TPI = 2;
constexpr int ITEM_KEYS = TPI * TILE_KEYS;
constexpr int CHUNKS = SK / ITEM_KEYS;
constexpr int NITEM_K = NBH * CHUNKS;
constexpr int NITEM = 2 * NITEM_K;

constexpr int A_PITCH = 1296;
constexpr int ACT_PITCH = FF * 2 + 16;
constexpr int P32 = 80;
constexpr int P48 = 112;
constexpr int PROW = DM * 2 + 16;
constexpr int WO_ROWS = 16 * NST;
constexpr int ND = QN / WO_ROWS;

constexpr int SM_RING = 0;
constexpr int SM_WQ = PRE * STAGE_BYTES;
constexpr int SM_WD = 0;
constexpr int SM_W32 = NST * STAGE_BYTES;
constexpr int SM_ACT = SM_W32;
constexpr int SM_A = SM_W32 + DM * P32;
constexpr int SM_PART = SM_A + NB * A_PITCH;
constexpr int SM_XP = SM_PART + 8 * 4 * 80 * 4;
constexpr int SM_RED = SM_XP + NB * DM * 4;
constexpr int SM_ITEM = SM_RED + 16 * 4;
constexpr int SM_TAG = SM_ITEM + 16 * 4;
constexpr int SM_BAR = SM_TAG + 16 * 4;
constexpr int SM_TOTAL = SM_BAR + (2 * NST + 2) * 8;
static_assert(SM_WQ + DM * P48 <= NST * STAGE_BYTES, "prologue overlay");
static_assert(SM_WD + FF * P32 <= NST * STAGE_BYTES && 16 * PROW <= STAGE_BYTES, "tail overlay");
static_assert(SM_TOTAL <= 232448, "smem");
#define THR_ITEMS 6
#define THR_DEPTH 3
#define HAND_EARLY 0
#define PSTART 0

__device__ __align__(128) unsigned long long g_mod[NB * MODN / 2];
__device__ __align__(128) unsigned long long g_q[NB * QN / 2];
__device__ __align__(128) unsigned long long g_act[NB * FF / 2];
__device__ __align__(128) unsigned int g_s[NBH * SK];
__device__ __align__(128) unsigned long long g_stat[NBH * CHUNKS];
__device__ __align__(128) float g_o[2][NB * QN];
__device__ __align__(128) float g_attn[2][NB * DM];
__device__ __align__(128) unsigned int g_bar[8];
__device__ unsigned int g_work;
__device__ unsigned int g_epoch;

#define PROF(k) do { } while (0)
#define PROFP(k) do { } while (0)

__device__ __forceinline__ float bf16r(float x) { return __bfloat162float(__float2bfloat16_rn(x)); }
__device__ __forceinline__ float bf_lo(uint32_t u) { return __uint_as_float(u << 16); }
__device__ __forceinline__ float bf_hi(uint32_t u) { return __uint_as_float(u & 0xffff0000u); }

__device__ __forceinline__ uint32_t smem_u32(const void* p) { return (uint32_t)__cvta_generic_to_shared(p); }
__device__ __forceinline__ void mbar_init(uint32_t bar, uint32_t count) {
    asm volatile("mbarrier.init.shared::cta.b64 [%0], %1;" ::"r"(bar), "r"(count) : "memory");
}
__device__ __forceinline__ void mbar_expect_tx(uint32_t bar, uint32_t bytes) {
    asm volatile("mbarrier.arrive.expect_tx.shared::cta.b64 _, [%0], %1;" ::"r"(bar), "r"(bytes) : "memory");
}
__device__ __forceinline__ void mbar_arrive(uint32_t bar) {
    asm volatile("mbarrier.arrive.shared::cta.b64 _, [%0];" ::"r"(bar) : "memory");
}
constexpr long long WAIT_LIMIT_CYCLES = 200000000LL;
__device__ __forceinline__ uint32_t mbar_try(uint32_t bar, uint32_t parity) {
    uint32_t done;
    asm volatile(
        "{\n\t.reg .pred p;\n\t"
        "mbarrier.try_wait.parity.shared::cta.b64 p, [%1], %2;\n\t"
        "selp.u32 %0, 1, 0, p;\n\t}"
        : "=r"(done) : "r"(bar), "r"(parity) : "memory");
    return done;
}
__device__ __noinline__ void mbar_wait_slow(uint32_t bar, uint32_t parity) {
    const long long t0 = clock64();
    while (!mbar_try(bar, parity)) {
        if (clock64() - t0 > WAIT_LIMIT_CYCLES) __trap();
    }
}
__device__ __forceinline__ void mbar_wait(uint32_t bar, uint32_t parity) {
    if (!mbar_try(bar, parity)) mbar_wait_slow(bar, parity);
}
__device__ __noinline__ void tag_wait_slow(volatile int* tag, int u) {
    const long long t0 = clock64();
    while (*tag != u) {
        __nanosleep(32);
        if (clock64() - t0 > WAIT_LIMIT_CYCLES) __trap();
    }
}
__device__ __noinline__ bool tag_wait_stop(volatile int* tag, int u, volatile int* stop) {
    const long long t0 = clock64();
    while (*tag != u) {
        if (*stop <= u) return false;
        __nanosleep(32);
        if (clock64() - t0 > WAIT_LIMIT_CYCLES) __trap();
    }
    return true;
}
__device__ __forceinline__ void stage_wait(uint32_t bar_full, volatile int* s_tag, int u) {
    const int st = u % NST;
    if (s_tag[st] != u) tag_wait_slow(s_tag + st, u);
    mbar_wait(bar_full + st * 8, (u / NST) & 1);
}
__device__ __forceinline__ void bulk_g2s(uint32_t dst, const void* src, uint32_t bytes, uint32_t bar, uint64_t pol) {
    asm volatile(
        "cp.async.bulk.shared::cluster.global.mbarrier::complete_tx::bytes.L2::cache_hint [%0], [%1], %2, [%3], %4;"
        ::"r"(dst), "l"(src), "r"(bytes), "r"(bar), "l"(pol) : "memory");
}
__device__ __forceinline__ void cp_async16(uint32_t dst, const void* src) {
    asm volatile("cp.async.cg.shared.global [%0], [%1], 16;" ::"r"(dst), "l"(src) : "memory");
}
__device__ __forceinline__ void cp_async_wait_all() { asm volatile("cp.async.wait_all;" ::: "memory"); }
__device__ __forceinline__ void cp_async_commit() { asm volatile("cp.async.commit_group;" ::: "memory"); }
__device__ __forceinline__ void cp_async_wait1() { asm volatile("cp.async.wait_group 1;" ::: "memory"); }
__device__ __forceinline__ void red_release_add(unsigned int* p, unsigned int v) {
    asm volatile("red.release.gpu.global.add.u32 [%0], %1;" ::"l"(p), "r"(v) : "memory");
}
__device__ __forceinline__ void cons_sync() { asm volatile("bar.sync 1, 256;" ::: "memory"); }

__device__ __forceinline__ void red_add_v4(float* p, float a, float b, float c, float d) {
    asm volatile("red.global.add.v4.f32 [%0], {%1, %2, %3, %4};" ::"l"(p), "f"(a), "f"(b), "f"(c), "f"(d) : "memory");
}
__device__ __forceinline__ unsigned int ld_acquire(const unsigned int* p) {
    unsigned int v;
    asm volatile("ld.acquire.gpu.global.u32 %0, [%1];" : "=r"(v) : "l"(p) : "memory");
    return v;
}
__device__ __forceinline__ void ll_store(unsigned long long* p, float a, float b, unsigned int ep) {
    __nv_bfloat162 v = __floats2bfloat162_rn(a, b);
    const unsigned long long w = ((unsigned long long)ep << 32) | *(uint32_t*)&v;
    asm volatile("st.relaxed.gpu.global.u64 [%0], %1;" ::"l"(p), "l"(w) : "memory");
}
__device__ __forceinline__ uint2 ll_ld1(const unsigned long long* p) {
    unsigned long long w;
    asm volatile("ld.relaxed.gpu.global.u64 %0, [%1];" : "=l"(w) : "l"(p) : "memory");
    return make_uint2((uint32_t)w, (uint32_t)(w >> 32));
}
__device__ __forceinline__ uint4 ll_ld2(const unsigned long long* p) {
    unsigned long long a, b;
    asm volatile("ld.relaxed.gpu.global.v2.u64 {%0, %1}, [%2];" : "=l"(a), "=l"(b) : "l"(p) : "memory");
    return make_uint4((uint32_t)a, (uint32_t)(a >> 32), (uint32_t)b, (uint32_t)(b >> 32));
}
template <int N>
__device__ __forceinline__ void ll_get(const unsigned long long* p, uint32_t (&d)[N], unsigned int ep) {
    long long t0 = 0;
    for (;;) {
        bool ok = true;
#pragma unroll
        for (int i = 0; i < N; ++i) {
            const uint2 v = ll_ld1(p + i);
            d[i] = v.x;
            ok = ok && (v.y == ep);
        }
        if (ok) break;
        if (t0 == 0) t0 = clock64();
        else if (clock64() - t0 > WAIT_LIMIT_CYCLES) __trap();
    }
}

__device__ __forceinline__ void grid_arrive(unsigned int* ctr, int tid) {
    cons_sync();
    if (tid == 0) red_release_add(ctr, 1u);
}
__device__ __noinline__ void grid_wait(const unsigned int* ctr, unsigned int target, int tid) {
    if (tid == 0) {
        const long long t0 = clock64();
        while ((int)(ld_acquire(ctr) - target) < 0) {
            if (clock64() - t0 > WAIT_LIMIT_CYCLES) __trap();
        }
    }
    cons_sync();
}

__device__ __forceinline__ float warp_sum(float v) {
#pragma unroll
    for (int o = 16; o > 0; o >>= 1) v += __shfl_xor_sync(0xffffffffu, v, o);
    return v;
}
__device__ __forceinline__ float warp_max(float v) {
#pragma unroll
    for (int o = 16; o > 0; o >>= 1) v = fmaxf(v, __shfl_xor_sync(0xffffffffu, v, o));
    return v;
}

__device__ __forceinline__ void fma8(float (&acc)[8], const uint4& w, float s) {
    acc[0] = fmaf(s, bf_lo(w.x), acc[0]);
    acc[1] = fmaf(s, bf_hi(w.x), acc[1]);
    acc[2] = fmaf(s, bf_lo(w.y), acc[2]);
    acc[3] = fmaf(s, bf_hi(w.y), acc[3]);
    acc[4] = fmaf(s, bf_lo(w.z), acc[4]);
    acc[5] = fmaf(s, bf_hi(w.z), acc[5]);
    acc[6] = fmaf(s, bf_lo(w.w), acc[6]);
    acc[7] = fmaf(s, bf_hi(w.w), acc[7]);
}
__device__ __forceinline__ float dot8(const uint4& w, const float* q) {
    float s = q[0] * bf_lo(w.x);
    s = fmaf(q[1], bf_hi(w.x), s);
    s = fmaf(q[2], bf_lo(w.y), s);
    s = fmaf(q[3], bf_hi(w.y), s);
    s = fmaf(q[4], bf_lo(w.z), s);
    s = fmaf(q[5], bf_hi(w.z), s);
    s = fmaf(q[6], bf_lo(w.w), s);
    s = fmaf(q[7], bf_hi(w.w), s);
    return s;
}

__device__ __noinline__ void stage_rows(uint32_t dst, int dst_pitch, const void* src, int src_stride, int rows,
                                        int cpr, int tid, int nthr) {
    const int n = rows * cpr;
#pragma unroll 1
    for (int i = tid; i < n; i += nthr) {
        const int r = i / cpr, c = i - r * cpr;
        cp_async16(dst + r * dst_pitch + c * 16, (const unsigned char*)src + (size_t)r * src_stride + c * 16);
    }
}

template <int KS, int NT>
__device__ __noinline__ void gemv_mma(uint32_t w, int w_pitch, uint32_t a, int a_pitch, float* part, int lane) {
    float c[NT][4];
#pragma unroll
    for (int nt = 0; nt < NT; ++nt) { c[nt][0] = 0.f; c[nt][1] = 0.f; c[nt][2] = 0.f; c[nt][3] = 0.f; }
    const uint32_t ap = a + (lane >> 2) * a_pitch + (lane & 3) * 4;
    const uint32_t wp = w + ((lane & 7) + ((lane >> 4) << 3)) * w_pitch + ((lane >> 3) & 1) * 16;
#pragma unroll
    for (int ks = 0; ks < KS; ++ks) {
        uint32_t b0 = 0, b1 = 0;
        if (lane < 16) {
            asm("ld.shared.u32 %0, [%1];" : "=r"(b0) : "r"(ap + ks * 32));
            asm("ld.shared.u32 %0, [%1];" : "=r"(b1) : "r"(ap + ks * 32 + 16));
        }
#pragma unroll
        for (int nt = 0; nt < NT; ++nt) {
            uint32_t a0, a1, a2, a3;
            asm("ldmatrix.sync.aligned.m8n8.x4.trans.shared.b16 {%0, %1, %2, %3}, [%4];"
                         : "=r"(a0), "=r"(a1), "=r"(a2), "=r"(a3) : "r"(wp + ks * 16 * w_pitch + nt * 32));
            asm("mma.sync.aligned.m16n8k16.row.col.f32.bf16.bf16.f32 {%0, %1, %2, %3}, {%4, %5, %6, %7}, "
                "{%8, %9}, {%0, %1, %2, %3};"
                : "+f"(c[nt][0]), "+f"(c[nt][1]), "+f"(c[nt][2]), "+f"(c[nt][3])
                : "r"(a0), "r"(a1), "r"(a2), "r"(a3), "r"(b0), "r"(b1));
        }
    }
    if ((lane & 3) < 2) {
        float* pp = part + (lane & 3) * 160 + (lane >> 2);
#pragma unroll
        for (int nt = 0; nt < NT; ++nt) {
            pp[nt * 16] = c[nt][0];
            pp[nt * 16 + 80] = c[nt][1];
            pp[nt * 16 + 8] = c[nt][2];
            pp[nt * 16 + 88] = c[nt][3];
        }
    }
}

template <int KS, int NT>
__device__ __forceinline__ void frag_load(uint32_t (&f)[KS][NT][4], uint32_t w, int w_pitch, int lane, int k_stride = 0) {
    if (k_stride == 0) k_stride = 16 * w_pitch;
    const uint32_t wp = w + ((lane & 7) + ((lane >> 4) << 3)) * w_pitch + ((lane >> 3) & 1) * 16;
#pragma unroll
    for (int ks = 0; ks < KS; ++ks)
#pragma unroll
        for (int nt = 0; nt < NT; ++nt)
            asm volatile("ldmatrix.sync.aligned.m8n8.x4.trans.shared.b16 {%0, %1, %2, %3}, [%4];"
                         : "=r"(f[ks][nt][0]), "=r"(f[ks][nt][1]), "=r"(f[ks][nt][2]), "=r"(f[ks][nt][3])
                         : "r"(wp + ks * k_stride + nt * 32) : "memory");
}
template <int KS, int NT>
__device__ __forceinline__ void frag_mma(const uint32_t (&f)[KS][NT][4], uint32_t a, int a_pitch, float* part, int lane) {
    float c[NT][4];
#pragma unroll
    for (int nt = 0; nt < NT; ++nt) { c[nt][0] = 0.f; c[nt][1] = 0.f; c[nt][2] = 0.f; c[nt][3] = 0.f; }
    const uint32_t ap = a + (lane >> 2) * a_pitch + (lane & 3) * 4;
    uint32_t b[KS][2];
#pragma unroll
    for (int ks = 0; ks < KS; ++ks) {
        b[ks][0] = 0; b[ks][1] = 0;
        if (lane < 16) {
            asm volatile("ld.shared.u32 %0, [%1];" : "=r"(b[ks][0]) : "r"(ap + ks * 32) : "memory");
            asm volatile("ld.shared.u32 %0, [%1];" : "=r"(b[ks][1]) : "r"(ap + ks * 32 + 16) : "memory");
        }
    }
#pragma unroll
    for (int ks = 0; ks < KS; ++ks)
#pragma unroll
        for (int nt = 0; nt < NT; ++nt)
            asm("mma.sync.aligned.m16n8k16.row.col.f32.bf16.bf16.f32 {%0, %1, %2, %3}, {%4, %5, %6, %7}, "
                "{%8, %9}, {%0, %1, %2, %3};"
                : "+f"(c[nt][0]), "+f"(c[nt][1]), "+f"(c[nt][2]), "+f"(c[nt][3])
                : "r"(f[ks][nt][0]), "r"(f[ks][nt][1]), "r"(f[ks][nt][2]), "r"(f[ks][nt][3]), "r"(b[ks][0]), "r"(b[ks][1]));
    if ((lane & 3) < 2) {
        float* pp = part + (lane & 3) * 160 + (lane >> 2);
#pragma unroll
        for (int nt = 0; nt < NT; ++nt) {
            pp[nt * 16] = c[nt][0];
            pp[nt * 16 + 80] = c[nt][1];
            pp[nt * 16 + 8] = c[nt][2];
            pp[nt * 16 + 88] = c[nt][3];
        }
    }
}

__device__ __forceinline__ float tall_sum(const float* part, int b, int n) {
    float s = 0.f;
#pragma unroll
    for (int w = 0; w < 8; ++w) s += part[(w * 4 + b) * 80 + n];
    return s;
}

__device__ __forceinline__ void ln_norm(float (&v)[10], float* s_red, int tid) {
    const int warp = tid >> 5;
    const float pv = __shfl_sync(0xffffffffu, v[0], 0);
    float s = 0.f, q = 0.f;
#pragma unroll
    for (int i = 0; i < 10; ++i) { const float d = v[i] - pv; s += d; q = fmaf(d, d, q); }
#pragma unroll
    for (int o = 16; o > 0; o >>= 1) {
        s += __shfl_xor_sync(0xffffffffu, s, o);
        q += __shfl_xor_sync(0xffffffffu, q, o);
    }
    const float md = s * (2.0f / DM);
    if ((tid & 31) == 0) *(float2*)(s_red + 2 * warp) = make_float2(pv + md, fmaxf(q - s * md, 0.f));
    cons_sync();
    const float4 r = *(const float4*)(s_red + 4 * (warp >> 1));
    const float dm = r.x - r.z;
    const float var = (r.y + r.w + dm * dm * (DM / 4)) * (1.0f / DM);
    const float mean = bf16r(0.5f * (r.x + r.z));
    const float inv = __fdiv_rn(1.0f, bf16r(sqrtf(bf16r(bf16r(var) + 1e-5f))));
#pragma unroll
    for (int i = 0; i < 10; ++i) v[i] = bf16r(bf16r(v[i] - mean) * inv);
}
__device__ __forceinline__ void modulate(const float (&n)[10], const uint32_t (&sh)[5], const uint32_t (&sc)[5], uint32_t* dst) {
#pragma unroll
    for (int i = 0; i < 5; ++i) {
        const float h0 = bf16r(n[2 * i] * bf16r(1.0f + bf_lo(sc[i]))) + bf_lo(sh[i]);
        const float h1 = bf16r(n[2 * i + 1] * bf16r(1.0f + bf_hi(sc[i]))) + bf_hi(sh[i]);
        __nv_bfloat162 p = __floats2bfloat162_rn(h0, h1);
        dst[i] = *(uint32_t*)&p;
    }
}

__device__ __forceinline__ float gelu_tanh(float x) {
    const float kBeta = 0.7978845608028654f;
    const float inner = kBeta * (x + 0.044715f * x * x * x);
    return 0.5f * x * (1.0f + tanhf(inner));
}

__global__ void __launch_bounds__(NTHREADS, 1)
decode_block_kernel(const __nv_bfloat16* __restrict__ x_in, const __nv_bfloat16* __restrict__ k_cache,
                    const __nv_bfloat16* __restrict__ v_cache, const __nv_bfloat16* __restrict__ wq,
                    const __nv_bfloat16* __restrict__ wo, const __nv_bfloat16* __restrict__ w_gate,
                    const __nv_bfloat16* __restrict__ w_up, const __nv_bfloat16* __restrict__ w_down,
                    const __nv_bfloat16* __restrict__ cvec, const __nv_bfloat16* __restrict__ w_mod,
                    __nv_bfloat16* __restrict__ out) {
    extern __shared__ __align__(128) unsigned char smem[];
    const int tid = threadIdx.x;
    const int cta = blockIdx.x;

    const uint32_t sbase = smem_u32(smem);
    const uint32_t bar_full = sbase + SM_BAR;
    const uint32_t bar_empty = bar_full + NST * 8;
    volatile int* s_item = (volatile int*)(smem + SM_ITEM);
    volatile int* s_tag = (volatile int*)(smem + SM_TAG);

    const uint32_t bar_go = bar_empty + NST * 8;
    if (tid < NST) s_tag[tid] = -1;
    if (tid == NST) s_item[NST + 1] = 0x7fffffff;
    if (tid == 0) {
#pragma unroll 1
        for (int s = 0; s < 2 * NST + 2; ++s) mbar_init(bar_full + s * 8, 1);
        asm volatile("fence.mbarrier_init.release.cluster;" ::: "memory");
        asm volatile("fence.proxy.async.shared::cta;" ::: "memory");
#pragma unroll 1
        for (int s = 0; s < PRE; ++s) mbar_arrive(bar_empty + s * 8);
    }
    __syncthreads();

    if (tid >= NCONS) {
        if (tid == NCONS) {
            int u = 0;
            const int G = (int)gridDim.x;
            uint64_t pol;
            asm volatile("createpolicy.fractional.L2::evict_first.b64 %0, 1.0;" : "=l"(pol));
            auto produce = [&](const int item) {
                const int it = item & (NITEM_K - 1);
                const bool is_v = item >= NITEM_K;
                const unsigned char* src = (const unsigned char*)(is_v ? v_cache : k_cache) + (size_t)it * (ITEM_KEYS * DH * 2);
#pragma unroll 1
                for (int t = 0; t < TPI; ++t, ++u) {
                    const int st = u % NST;
                    const uint32_t fb = bar_full + st * 8;
                    mbar_wait(bar_empty + st * 8, (u / NST) & 1);
                    if (item >= NITEM - THR_ITEMS * G) mbar_wait(bar_empty + ((u - THR_DEPTH) % NST) * 8, ((u - THR_DEPTH) / NST + 1) & 1);
                    s_item[st] = item;
                    s_tag[st] = u;
                    mbar_expect_tx(fb, TILE_BYTES);
                    bulk_g2s(sbase + SM_RING + st * STAGE_BYTES, src + t * TILE_BYTES, TILE_BYTES, fb, pol);
                }
            };
            if (PSTART != 3) mbar_wait(bar_go, 0);
            int item = cta;
#pragma unroll 1
            while (item < NITEM) {
                const int next = (int)atomicAdd(&g_work, 1u) + G;
                produce(item);
                item = next;
            }
            const int role = item - NITEM;
            s_item[NST] = role;
            __threadfence_block();
            s_item[NST + 1] = u;
            if (role < ND) {
                mbar_expect_tx(bar_go + 8, WO_ROWS * DM * 2);
#pragma unroll 1
                for (int j = 0; j < NST; ++j, ++u) {
                    const int st = u % NST;
                    mbar_wait(bar_empty + st * 8, (u / NST) & 1);
#pragma unroll 1
                    for (int r = 0; r < 16; ++r)
                        bulk_g2s(sbase + SM_RING + st * STAGE_BYTES + r * PROW, wo + (size_t)(role * WO_ROWS + st * 16 + r) * DM, DM * 2,
                                 bar_go + 8, pol);
                }
            }
            PROFP(13);
        }
        return;
    }

    const int lane = tid & 31, warp = tid >> 5;
    float* s_part = (float*)(smem + SM_PART);
    float* s_xp = (float*)(smem + SM_XP);
    float* s_red = (float*)(smem + SM_RED);
    const int lrow = tid >> 6, lcol = (tid & 63) * 10;
    uint32_t* h_dst = (uint32_t*)(smem + SM_A + lrow * A_PITCH + lcol * 2);

    PROF(0);
    const unsigned int ep = ld_acquire(&g_epoch) + 1u;
    const unsigned int target = ep * gridDim.x, tag16 = ep & 0xffffu;
    const unsigned long long* mod_row = g_mod + (lrow * MODN + lcol) / 2;
    float nv[10];
    {
        const int i1 = tid + NCONS;
        const uint4 c0 = __ldg((const uint4*)cvec + tid);
        uint4 c1 = c0;
        if (i1 < 320) c1 = __ldg((const uint4*)cvec + i1);
        uint32_t xw[5];
#pragma unroll
        for (int i = 0; i < 5; ++i) xw[i] = __ldg((const uint32_t*)(x_in + lrow * DM + lcol) + i);
        if (cta < MODN / 32) stage_rows(sbase + SM_W32, P32, w_mod + cta * 32, MODN * 2, DM, 4, tid, NCONS);
        cp_async_commit();
        if (cta < QN / 48) stage_rows(sbase + SM_WQ, P48, wq + cta * 48, QN * 2, DM, 6, tid, NCONS);
        cp_async_commit();
        if (PSTART == 1 && tid == 0) mbar_arrive(bar_go);
#pragma unroll 1
        for (int r = 0; r < 2; ++r) {
            const int i = r ? i1 : tid;
            if (i < 320) {
                const uint4 cc = r ? c1 : c0;
                const uint32_t cw[4] = {cc.x, cc.y, cc.z, cc.w};
                uint32_t ow[4];
#pragma unroll
                for (int k = 0; k < 4; ++k) {
                    const float a = bf_lo(cw[k]), b = bf_hi(cw[k]);
                    __nv_bfloat162 p = __floats2bfloat162_rn(__fdiv_rn(a, 1.0f + __expf(-a)), __fdiv_rn(b, 1.0f + __expf(-b)));
                    ow[k] = *(uint32_t*)&p;
                }
                const int b = i / 80, c8 = i - b * 80;
                *(uint4*)(smem + SM_A + b * A_PITCH + c8 * 16) = make_uint4(ow[0], ow[1], ow[2], ow[3]);
            }
        }
#pragma unroll
        for (int i = 0; i < 5; ++i) {
            nv[2 * i] = bf_lo(xw[i]);
            nv[2 * i + 1] = bf_hi(xw[i]);
            *(float2*)(s_xp + lrow * DM + lcol + 2 * i) = make_float2(nv[2 * i], nv[2 * i + 1]);
        }
    }
    float* acc_o = g_o[ep & 1];
    float* acc_attn = g_attn[ep & 1];
    if (cta == gridDim.x - 1) {
#pragma unroll 1
        for (int i = tid; i < NB * QN / 4; i += NCONS) ((float4*)g_o[~ep & 1])[i] = make_float4(0.f, 0.f, 0.f, 0.f);
#pragma unroll 1
        for (int i = tid; i < NB * DM; i += NCONS) g_attn[~ep & 1][i] = 0.f;
    }
    ln_norm(nv, s_red, tid);
    cp_async_wait1();
    cons_sync();
    if (PSTART == 0 && tid == 0) mbar_arrive(bar_go);
    if (cta < MODN / 32) {
        gemv_mma<5, 2>(sbase + SM_W32 + warp * 80 * P32, P32, sbase + SM_A + warp * 160, A_PITCH, s_part + warp * 320, lane);
        cons_sync();
        if (tid < 64) {
            const int b = tid >> 4, n = (tid & 15) * 2;
            ll_store(g_mod + (b * MODN + cta * 32 + n) / 2, tall_sum(s_part, b, n), tall_sum(s_part, b, n + 1), ep);
        }
    }
    PROF(1);

    if (cta < QN / 48) {
        cp_async_wait_all();
        cons_sync();
        if (PSTART == 2 && tid == 0) mbar_arrive(bar_go);
        uint32_t fq[5][3][4];
        frag_load<5, 3>(fq, sbase + SM_WQ + warp * 80 * P48, P48, lane);
        {
            long long t0 = 0;
            for (;;) {
                bool ok = true;
#pragma unroll
                for (int r = 0; r < 5; ++r) {
                    const int i = tid + r * NCONS, b = i / 320, c4 = i - b * 320;
                    const uint4 v = ll_ld2(g_mod + b * (MODN / 2) + 2 * c4);
                    *(uint2*)(s_part + b * DM + 2 * c4) = make_uint2(v.x, v.z);
                    ok = ok && v.y == ep && v.w == ep;
                }
                if (ok) break;
                if (t0 == 0) t0 = clock64();
                else if (clock64() - t0 > WAIT_LIMIT_CYCLES) __trap();
            }
        }
        cons_sync();
        PROF(2);
        uint32_t sh[5], sc[5];
#pragma unroll
        for (int i = 0; i < 5; ++i) {
            sh[i] = ((const uint32_t*)s_part)[lrow * DM + lcol / 2 + i];
            sc[i] = ((const uint32_t*)s_part)[lrow * DM + DM / 2 + lcol / 2 + i];
        }
        modulate(nv, sh, sc, h_dst);
        cons_sync();
        frag_mma<5, 3>(fq, sbase + SM_A + warp * 160, A_PITCH, s_part + warp * 320, lane);
        cons_sync();
        if (tid < 96) {
            const int b = tid / 24, n = (tid - b * 24) * 2;
            ll_store(g_q + (b * QN + cta * 48 + n) / 2, tall_sum(s_part, b, n), tall_sum(s_part, b, n + 1), ep);
        }
    } else if (PSTART == 2 && tid == 0) {
        mbar_arrive(bar_go);
    }
    PROF(3);
    if (tid == 0 && (!HAND_EARLY || cta >= QN / 48)) {
#pragma unroll 1
        for (int s = PRE; s < NST; ++s) mbar_arrive(bar_empty + s * 8);
    }
    uint32_t m_ga[5], m_sb[5], m_cb[5], m_fa[1] = {0u}, m_fb[1] = {0u};
    const int fcta = cta - ((int)gridDim.x - DM / 32);
    if (cta < FF / 16) {
        if (warp == 7) {
            stage_rows(sbase + SM_W32, P32, w_gate + cta * 16, FF * 2, DM, 2, lane, 32);
            stage_rows(sbase + SM_W32 + 32, P32, w_up + cta * 16, FF * 2, DM, 2, lane, 32);
        }
    }
    PROF(4);

    {
        const int sub = lane & 7, grp = lane >> 3;
        for (int u0 = warp * TPI;; u0 += 8 * TPI) {
            int item = -1;
            if (s_tag[u0 % NST] == u0 || tag_wait_stop(s_tag + u0 % NST, u0, s_item + NST + 1)) item = s_item[u0 % NST];
            if ((u0 >= 8 * TPI && u0 < 16 * TPI) || (item < 0 && u0 < 8 * TPI)) {
                if (cta < FF / 16) {
                    ll_get(mod_row + DM, m_ga, ep);
                    ll_get(mod_row + 3 * DM / 2, m_sb, ep);
                    ll_get(mod_row + 2 * DM, m_cb, ep);
                }
                if (tid < 64 && fcta >= 0) {
                    ll_get(g_mod + ((tid >> 4) * MODN + 2 * DM + fcta * 32) / 2 + (tid & 15), m_fa, ep);
                    ll_get(g_mod + ((tid >> 4) * MODN + 5 * DM + fcta * 32) / 2 + (tid & 15), m_fb, ep);
                }
            }
            if (item < 0) break;
            const int bh = (item & (NITEM_K - 1)) / CHUNKS;
            if (item < NITEM_K) {
                unsigned int* gs = g_s + (size_t)item * ITEM_KEYS;
                float qr[24];
                {
                    const unsigned long long* qp = g_q + ((bh >> 5) * QN + (bh & 31) * DH) / 2 + sub * 4;
                    long long t0 = 0;
                    for (;;) {
                        bool ok = true;
#pragma unroll
                        for (int j = 0; j < 6; ++j) {
                            const uint4 v = ll_ld2(qp + (j >> 1) * 32 + (j & 1) * 2);
                            qr[j * 4 + 0] = bf_lo(v.x); qr[j * 4 + 1] = bf_hi(v.x);
                            qr[j * 4 + 2] = bf_lo(v.z); qr[j * 4 + 3] = bf_hi(v.z);
                            ok = ok && v.y == ep && v.w == ep;
                        }
                        if (ok) break;
                        if (t0 == 0) t0 = clock64();
                        else if (clock64() - t0 > WAIT_LIMIT_CYCLES) __trap();
                    }
                }
                float m_run = -INFINITY, l_run = 0.f;
#pragma unroll 1
                for (int hh = 0; hh < 2 * TPI; ++hh) {
                    const int u = u0 + (hh >> 1), st = u % NST;
                    if (!(hh & 1)) stage_wait(bar_full, s_tag, u);
                    const uint4* tile = (const uint4*)(smem + SM_RING + st * STAGE_BYTES) + (hh & 1) * (32 * 24);
                    float part[8];
#pragma unroll
                    for (int it = 0; it < 8; ++it) {
                        const uint4* row = tile + (it * 4 + grp) * 24 + sub;
                        const uint4 a = row[0], b = row[8], c = row[16];
                        part[it] = dot8(a, qr) + dot8(b, qr + 8) + dot8(c, qr + 16);
                    }
                    if (hh & 1) {
                        __syncwarp();
                        if (lane == 0) mbar_arrive(bar_empty + st * 8);
                    }
#pragma unroll
                    for (int j = 0; j < 4; ++j) {
                        const float send = (sub & 4) ? part[j] : part[j + 4];
                        const float keep = (sub & 4) ? part[j + 4] : part[j];
                        part[j] = keep + __shfl_xor_sync(0xffffffffu, send, 4);
                    }
#pragma unroll
                    for (int j = 0; j < 2; ++j) {
                        const float send = (sub & 2) ? part[j] : part[j + 2];
                        const float keep = (sub & 2) ? part[j + 2] : part[j];
                        part[j] = keep + __shfl_xor_sync(0xffffffffu, send, 2);
                    }
                    {
                        const float send = (sub & 1) ? part[0] : part[1];
                        const float keep = (sub & 1) ? part[1] : part[0];
                        part[0] = keep + __shfl_xor_sync(0xffffffffu, send, 1);
                    }
                    const float s = bf16r(bf16r(part[0]) * 0.07216878364870323f);
                    asm volatile("st.relaxed.gpu.global.u32 [%0], %1;" ::"l"(gs + hh * 32 + sub * 4 + grp), "r"(__float_as_uint(s) | tag16) : "memory");
                    const float m_new = fmaxf(m_run, s);
                    l_run = l_run * __expf(m_run - m_new) + __expf(s - m_new);
                    m_run = m_new;
                }
                const float m = warp_max(m_run);
                const float l = warp_sum(l_run * __expf(m_run - m));
                if (lane == 0)
                    asm volatile("st.relaxed.gpu.global.u64 [%0], %1;" ::"l"(g_stat + item),
                                 "l"(((unsigned long long)__float_as_uint(l) << 32) | (__float_as_uint(m) | tag16)) : "memory");
            } else {
                float pr[2 * TPI];
                {
                    const unsigned int* gs = g_s + (size_t)(item - NITEM_K) * ITEM_KEYS + lane;
                    uint2 st2;
                    long long t0 = 0;
                    for (;;) {
                        st2 = ll_ld1(g_stat + bh * CHUNKS + lane);
                        bool ok = (st2.x & 0xffffu) == tag16;
#pragma unroll
                        for (int hh = 0; hh < 2 * TPI; ++hh) {
                            unsigned int w;
                            asm volatile("ld.relaxed.gpu.global.u32 %0, [%1];" : "=r"(w) : "l"(gs + hh * 32) : "memory");
                            ok = ok && (w & 0xffffu) == tag16;
                            pr[hh] = bf_hi(w);
                        }
                        if (__all_sync(0xffffffffu, ok)) break;
                        if (t0 == 0) t0 = clock64();
                        else if (clock64() - t0 > WAIT_LIMIT_CYCLES) __trap();
                    }
                    const float mi = bf_hi(st2.x);
                    const float mm = warp_max(mi);
                    const float ll = warp_sum(__uint_as_float(st2.y) * __expf(mi - mm));
#pragma unroll
                    for (int hh = 0; hh < 2 * TPI; ++hh) pr[hh] = bf16r(__fdiv_rn(__expf(pr[hh] - mm), ll));
                }
                float acc[3][8];
#pragma unroll
                for (int j = 0; j < 3; ++j)
#pragma unroll
                    for (int e = 0; e < 8; ++e) acc[j][e] = 0.f;
#pragma unroll
                for (int hh = 0; hh < 2 * TPI; ++hh) {
                    const int u = u0 + (hh >> 1), st = u % NST;
                    if (!(hh & 1)) stage_wait(bar_full, s_tag, u);
                    const uint4* tile = (const uint4*)(smem + SM_RING + st * STAGE_BYTES) + (hh & 1) * (32 * 24);
#pragma unroll
                    for (int it = 0; it < 8; ++it) {
                        const uint4* row = tile + (it * 4 + grp) * 24 + sub;
                        const uint4 a = row[0], b = row[8], c = row[16];
                        const float p = __shfl_sync(0xffffffffu, pr[hh], it * 4 + grp);
                        fma8(acc[0], a, p);
                        fma8(acc[1], b, p);
                        fma8(acc[2], c, p);
                    }
                    if (hh & 1) {
                        __syncwarp();
                        if (lane == 0) mbar_arrive(bar_empty + st * 8);
                    }
                }
                float* go = acc_o + (bh >> 5) * QN + (bh & 31) * DH + sub * 8;
#pragma unroll
                for (int j = 0; j < 3; ++j) {
#pragma unroll
                    for (int e = 0; e < 8; ++e) {
                        float v = acc[j][e];
                        v += __shfl_xor_sync(0xffffffffu, v, 8);
                        v += __shfl_xor_sync(0xffffffffu, v, 16);
                        acc[j][e] = v;
                    }
                    if (grp == 0) {
                        red_add_v4(go + j * 64, acc[j][0], acc[j][1], acc[j][2], acc[j][3]);
                        red_add_v4(go + j * 64 + 4, acc[j][4], acc[j][5], acc[j][6], acc[j][7]);
                    }
                }
            }
        }
    }
    PROF(5);
    grid_arrive(&g_bar[2], tid);
    PROF(6);
    const int role = s_item[NST];
    if (role < ND) {
        uint32_t fd[NST][5][4];
        mbar_wait(bar_go + 8, 0);
        frag_load<NST, 5>(fd, sbase + SM_RING + warp * 160, PROW, lane, STAGE_BYTES);
        grid_wait(&g_bar[2], target, tid);
        if (role == 0 && tid == 0) { g_work = 0u; g_epoch = ep; }
        PROF(7);
        float2 ov[NST][2];
        const float* op = acc_o + (lane >> 2) * QN + role * WO_ROWS + (lane & 3) * 2;
#pragma unroll
        for (int k = 0; k < NST; ++k) {
            ov[k][0] = make_float2(0.f, 0.f); ov[k][1] = ov[k][0];
            if (lane < 16) {
                ov[k][0] = __ldcg((const float2*)(op + k * 16));
                ov[k][1] = __ldcg((const float2*)(op + k * 16 + 8));
            }
        }
        float c[5][4];
#pragma unroll
        for (int nt = 0; nt < 5; ++nt) { c[nt][0] = 0.f; c[nt][1] = 0.f; c[nt][2] = 0.f; c[nt][3] = 0.f; }
#pragma unroll
        for (int k = 0; k < NST; ++k) {
            __nv_bfloat162 p0 = __floats2bfloat162_rn(ov[k][0].x, ov[k][0].y), p1 = __floats2bfloat162_rn(ov[k][1].x, ov[k][1].y);
#pragma unroll
            for (int nt = 0; nt < 5; ++nt)
                asm("mma.sync.aligned.m16n8k16.row.col.f32.bf16.bf16.f32 {%0, %1, %2, %3}, {%4, %5, %6, %7}, "
                    "{%8, %9}, {%0, %1, %2, %3};"
                    : "+f"(c[nt][0]), "+f"(c[nt][1]), "+f"(c[nt][2]), "+f"(c[nt][3])
                    : "r"(fd[k][nt][0]), "r"(fd[k][nt][1]), "r"(fd[k][nt][2]), "r"(fd[k][nt][3]),
                      "r"(*(uint32_t*)&p0), "r"(*(uint32_t*)&p1));
        }
        if ((lane & 3) < 2) {
            float* ap = acc_attn + (lane & 3) * 2 * DM + warp * 80 + (lane >> 2);
#pragma unroll
            for (int nt = 0; nt < 5; ++nt) {
                atomicAdd(ap + nt * 16, c[nt][0]);
                atomicAdd(ap + nt * 16 + DM, c[nt][1]);
                atomicAdd(ap + nt * 16 + 8, c[nt][2]);
                atomicAdd(ap + nt * 16 + DM + 8, c[nt][3]);
            }
        }
        PROF(8);
        grid_arrive(&g_bar[3], tid);
    }
    const bool has_e = cta < FF / 16;
    if (!has_e && fcta < 0) return;
    if (fcta >= 0) {
        const unsigned char* src = (const unsigned char*)(w_down + (size_t)(tid >> 2) * DM + fcta * 32) + (tid & 3) * 16;
        const uint32_t dst = sbase + SM_WD + (tid >> 2) * P32 + (tid & 3) * 16;
#pragma unroll
        for (int i = 0; i < FF / 64; ++i) cp_async16(dst + i * 64 * P32, src + (size_t)i * 64 * DM * 2);
    }
    if (has_e) {
        uint32_t fe[5][2][4];
        cp_async_wait_all();
        cons_sync();
        frag_load<5, 2>(fe, sbase + SM_W32 + warp * 80 * P32, P32, lane);
        grid_wait(&g_bar[3], ep * ND, tid);
        PROF(9);
        {
            float4 v[3];
#pragma unroll
            for (int r = 0; r < 3; ++r)
                if (tid + r * NCONS < NB * DM / 4) v[r] = __ldcg((const float4*)acc_attn + tid + r * NCONS);
#pragma unroll
            for (int r = 0; r < 3; ++r)
                if (tid + r * NCONS < NB * DM / 4) ((float4*)s_part)[tid + r * NCONS] = v[r];
        }
        cons_sync();
#pragma unroll
        for (int i = 0; i < 5; ++i) {
            const float2 av = *((const float2*)(s_part + lrow * DM + lcol) + i);
            const float2 xv = *((const float2*)(s_xp + lrow * DM + lcol) + i);
            nv[2 * i] = bf16r(xv.x + bf16r(bf_lo(m_ga[i]) * bf16r(av.x)));
            nv[2 * i + 1] = bf16r(xv.y + bf16r(bf_hi(m_ga[i]) * bf16r(av.y)));
        }
        ln_norm(nv, s_red, tid);
        modulate(nv, m_sb, m_cb, h_dst);
        cons_sync();
        frag_mma<5, 2>(fe, sbase + SM_A + warp * 160, A_PITCH, s_part + warp * 320, lane);
        cons_sync();
        if (tid < 32) {
            const int b = tid >> 3, n = (tid & 7) * 2;
            const float g0 = bf16r(tall_sum(s_part, b, n)), g1 = bf16r(tall_sum(s_part, b, n + 1));
            const float u0 = bf16r(tall_sum(s_part, b, 16 + n)), u1 = bf16r(tall_sum(s_part, b, 17 + n));
            ll_store(g_act + (b * FF + cta * 16 + n) / 2, bf16r(gelu_tanh(g0)) * u0, bf16r(gelu_tanh(g1)) * u1, ep);
        }
        PROF(10);
        if (fcta < 0) return;
    } else {
        grid_wait(&g_bar[3], ep * ND, tid);
    }
    {
        float x10 = 0.f, x11 = 0.f;
        if (tid < 64) {
            const int b = tid >> 4, col = fcta * 32 + (tid & 15) * 2;
            const float2 av = __ldcg((const float2*)(acc_attn + b * DM + col));
            x10 = bf16r(s_xp[b * DM + col] + bf16r(bf_lo(m_fa[0]) * bf16r(av.x)));
            x11 = bf16r(s_xp[b * DM + col + 1] + bf16r(bf_hi(m_fa[0]) * bf16r(av.y)));
        }
        cp_async_wait_all();
        cons_sync();
        uint32_t ff[12][2][4];
        frag_load<12, 2>(ff, sbase + SM_WD + warp * 192 * P32, P32, lane);
        long long t0 = 0;
        for (;;) {
            bool ok = true;
#pragma unroll
            for (int r = 0; r < 6; ++r) {
                const int i = tid + r * NCONS, b = i / 384, c4 = i - b * 384;
                const uint4 v = ll_ld2(g_act + 2 * i);
                *(uint2*)(smem + SM_ACT + b * ACT_PITCH + c4 * 8) = make_uint2(v.x, v.z);
                ok = ok && v.y == ep && v.w == ep;
            }
            if (ok) break;
            if (t0 == 0) t0 = clock64();
            else if (clock64() - t0 > WAIT_LIMIT_CYCLES) __trap();
        }
        cons_sync();
        PROF(11);
        frag_mma<12, 2>(ff, sbase + SM_ACT + warp * 384, ACT_PITCH, s_part + warp * 320, lane);
        cons_sync();
        if (tid < 64) {
            const int b = tid >> 4, n = (tid & 15) * 2;
            const float f0 = bf16r(tall_sum(s_part, b, n)), f1 = bf16r(tall_sum(s_part, b, n + 1));
            *(__nv_bfloat162*)(out + b * DM + fcta * 32 + n) =
                __floats2bfloat162_rn(x10 + bf16r(bf_lo(m_fb[0]) * f0), x11 + bf16r(bf_hi(m_fb[0]) * f1));
        }
    }
    PROF(12);
}

}

extern "C" void kernel_launch(void* const* d_in, const int* in_sizes, int n_in, void* d_out, int out_size) {
    (void)in_sizes; (void)n_in; (void)out_size;
    const __nv_bfloat16* A_x = (const __nv_bfloat16*)d_in[0];
    const __nv_bfloat16* A_k = (const __nv_bfloat16*)d_in[1];
    const __nv_bfloat16* A_v = (const __nv_bfloat16*)d_in[2];
    const __nv_bfloat16* A_wq = (const __nv_bfloat16*)d_in[3];
    const __nv_bfloat16* A_wo = (const __nv_bfloat16*)d_in[4];
    const __nv_bfloat16* B_wg = (const __nv_bfloat16*)d_in[6];
    const __nv_bfloat16* B_wu = (const __nv_bfloat16*)d_in[7];
    const __nv_bfloat16* B_wd = (const __nv_bfloat16*)d_in[8];
    const __nv_bfloat16* c = (const __nv_bfloat16*)d_in[9];
    const __nv_bfloat16* w_mod = (const __nv_bfloat16*)d_in[10];
    static int grid = 0;
    if (grid == 0) {
        cudaFuncSetAttribute(decode_block_kernel, cudaFuncAttributeMaxDynamicSharedMemorySize, SM_TOTAL);
        int dev = 0, sms = 0;
        cudaGetDevice(&dev);
        cudaDeviceGetAttribute(&sms, cudaDevAttrMultiProcessorCount, dev);
        grid = sms < 132 ? sms : 132;
    }
    decode_block_kernel<<<grid, NTHREADS, SM_TOTAL>>>(A_x, A_k, A_v, A_wq, A_wo, B_wg, B_wu, B_wd, c, w_mod,
                                                      (__nv_bfloat16*)d_out);
}
```

```cpp
#include <cuda.h>
#include <cuda_runtime.h>
#include <cuda_bf16.h>
#include <stdint.h>

namespace {

constexpr int NB = 4;
constexpr int DM = 640;
constexpr int NH = 32;
constexpr int SK = 4096;
constexpr int DH = 192;
constexpr int FF = 1536;
constexpr int MODN = 6 * DM;
constexpr int QN = NH * DH;
constexpr int NBH = NB * NH;

constexpr int NCONS = 256;
constexpr int NTHREADS = NCONS + 32;
constexpr int TILE_KEYS = 64;
constexpr int TILE_BYTES = TILE_KEYS * DH * 2;
constexpr int STAGE_BYTES = TILE_BYTES;
constexpr int NST = 6;
constexpr int PRE = 3;
constexpr int TPI = 2;
constexpr int ITEM_KEYS = TPI * TILE_KEYS;
constexpr int CHUNKS = SK / ITEM_KEYS;
constexpr int NITEM_K = NBH * CHUNKS;
constexpr int NITEM = 2 * NITEM_K;

constexpr int A_PITCH = 1296;
constexpr int ACT_PITCH = FF * 2 + 16;
constexpr int P32 = 80;
constexpr int P48 = 112;
constexpr int P80 = 176;
constexpr int WO_ROWS = 384;
constexpr int BOX = 128;

constexpr int SM_RING = 0;
constexpr int SM_WQ = PRE * STAGE_BYTES;
constexpr int SM_WD = 0;
constexpr int SM_W32 = NST * STAGE_BYTES;
constexpr int SM_ACT = SM_W32;
constexpr int SM_A = SM_W32 + DM * P32;
constexpr int SM_PART = SM_A + NB * A_PITCH;
constexpr int SM_XP = SM_PART + 8 * 4 * 80 * 4;
constexpr int SM_RED = SM_XP + NB * DM * 4;
constexpr int SM_ITEM = SM_RED + 16 * 4;
constexpr int SM_TAG = SM_ITEM + 16 * 4;
constexpr int SM_BAR = SM_TAG + 16 * 4;
constexpr int SM_TOTAL = SM_BAR + (2 * NST + 5) * 8;
static_assert(SM_WQ + DM * P48 <= NST * STAGE_BYTES, "prologue overlay");
static_assert(SM_WD + FF * P32 <= NST * STAGE_BYTES && BOX * P80 <= STAGE_BYTES, "tail overlay");
static_assert(SM_TOTAL <= 232448, "smem");
#define THR_ITEMS 6
#define THR_DEPTH 3
#define HAND_EARLY 0
#define PSTART 0
#define WO_AT 1
#define GU_AT 1

__device__ __align__(128) unsigned long long g_mod[NB * MODN / 2];
__device__ __align__(128) unsigned long long g_q[NB * QN / 2];
__device__ __align__(128) unsigned long long g_act[NB * FF / 2];
__device__ __align__(128) unsigned int g_s[NBH * SK];
__device__ __align__(128) unsigned long long g_stat[NBH * CHUNKS];
__device__ __align__(128) float g_o[2][NB * QN];
__device__ __align__(128) float g_attn[2][NB * DM];
__device__ __align__(128) unsigned int g_bar[8];
__device__ unsigned int g_work;
__device__ unsigned int g_epoch;

#define PROF(k) do { } while (0)
#define PROFP(k) do { } while (0)

__device__ __forceinline__ float bf16r(float x) { return __bfloat162float(__float2bfloat16_rn(x)); }
__device__ __forceinline__ float bf_lo(uint32_t u) { return __uint_as_float(u << 16); }
__device__ __forceinline__ float bf_hi(uint32_t u) { return __uint_as_float(u & 0xffff0000u); }

__device__ __forceinline__ uint32_t smem_u32(const void* p) { return (uint32_t)__cvta_generic_to_shared(p); }
__device__ __forceinline__ void mbar_init(uint32_t bar, uint32_t count) {
    asm volatile("mbarrier.init.shared::cta.b64 [%0], %1;" ::"r"(bar), "r"(count) : "memory");
}
__device__ __forceinline__ void mbar_expect_tx(uint32_t bar, uint32_t bytes) {
    asm volatile("mbarrier.arrive.expect_tx.shared::cta.b64 _, [%0], %1;" ::"r"(bar), "r"(bytes) : "memory");
}
__device__ __forceinline__ void mbar_arrive(uint32_t bar) {
    asm volatile("mbarrier.arrive.shared::cta.b64 _, [%0];" ::"r"(bar) : "memory");
}
constexpr long long WAIT_LIMIT_CYCLES = 200000000LL;
__device__ __forceinline__ uint32_t mbar_try(uint32_t bar, uint32_t parity) {
    uint32_t done;
    asm volatile(
        "{\n\t.reg .pred p;\n\t"
        "mbarrier.try_wait.parity.shared::cta.b64 p, [%1], %2;\n\t"
        "selp.u32 %0, 1, 0, p;\n\t}"
        : "=r"(done) : "r"(bar), "r"(parity) : "memory");
    return done;
}
__device__ __noinline__ void mbar_wait_slow(uint32_t bar, uint32_t parity) {
    const long long t0 = clock64();
    while (!mbar_try(bar, parity)) {
        if (clock64() - t0 > WAIT_LIMIT_CYCLES) __trap();
    }
}
__device__ __forceinline__ void mbar_wait(uint32_t bar, uint32_t parity) {
    if (!mbar_try(bar, parity)) mbar_wait_slow(bar, parity);
}
__device__ __noinline__ void tag_wait_slow(volatile int* tag, int u) {
    const long long t0 = clock64();
    while (*tag != u) {
        __nanosleep(32);
        if (clock64() - t0 > WAIT_LIMIT_CYCLES) __trap();
    }
}
__device__ __noinline__ bool tag_wait_stop(volatile int* tag, int u, volatile int* stop) {
    const long long t0 = clock64();
    while (*tag != u) {
        if (*stop <= u) return false;
        __nanosleep(32);
        if (clock64() - t0 > WAIT_LIMIT_CYCLES) __trap();
    }
    return true;
}
__device__ __forceinline__ void stage_wait(uint32_t bar_full, volatile int* s_tag, int u) {
    const int st = u % NST;
    if (s_tag[st] != u) tag_wait_slow(s_tag + st, u);
    mbar_wait(bar_full + st * 8, (u / NST) & 1);
}
__device__ __forceinline__ void bulk_g2s(uint32_t dst, const void* src, uint32_t bytes, uint32_t bar, uint64_t pol) {
    asm volatile(
        "cp.async.bulk.shared::cluster.global.mbarrier::complete_tx::bytes.L2::cache_hint [%0], [%1], %2, [%3], %4;"
        ::"r"(dst), "l"(src), "r"(bytes), "r"(bar), "l"(pol) : "memory");
}
__device__ __forceinline__ void tma2d(uint32_t dst, const CUtensorMap* map, int col, int row, uint32_t bar) {
    asm volatile(
        "cp.async.bulk.tensor.2d.shared::cluster.global.tile.mbarrier::complete_tx::bytes [%0], [%1, {%2, %3}], [%4];"
        ::"r"(dst), "l"(map), "r"(col), "r"(row), "r"(bar) : "memory");
}
__device__ __forceinline__ void tma_block(uint32_t dst, const CUtensorMap* map, int col, int row, int rows, int pitch, uint32_t bar) {
#pragma unroll 1
    for (int r = 0; r < rows; r += BOX) tma2d(dst + r * pitch, map, col, row + r, bar);
}
__device__ __forceinline__ void cp_async16(uint32_t dst, const void* src) {
    asm volatile("cp.async.cg.shared.global [%0], [%1], 16;" ::"r"(dst), "l"(src) : "memory");
}
__device__ __forceinline__ void cp_async_wait_all() { asm volatile("cp.async.wait_all;" ::: "memory"); }
__device__ __forceinline__ void cp_async_commit() { asm volatile("cp.async.commit_group;" ::: "memory"); }
__device__ __forceinline__ void cp_async_wait1() { asm volatile("cp.async.wait_group 1;" ::: "memory"); }
__device__ __forceinline__ void red_release_add(unsigned int* p, unsigned int v) {
    asm volatile("red.release.gpu.global.add.u32 [%0], %1;" ::"l"(p), "r"(v) : "memory");
}
__device__ __forceinline__ void cons_sync() { asm volatile("bar.sync 1, 256;" ::: "memory"); }

__device__ __forceinline__ void red_add_v4(float* p, float a, float b, float c, float d) {
    asm volatile("red.global.add.v4.f32 [%0], {%1, %2, %3, %4};" ::"l"(p), "f"(a), "f"(b), "f"(c), "f"(d) : "memory");
}
__device__ __forceinline__ unsigned int ld_acquire(const unsigned int* p) {
    unsigned int v;
    asm volatile("ld.acquire.gpu.global.u32 %0, [%1];" : "=r"(v) : "l"(p) : "memory");
    return v;
}
__device__ __forceinline__ void ll_store(unsigned long long* p, float a, float b, unsigned int ep) {
    __nv_bfloat162 v = __floats2bfloat162_rn(a, b);
    const unsigned long long w = ((unsigned long long)ep << 32) | *(uint32_t*)&v;
    asm volatile("st.relaxed.gpu.global.u64 [%0], %1;" ::"l"(p), "l"(w) : "memory");
}
__device__ __forceinline__ uint2 ll_ld1(const unsigned long long* p) {
    unsigned long long w;
    asm volatile("ld.relaxed.gpu.global.u64 %0, [%1];" : "=l"(w) : "l"(p) : "memory");
    return make_uint2((uint32_t)w, (uint32_t)(w >> 32));
}
__device__ __forceinline__ uint4 ll_ld2(const unsigned long long* p) {
    unsigned long long a, b;
    asm volatile("ld.relaxed.gpu.global.v2.u64 {%0, %1}, [%2];" : "=l"(a), "=l"(b) : "l"(p) : "memory");
    return make_uint4((uint32_t)a, (uint32_t)(a >> 32), (uint32_t)b, (uint32_t)(b >> 32));
}
template <int N>
__device__ __forceinline__ void ll_get(const unsigned long long* p, uint32_t (&d)[N], unsigned int ep) {
    long long t0 = 0;
    for (;;) {
        bool ok = true;
#pragma unroll
        for (int i = 0; i < N; ++i) {
            const uint2 v = ll_ld1(p + i);
            d[i] = v.x;
            ok = ok && (v.y == ep);
        }
        if (ok) break;
        if (t0 == 0) t0 = clock64();
        else if (clock64() - t0 > WAIT_LIMIT_CYCLES) __trap();
    }
}

__device__ __forceinline__ void grid_arrive(unsigned int* ctr, int tid) {
    cons_sync();
    if (tid == 0) red_release_add(ctr, 1u);
}
__device__ __noinline__ void grid_wait(const unsigned int* ctr, unsigned int target, int tid) {
    if (tid == 0) {
        const long long t0 = clock64();
        while ((int)(ld_acquire(ctr) - target) < 0) {
            if (clock64() - t0 > WAIT_LIMIT_CYCLES) __trap();
        }
    }
    cons_sync();
}

__device__ __forceinline__ float warp_sum(float v) {
#pragma unroll
    for (int o = 16; o > 0; o >>= 1) v += __shfl_xor_sync(0xffffffffu, v, o);
    return v;
}
__device__ __forceinline__ float warp_max(float v) {
#pragma unroll
    for (int o = 16; o > 0; o >>= 1) v = fmaxf(v, __shfl_xor_sync(0xffffffffu, v, o));
    return v;
}

__device__ __forceinline__ void fma8(float (&acc)[8], const uint4& w, float s) {
    acc[0] = fmaf(s, bf_lo(w.x), acc[0]);
    acc[1] = fmaf(s, bf_hi(w.x), acc[1]);
    acc[2] = fmaf(s, bf_lo(w.y), acc[2]);
    acc[3] = fmaf(s, bf_hi(w.y), acc[3]);
    acc[4] = fmaf(s, bf_lo(w.z), acc[4]);
    acc[5] = fmaf(s, bf_hi(w.z), acc[5]);
    acc[6] = fmaf(s, bf_lo(w.w), acc[6]);
    acc[7] = fmaf(s, bf_hi(w.w), acc[7]);
}
__device__ __forceinline__ float dot8(const uint4& w, const float* q) {
    float s = q[0] * bf_lo(w.x);
    s = fmaf(q[1], bf_hi(w.x), s);
    s = fmaf(q[2], bf_lo(w.y), s);
    s = fmaf(q[3], bf_hi(w.y), s);
    s = fmaf(q[4], bf_lo(w.z), s);
    s = fmaf(q[5], bf_hi(w.z), s);
    s = fmaf(q[6], bf_lo(w.w), s);
    s = fmaf(q[7], bf_hi(w.w), s);
    return s;
}

__device__ __noinline__ void stage_rows(uint32_t dst, int dst_pitch, const void* src, int src_stride, int rows,
                                        int cpr, int tid, int nthr) {
    const int n = rows * cpr;
#pragma unroll 1
    for (int i = tid; i < n; i += nthr) {
        const int r = i / cpr, c = i - r * cpr;
        cp_async16(dst + r * dst_pitch + c * 16, (const unsigned char*)src + (size_t)r * src_stride + c * 16);
    }
}

template <int KS, int NT>
__device__ __noinline__ void gemv_mma(uint32_t w, int w_pitch, uint32_t a, int a_pitch, float* part, int lane) {
    float c[NT][4];
#pragma unroll
    for (int nt = 0; nt < NT; ++nt) { c[nt][0] = 0.f; c[nt][1] = 0.f; c[nt][2] = 0.f; c[nt][3] = 0.f; }
    const uint32_t ap = a + (lane >> 2) * a_pitch + (lane & 3) * 4;
    const uint32_t wp = w + ((lane & 7) + ((lane >> 4) << 3)) * w_pitch + ((lane >> 3) & 1) * 16;
#pragma unroll
    for (int ks = 0; ks < KS; ++ks) {
        uint32_t b0 = 0, b1 = 0;
        if (lane < 16) {
            asm("ld.shared.u32 %0, [%1];" : "=r"(b0) : "r"(ap + ks * 32));
            asm("ld.shared.u32 %0, [%1];" : "=r"(b1) : "r"(ap + ks * 32 + 16));
        }
#pragma unroll
        for (int nt = 0; nt < NT; ++nt) {
            uint32_t a0, a1, a2, a3;
            asm("ldmatrix.sync.aligned.m8n8.x4.trans.shared.b16 {%0, %1, %2, %3}, [%4];"
                         : "=r"(a0), "=r"(a1), "=r"(a2), "=r"(a3) : "r"(wp + ks * 16 * w_pitch + nt * 32));
            asm("mma.sync.aligned.m16n8k16.row.col.f32.bf16.bf16.f32 {%0, %1, %2, %3}, {%4, %5, %6, %7}, "
                "{%8, %9}, {%0, %1, %2, %3};"
                : "+f"(c[nt][0]), "+f"(c[nt][1]), "+f"(c[nt][2]), "+f"(c[nt][3])
                : "r"(a0), "r"(a1), "r"(a2), "r"(a3), "r"(b0), "r"(b1));
        }
    }
    if ((lane & 3) < 2) {
        float* pp = part + (lane & 3) * 160 + (lane >> 2);
#pragma unroll
        for (int nt = 0; nt < NT; ++nt) {
            pp[nt * 16] = c[nt][0];
            pp[nt * 16 + 80] = c[nt][1];
            pp[nt * 16 + 8] = c[nt][2];
            pp[nt * 16 + 88] = c[nt][3];
        }
    }
}

template <int KS, int NT>
__device__ __forceinline__ void frag_load(uint32_t (&f)[KS][NT][4], uint32_t w, int w_pitch, int lane, int n_stride = 32) {
    const uint32_t wp = w + ((lane & 7) + ((lane >> 4) << 3)) * w_pitch + ((lane >> 3) & 1) * 16;
#pragma unroll
    for (int ks = 0; ks < KS; ++ks)
#pragma unroll
        for (int nt = 0; nt < NT; ++nt)
            asm volatile("ldmatrix.sync.aligned.m8n8.x4.trans.shared.b16 {%0, %1, %2, %3}, [%4];"
                         : "=r"(f[ks][nt][0]), "=r"(f[ks][nt][1]), "=r"(f[ks][nt][2]), "=r"(f[ks][nt][3])
                         : "r"(wp + ks * 16 * w_pitch + nt * n_stride) : "memory");
}
template <int KS, int NT>
__device__ __forceinline__ void frag_mma(const uint32_t (&f)[KS][NT][4], uint32_t a, int a_pitch, float* part, int lane) {
    float c[NT][4];
#pragma unroll
    for (int nt = 0; nt < NT; ++nt) { c[nt][0] = 0.f; c[nt][1] = 0.f; c[nt][2] = 0.f; c[nt][3] = 0.f; }
    const uint32_t ap = a + (lane >> 2) * a_pitch + (lane & 3) * 4;
    uint32_t b[KS][2];
#pragma unroll
    for (int ks = 0; ks < KS; ++ks) {
        b[ks][0] = 0; b[ks][1] = 0;
        if (lane < 16) {
            asm volatile("ld.shared.u32 %0, [%1];" : "=r"(b[ks][0]) : "r"(ap + ks * 32) : "memory");
            asm volatile("ld.shared.u32 %0, [%1];" : "=r"(b[ks][1]) : "r"(ap + ks * 32 + 16) : "memory");
        }
    }
#pragma unroll
    for (int ks = 0; ks < KS; ++ks)
#pragma unroll
        for (int nt = 0; nt < NT; ++nt)
            asm("mma.sync.aligned.m16n8k16.row.col.f32.bf16.bf16.f32 {%0, %1, %2, %3}, {%4, %5, %6, %7}, "
                "{%8, %9}, {%0, %1, %2, %3};"
                : "+f"(c[nt][0]), "+f"(c[nt][1]), "+f"(c[nt][2]), "+f"(c[nt][3])
                : "r"(f[ks][nt][0]), "r"(f[ks][nt][1]), "r"(f[ks][nt][2]), "r"(f[ks][nt][3]), "r"(b[ks][0]), "r"(b[ks][1]));
    if ((lane & 3) < 2) {
        float* pp = part + (lane & 3) * 160 + (lane >> 2);
#pragma unroll
        for (int nt = 0; nt < NT; ++nt) {
            pp[nt * 16] = c[nt][0];
            pp[nt * 16 + 80] = c[nt][1];
            pp[nt * 16 + 8] = c[nt][2];
            pp[nt * 16 + 88] = c[nt][3];
        }
    }
}

__device__ __forceinline__ float tall_sum(const float* part, int b, int n) {
    float s = 0.f;
#pragma unroll
    for (int w = 0; w < 8; ++w) s += part[(w * 4 + b) * 80 + n];
    return s;
}

__device__ __forceinline__ void ln_norm(float (&v)[10], float* s_red, int tid) {
    const int warp = tid >> 5;
    const float pv = __shfl_sync(0xffffffffu, v[0], 0);
    float s = 0.f, q = 0.f;
#pragma unroll
    for (int i = 0; i < 10; ++i) { const float d = v[i] - pv; s += d; q = fmaf(d, d, q); }
#pragma unroll
    for (int o = 16; o > 0; o >>= 1) {
        s += __shfl_xor_sync(0xffffffffu, s, o);
        q += __shfl_xor_sync(0xffffffffu, q, o);
    }
    const float md = s * (2.0f / DM);
    if ((tid & 31) == 0) *(float2*)(s_red + 2 * warp) = make_float2(pv + md, fmaxf(q - s * md, 0.f));
    cons_sync();
    const float4 r = *(const float4*)(s_red + 4 * (warp >> 1));
    const float dm = r.x - r.z;
    const float var = (r.y + r.w + dm * dm * (DM / 4)) * (1.0f / DM);
    const float mean = bf16r(0.5f * (r.x + r.z));
    const float inv = __fdiv_rn(1.0f, bf16r(sqrtf(bf16r(bf16r(var) + 1e-5f))));
#pragma unroll
    for (int i = 0; i < 10; ++i) v[i] = bf16r(bf16r(v[i] - mean) * inv);
}
__device__ __forceinline__ void modulate(const float (&n)[10], const uint32_t (&sh)[5], const uint32_t (&sc)[5], uint32_t* dst) {
#pragma unroll
    for (int i = 0; i < 5; ++i) {
        const float h0 = bf16r(n[2 * i] * bf16r(1.0f + bf_lo(sc[i]))) + bf_lo(sh[i]);
        const float h1 = bf16r(n[2 * i + 1] * bf16r(1.0f + bf_hi(sc[i]))) + bf_hi(sh[i]);
        __nv_bfloat162 p = __floats2bfloat162_rn(h0, h1);
        dst[i] = *(uint32_t*)&p;
    }
}

__device__ __forceinline__ float gelu_tanh(float x) {
    const float kBeta = 0.7978845608028654f;
    const float inner = kBeta * (x + 0.044715f * x * x * x);
    return 0.5f * x * (1.0f + tanhf(inner));
}

__global__ void __launch_bounds__(NTHREADS, 1)
decode_block_kernel(const __nv_bfloat16* __restrict__ x_in, const __nv_bfloat16* __restrict__ k_cache,
                    const __nv_bfloat16* __restrict__ v_cache, const __nv_bfloat16* __restrict__ cvec,
                    __nv_bfloat16* __restrict__ out, const __grid_constant__ CUtensorMap tm_mod,
                    const __grid_constant__ CUtensorMap tm_q, const __grid_constant__ CUtensorMap tm_o,
                    const __grid_constant__ CUtensorMap tm_gate, const __grid_constant__ CUtensorMap tm_up,
                    const __grid_constant__ CUtensorMap tm_down) {
    extern __shared__ __align__(128) unsigned char smem[];
    const int tid = threadIdx.x;
    const int cta = blockIdx.x;

    const uint32_t sbase = smem_u32(smem);
    const uint32_t bar_full = sbase + SM_BAR;
    const uint32_t bar_empty = bar_full + NST * 8;
    volatile int* s_item = (volatile int*)(smem + SM_ITEM);
    volatile int* s_tag = (volatile int*)(smem + SM_TAG);

    const uint32_t bar_wm = bar_empty + NST * 8, bar_wq = bar_wm + 8, bar_wo = bar_wm + 16, bar_gu = bar_wm + 24, bar_wd = bar_wm + 32;
    if (tid < NST) s_tag[tid] = -1;
    if (tid == NST) s_item[NST] = 0x7fffffff;
    if (tid == 0) {
#pragma unroll 1
        for (int s = 0; s < 2 * NST + 5; ++s) mbar_init(bar_full + s * 8, 1);
        asm volatile("fence.mbarrier_init.release.cluster;" ::: "memory");
        asm volatile("fence.proxy.async.shared::cta;" ::: "memory");
        if (cta < MODN / 32) {
            mbar_expect_tx(bar_wm, DM * P32);
            tma_block(sbase + SM_W32, &tm_mod, cta * 32, 0, DM, P32, bar_wm);
        }
        if (cta < QN / 48) {
            mbar_expect_tx(bar_wq, DM * P48);
            tma_block(sbase + SM_WQ, &tm_q, cta * 48, 0, DM, P48, bar_wq);
        }
#pragma unroll 1
        for (int s = 0; s < PRE; ++s) mbar_arrive(bar_empty + s * 8);
    }
    __syncthreads();
    const int ks = cta >> 3, ns = cta & 7;

    if (tid >= NCONS) {
        if (tid == NCONS) {
            int u = 0;
            const int G = (int)gridDim.x;
            uint64_t pol;
            asm volatile("createpolicy.fractional.L2::evict_first.b64 %0, 1.0;" : "=l"(pol));
            auto produce = [&](const int item) {
                const int it = item & (NITEM_K - 1);
                const bool is_v = item >= NITEM_K;
                const unsigned char* src = (const unsigned char*)(is_v ? v_cache : k_cache) + (size_t)it * (ITEM_KEYS * DH * 2);
#pragma unroll 1
                for (int t = 0; t < TPI; ++t, ++u) {
                    const int st = u % NST;
                    const uint32_t fb = bar_full + st * 8;
                    mbar_wait(bar_empty + st * 8, (u / NST) & 1);
                    if (item >= NITEM - THR_ITEMS * G) mbar_wait(bar_empty + ((u - THR_DEPTH) % NST) * 8, ((u - THR_DEPTH) / NST + 1) & 1);
                    s_item[st] = item;
                    s_tag[st] = u;
                    mbar_expect_tx(fb, TILE_BYTES);
                    bulk_g2s(sbase + SM_RING + st * STAGE_BYTES, src + t * TILE_BYTES, TILE_BYTES, fb, pol);
                }
            };
            asm volatile("prefetch.tensormap [%0];" ::"l"(&tm_o) : "memory");
            asm volatile("prefetch.tensormap [%0];" ::"l"(&tm_gate) : "memory");
            asm volatile("prefetch.tensormap [%0];" ::"l"(&tm_up) : "memory");
            asm volatile("prefetch.tensormap [%0];" ::"l"(&tm_down) : "memory");
            if (PSTART == 0 && cta < MODN / 32) mbar_wait(bar_wm, 0);
            if (PSTART == 2 && cta < QN / 48) mbar_wait(bar_wq, 0);
            int item = cta;
#pragma unroll 1
            while (item < NITEM) {
                const int next = (int)atomicAdd(&g_work, 1u) + G;
                produce(item);
                item = next;
            }
            s_item[NST] = u;
            if (WO_AT == 1 && cta < 128) {
                mbar_expect_tx(bar_wo, WO_ROWS * P80);
#pragma unroll 1
                for (int j = 0; j < WO_ROWS / BOX; ++j, ++u) {
                    const int st = u % NST;
                    mbar_wait(bar_empty + st * 8, (u / NST) & 1);
                    tma2d(sbase + SM_RING + st * STAGE_BYTES, &tm_o, ns * 80, ks * WO_ROWS + j * BOX, bar_wo);
                }
            }
            if (GU_AT == 1 && cta < FF / 16) {
                mbar_expect_tx(bar_gu, 2 * DM * 32);
                tma_block(sbase + SM_W32, &tm_gate, cta * 16, 0, DM, 32, bar_gu);
                tma_block(sbase + SM_W32 + DM * 32, &tm_up, cta * 16, 0, DM, 32, bar_gu);
            }
            PROFP(13);
        }
        return;
    }

    const int lane = tid & 31, warp = tid >> 5;
    float* s_part = (float*)(smem + SM_PART);
    float* s_xp = (float*)(smem + SM_XP);
    float* s_red = (float*)(smem + SM_RED);
    const int lrow = tid >> 6, lcol = (tid & 63) * 10;
    uint32_t* h_dst = (uint32_t*)(smem + SM_A + lrow * A_PITCH + lcol * 2);

    PROF(0);
    const unsigned int ep = ld_acquire(&g_epoch) + 1u;
    const unsigned int target = ep * gridDim.x, tag16 = ep & 0xffffu;
    const unsigned long long* mod_row = g_mod + (lrow * MODN + lcol) / 2;
    float nv[10];
    {
        const int i1 = tid + NCONS;
        const uint4 c0 = __ldg((const uint4*)cvec + tid);
        uint4 c1 = c0;
        if (i1 < 320) c1 = __ldg((const uint4*)cvec + i1);
        uint32_t xw[5];
#pragma unroll
        for (int i = 0; i < 5; ++i) xw[i] = __ldg((const uint32_t*)(x_in + lrow * DM + lcol) + i);
#pragma unroll 1
        for (int r = 0; r < 2; ++r) {
            const int i = r ? i1 : tid;
            if (i < 320) {
                const uint4 cc = r ? c1 : c0;
                const uint32_t cw[4] = {cc.x, cc.y, cc.z, cc.w};
                uint32_t ow[4];
#pragma unroll
                for (int k = 0; k < 4; ++k) {
                    const float a = bf_lo(cw[k]), b = bf_hi(cw[k]);
                    __nv_bfloat162 p = __floats2bfloat162_rn(__fdiv_rn(a, 1.0f + __expf(-a)), __fdiv_rn(b, 1.0f + __expf(-b)));
                    ow[k] = *(uint32_t*)&p;
                }
                const int b = i / 80, c8 = i - b * 80;
                *(uint4*)(smem + SM_A + b * A_PITCH + c8 * 16) = make_uint4(ow[0], ow[1], ow[2], ow[3]);
            }
        }
#pragma unroll
        for (int i = 0; i < 5; ++i) {
            nv[2 * i] = bf_lo(xw[i]);
            nv[2 * i + 1] = bf_hi(xw[i]);
            *(float2*)(s_xp + lrow * DM + lcol + 2 * i) = make_float2(nv[2 * i], nv[2 * i + 1]);
        }
    }
    float* acc_o = g_o[ep & 1];
    float* acc_attn = g_attn[ep & 1];
    if (cta == gridDim.x - 1) {
#pragma unroll 1
        for (int i = tid; i < NB * QN / 4; i += NCONS) ((float4*)g_o[~ep & 1])[i] = make_float4(0.f, 0.f, 0.f, 0.f);
#pragma unroll 1
        for (int i = tid; i < NB * DM; i += NCONS) g_attn[~ep & 1][i] = 0.f;
    }
    ln_norm(nv, s_red, tid);
    cons_sync();
    if (cta < MODN / 32) {
        mbar_wait(bar_wm, 0);
        gemv_mma<5, 2>(sbase + SM_W32 + warp * 80 * P32, P32, sbase + SM_A + warp * 160, A_PITCH, s_part + warp * 320, lane);
        cons_sync();
        if (tid < 64) {
            const int b = tid >> 4, n = (tid & 15) * 2;
            ll_store(g_mod + (b * MODN + cta * 32 + n) / 2, tall_sum(s_part, b, n), tall_sum(s_part, b, n + 1), ep);
        }
    }
    PROF(1);

    if (cta < QN / 48) {
        cons_sync();
        mbar_wait(bar_wq, 0);
        uint32_t fq[5][3][4];
        frag_load<5, 3>(fq, sbase + SM_WQ + warp * 80 * P48, P48, lane);
        {
            long long t0 = 0;
            for (;;) {
                bool ok = true;
#pragma unroll
                for (int r = 0; r < 5; ++r) {
                    const int i = tid + r * NCONS, b = i / 320, c4 = i - b * 320;
                    const uint4 v = ll_ld2(g_mod + b * (MODN / 2) + 2 * c4);
                    *(uint2*)(s_part + b * DM + 2 * c4) = make_uint2(v.x, v.z);
                    ok = ok && v.y == ep && v.w == ep;
                }
                if (ok) break;
                if (t0 == 0) t0 = clock64();
                else if (clock64() - t0 > WAIT_LIMIT_CYCLES) __trap();
            }
        }
        cons_sync();
        PROF(2);
        uint32_t sh[5], sc[5];
#pragma unroll
        for (int i = 0; i < 5; ++i) {
            sh[i] = ((const uint32_t*)s_part)[lrow * DM + lcol / 2 + i];
            sc[i] = ((const uint32_t*)s_part)[lrow * DM + DM / 2 + lcol / 2 + i];
        }
        modulate(nv, sh, sc, h_dst);
        cons_sync();
        frag_mma<5, 3>(fq, sbase + SM_A + warp * 160, A_PITCH, s_part + warp * 320, lane);
        cons_sync();
        if (tid < 96) {
            const int b = tid / 24, n = (tid - b * 24) * 2;
            ll_store(g_q + (b * QN + cta * 48 + n) / 2, tall_sum(s_part, b, n), tall_sum(s_part, b, n + 1), ep);
        }
    }
    PROF(3);
    if (tid == 0 && (!HAND_EARLY || cta >= QN / 48)) {
#pragma unroll 1
        for (int s = PRE; s < NST; ++s) mbar_arrive(bar_empty + s * 8);
    }
    uint32_t m_ga[5], m_sb[5], m_cb[5], m_fa[1] = {0u}, m_fb[1] = {0u};
    const int fcta = cta - ((int)gridDim.x - DM / 32);
    if (GU_AT == 0 && cta < FF / 16 && tid == 0) {
        mbar_expect_tx(bar_gu, 2 * DM * 32);
        tma_block(sbase + SM_W32, &tm_gate, cta * 16, 0, DM, 32, bar_gu);
        tma_block(sbase + SM_W32 + DM * 32, &tm_up, cta * 16, 0, DM, 32, bar_gu);
    }
    PROF(4);

    {
        const int sub = lane & 7, grp = lane >> 3;
        for (int u0 = warp * TPI;; u0 += 8 * TPI) {
            int item = -1;
            if (s_tag[u0 % NST] == u0 || tag_wait_stop(s_tag + u0 % NST, u0, s_item + NST)) item = s_item[u0 % NST];
            if ((u0 >= 8 * TPI && u0 < 16 * TPI) || (item < 0 && u0 < 8 * TPI)) {
                if (cta < FF / 16) {
                    ll_get(mod_row + DM, m_ga, ep);
                    ll_get(mod_row + 3 * DM / 2, m_sb, ep);
                    ll_get(mod_row + 2 * DM, m_cb, ep);
                }
                if (tid < 64 && fcta >= 0) {
                    ll_get(g_mod + ((tid >> 4) * MODN + 2 * DM + fcta * 32) / 2 + (tid & 15), m_fa, ep);
                    ll_get(g_mod + ((tid >> 4) * MODN + 5 * DM + fcta * 32) / 2 + (tid & 15), m_fb, ep);
                }
            }
            if (item < 0) break;
            const int bh = (item & (NITEM_K - 1)) / CHUNKS;
            if (item < NITEM_K) {
                unsigned int* gs = g_s + (size_t)item * ITEM_KEYS;
                float qr[24];
                {
                    const unsigned long long* qp = g_q + ((bh >> 5) * QN + (bh & 31) * DH) / 2 + sub * 4;
                    long long t0 = 0;
                    for (;;) {
                        bool ok = true;
#pragma unroll
                        for (int j = 0; j < 6; ++j) {
                            const uint4 v = ll_ld2(qp + (j >> 1) * 32 + (j & 1) * 2);
                            qr[j * 4 + 0] = bf_lo(v.x); qr[j * 4 + 1] = bf_hi(v.x);
                            qr[j * 4 + 2] = bf_lo(v.z); qr[j * 4 + 3] = bf_hi(v.z);
                            ok = ok && v.y == ep && v.w == ep;
                        }
                        if (ok) break;
                        if (t0 == 0) t0 = clock64();
                        else if (clock64() - t0 > WAIT_LIMIT_CYCLES) __trap();
                    }
                }
                float m_run = -INFINITY, l_run = 0.f;
#pragma unroll 1
                for (int hh = 0; hh < 2 * TPI; ++hh) {
                    const int u = u0 + (hh >> 1), st = u % NST;
                    if (!(hh & 1)) stage_wait(bar_full, s_tag, u);
                    const uint4* tile = (const uint4*)(smem + SM_RING + st * STAGE_BYTES) + (hh & 1) * (32 * 24);
                    float part[8];
#pragma unroll
                    for (int it = 0; it < 8; ++it) {
                        const uint4* row = tile + (it * 4 + grp) * 24 + sub;
                        const uint4 a = row[0], b = row[8], c = row[16];
                        part[it] = dot8(a, qr) + dot8(b, qr + 8) + dot8(c, qr + 16);
                    }
                    if (hh & 1) {
                        __syncwarp();
                        if (lane == 0) mbar_arrive(bar_empty + st * 8);
                    }
#pragma unroll
                    for (int j = 0; j < 4; ++j) {
                        const float send = (sub & 4) ? part[j] : part[j + 4];
                        const float keep = (sub & 4) ? part[j + 4] : part[j];
                        part[j] = keep + __shfl_xor_sync(0xffffffffu, send, 4);
                    }
#pragma unroll
                    for (int j = 0; j < 2; ++j) {
                        const float send = (sub & 2) ? part[j] : part[j + 2];
                        const float keep = (sub & 2) ? part[j + 2] : part[j];
                        part[j] = keep + __shfl_xor_sync(0xffffffffu, send, 2);
                    }
                    {
                        const float send = (sub & 1) ? part[0] : part[1];
                        const float keep = (sub & 1) ? part[1] : part[0];
                        part[0] = keep + __shfl_xor_sync(0xffffffffu, send, 1);
                    }
                    const float s = bf16r(bf16r(part[0]) * 0.07216878364870323f);
                    asm volatile("st.relaxed.gpu.global.u32 [%0], %1;" ::"l"(gs + hh * 32 + sub * 4 + grp), "r"(__float_as_uint(s) | tag16) : "memory");
                    const float m_new = fmaxf(m_run, s);
                    l_run = l_run * __expf(m_run - m_new) + __expf(s - m_new);
                    m_run = m_new;
                }
                const float m = warp_max(m_run);
                const float l = warp_sum(l_run * __expf(m_run - m));
                if (lane == 0)
                    asm volatile("st.relaxed.gpu.global.u64 [%0], %1;" ::"l"(g_stat + item),
                                 "l"(((unsigned long long)__float_as_uint(l) << 32) | (__float_as_uint(m) | tag16)) : "memory");
            } else {
                float pr[2 * TPI];
                {
                    const unsigned int* gs = g_s + (size_t)(item - NITEM_K) * ITEM_KEYS + lane;
                    uint2 st2;
                    long long t0 = 0;
                    for (;;) {
                        st2 = ll_ld1(g_stat + bh * CHUNKS + lane);
                        bool ok = (st2.x & 0xffffu) == tag16;
#pragma unroll
                        for (int hh = 0; hh < 2 * TPI; ++hh) {
                            unsigned int w;
                            asm volatile("ld.relaxed.gpu.global.u32 %0, [%1];" : "=r"(w) : "l"(gs + hh * 32) : "memory");
                            ok = ok && (w & 0xffffu) == tag16;
                            pr[hh] = bf_hi(w);
                        }
                        if (__all_sync(0xffffffffu, ok)) break;
                        if (t0 == 0) t0 = clock64();
                        else if (clock64() - t0 > WAIT_LIMIT_CYCLES) __trap();
                    }
                    const float mi = bf_hi(st2.x);
                    const float mm = warp_max(mi);
                    const float ll = warp_sum(__uint_as_float(st2.y) * __expf(mi - mm));
#pragma unroll
                    for (int hh = 0; hh < 2 * TPI; ++hh) pr[hh] = bf16r(__fdiv_rn(__expf(pr[hh] - mm), ll));
                }
                float acc[3][8];
#pragma unroll
                for (int j = 0; j < 3; ++j)
#pragma unroll
                    for (int e = 0; e < 8; ++e) acc[j][e] = 0.f;
#pragma unroll
                for (int hh = 0; hh < 2 * TPI; ++hh) {
                    const int u = u0 + (hh >> 1), st = u % NST;
                    if (!(hh & 1)) stage_wait(bar_full, s_tag, u);
                    const uint4* tile = (const uint4*)(smem + SM_RING + st * STAGE_BYTES) + (hh & 1) * (32 * 24);
#pragma unroll
                    for (int it = 0; it < 8; ++it) {
                        const uint4* row = tile + (it * 4 + grp) * 24 + sub;
                        const uint4 a = row[0], b = row[8], c = row[16];
                        const float p = __shfl_sync(0xffffffffu, pr[hh], it * 4 + grp);
                        fma8(acc[0], a, p);
                        fma8(acc[1], b, p);
                        fma8(acc[2], c, p);
                    }
                    if (hh & 1) {
                        __syncwarp();
                        if (lane == 0) mbar_arrive(bar_empty + st * 8);
                    }
                }
                float* go = acc_o + (bh >> 5) * QN + (bh & 31) * DH + sub * 8;
#pragma unroll
                for (int j = 0; j < 3; ++j) {
#pragma unroll
                    for (int e = 0; e < 8; ++e) {
                        float v = acc[j][e];
                        v += __shfl_xor_sync(0xffffffffu, v, 8);
                        v += __shfl_xor_sync(0xffffffffu, v, 16);
                        acc[j][e] = v;
                    }
                    if (grp == 0) {
                        red_add_v4(go + j * 64, acc[j][0], acc[j][1], acc[j][2], acc[j][3]);
                        red_add_v4(go + j * 64 + 4, acc[j][4], acc[j][5], acc[j][6], acc[j][7]);
                    }
                }
            }
        }
    }
    PROF(5);
    grid_arrive(&g_bar[2], tid);
    PROF(6);
    if (cta < 128) {
        const int u_end = WO_AT == 1 ? s_item[NST] : 0;
        if (WO_AT == 0 && tid == 0) {
            mbar_expect_tx(bar_wo, WO_ROWS * P80);
#pragma unroll 1
            for (int j = 0; j < WO_ROWS / BOX; ++j) tma2d(sbase + SM_RING + j * STAGE_BYTES, &tm_o, ns * 80, ks * WO_ROWS + j * BOX, bar_wo);
        }
        if (GU_AT == 2 && cta < FF / 16 && tid == 0) {
            mbar_expect_tx(bar_gu, 2 * DM * 32);
            tma_block(sbase + SM_W32, &tm_gate, cta * 16, 0, DM, 32, bar_gu);
            tma_block(sbase + SM_W32 + DM * 32, &tm_up, cta * 16, 0, DM, 32, bar_gu);
        }
        uint32_t fd[3][1][5][4];
        mbar_wait(bar_wo, 0);
#pragma unroll
        for (int k = 0; k < 3; ++k) {
            const int kk = warp * 3 + k;
            frag_load<1, 5>(fd[k], sbase + SM_RING + ((u_end + (kk >> 3)) % NST) * STAGE_BYTES + (kk & 7) * 16 * P80, P80, lane);
        }
        grid_wait(&g_bar[2], target, tid);
        if (cta == 0 && tid == 0) { g_work = 0u; g_epoch = ep; }
        PROF(7);
#pragma unroll
        for (int r = 0; r < 2; ++r) {
            const int i = tid + r * NCONS;
            if (i < NB * WO_ROWS / 4) {
                const int b = i / 96, c4 = i - b * 96;
                const float4 v = __ldcg((const float4*)(acc_o + b * QN + ks * WO_ROWS) + c4);
                __nv_bfloat162 p0 = __floats2bfloat162_rn(v.x, v.y), p1 = __floats2bfloat162_rn(v.z, v.w);
                uint2 w2;
                w2.x = *(uint32_t*)&p0; w2.y = *(uint32_t*)&p1;
                *(uint2*)(smem + SM_A + b * A_PITCH + c4 * 8) = w2;
            }
        }
        cons_sync();
        frag_mma<3, 5>(*(const uint32_t (*)[3][5][4])fd, sbase + SM_A + warp * 96, A_PITCH, s_part + warp * 320, lane);
        cons_sync();
        if (tid < 80) {
            const int b = tid / 20, n4 = tid - b * 20;
            float4 s4 = make_float4(0.f, 0.f, 0.f, 0.f);
#pragma unroll
            for (int w = 0; w < 8; ++w) {
                const float4 v = *(const float4*)(s_part + (w * 4 + b) * 80 + n4 * 4);
                s4.x += v.x; s4.y += v.y; s4.z += v.z; s4.w += v.w;
            }
            red_add_v4(acc_attn + b * DM + ns * 80 + n4 * 4, s4.x, s4.y, s4.z, s4.w);
        }
        PROF(8);
        grid_arrive(&g_bar[3], tid);
    }
    const bool has_e = cta < FF / 16;
    if (!has_e && fcta < 0) return;
    if (fcta >= 0 && tid == 0) {
        mbar_expect_tx(bar_wd, FF * P32);
        tma_block(sbase + SM_WD, &tm_down, fcta * 32, 0, FF, P32, bar_wd);
    }
    if (has_e) {
        uint32_t fe[5][2][4];
        mbar_wait(bar_gu, 0);
        frag_load<5, 2>(fe, sbase + SM_W32 + warp * 80 * 32, 32, lane, DM * 32);
        grid_wait(&g_bar[3], ep * 128u, tid);
        PROF(9);
        {
            float4 v[3];
#pragma unroll
            for (int r = 0; r < 3; ++r)
                if (tid + r * NCONS < NB * DM / 4) v[r] = __ldcg((const float4*)acc_attn + tid + r * NCONS);
#pragma unroll
            for (int r = 0; r < 3; ++r)
                if (tid + r * NCONS < NB * DM / 4) ((float4*)s_part)[tid + r * NCONS] = v[r];
        }
        cons_sync();
#pragma unroll
        for (int i = 0; i < 5; ++i) {
            const float2 av = *((const float2*)(s_part + lrow * DM + lcol) + i);
            const float2 xv = *((const float2*)(s_xp + lrow * DM + lcol) + i);
            nv[2 * i] = bf16r(xv.x + bf16r(bf_lo(m_ga[i]) * bf16r(av.x)));
            nv[2 * i + 1] = bf16r(xv.y + bf16r(bf_hi(m_ga[i]) * bf16r(av.y)));
        }
        ln_norm(nv, s_red, tid);
        modulate(nv, m_sb, m_cb, h_dst);
        cons_sync();
        frag_mma<5, 2>(fe, sbase + SM_A + warp * 160, A_PITCH, s_part + warp * 320, lane);
        cons_sync();
        if (tid < 32) {
            const int b = tid >> 3, n = (tid & 7) * 2;
            const float g0 = bf16r(tall_sum(s_part, b, n)), g1 = bf16r(tall_sum(s_part, b, n + 1));
            const float u0 = bf16r(tall_sum(s_part, b, 16 + n)), u1 = bf16r(tall_sum(s_part, b, 17 + n));
            ll_store(g_act + (b * FF + cta * 16 + n) / 2, bf16r(gelu_tanh(g0)) * u0, bf16r(gelu_tanh(g1)) * u1, ep);
        }
        PROF(10);
        if (fcta < 0) return;
    } else {
        grid_wait(&g_bar[3], ep * 128u, tid);
    }
    {
        float x10 = 0.f, x11 = 0.f;
        if (tid < 64) {
            const int b = tid >> 4, col = fcta * 32 + (tid & 15) * 2;
            const float2 av = __ldcg((const float2*)(acc_attn + b * DM + col));
            x10 = bf16r(s_xp[b * DM + col] + bf16r(bf_lo(m_fa[0]) * bf16r(av.x)));
            x11 = bf16r(s_xp[b * DM + col + 1] + bf16r(bf_hi(m_fa[0]) * bf16r(av.y)));
        }
        mbar_wait(bar_wd, 0);
        uint32_t ff[12][2][4];
        frag_load<12, 2>(ff, sbase + SM_WD + warp * 192 * P32, P32, lane);
        long long t0 = 0;
        for (;;) {
            bool ok = true;
#pragma unroll
            for (int r = 0; r < 6; ++r) {
                const int i = tid + r * NCONS, b = i / 384, c4 = i - b * 384;
                const uint4 v = ll_ld2(g_act + 2 * i);
                *(uint2*)(smem + SM_ACT + b * ACT_PITCH + c4 * 8) = make_uint2(v.x, v.z);
                ok = ok && v.y == ep && v.w == ep;
            }
            if (ok) break;
            if (t0 == 0) t0 = clock64();
            else if (clock64() - t0 > WAIT_LIMIT_CYCLES) __trap();
        }
        cons_sync();
        PROF(11);
        frag_mma<12, 2>(ff, sbase + SM_ACT + warp * 384, ACT_PITCH, s_part + warp * 320, lane);
        cons_sync();
        if (tid < 64) {
            const int b = tid >> 4, n = (tid & 15) * 2;
            const float f0 = bf16r(tall_sum(s_part, b, n)), f1 = bf16r(tall_sum(s_part, b, n + 1));
            *(__nv_bfloat162*)(out + b * DM + fcta * 32 + n) =
                __floats2bfloat162_rn(x10 + bf16r(bf_lo(m_fb[0]) * f0), x11 + bf16r(bf_hi(m_fb[0]) * f1));
        }
    }
    PROF(12);
}

}

extern "C" void kernel_launch(void* const* d_in, const int* in_sizes, int n_in, void* d_out, int out_size) {
    (void)in_sizes; (void)n_in; (void)out_size;
    const __nv_bfloat16* A_x = (const __nv_bfloat16*)d_in[0];
    const __nv_bfloat16* A_k = (const __nv_bfloat16*)d_in[1];
    const __nv_bfloat16* A_v = (const __nv_bfloat16*)d_in[2];
    const __nv_bfloat16* A_wq = (const __nv_bfloat16*)d_in[3];
    const __nv_bfloat16* A_wo = (const __nv_bfloat16*)d_in[4];
    const __nv_bfloat16* B_wg = (const __nv_bfloat16*)d_in[6];
    const __nv_bfloat16* B_wu = (const __nv_bfloat16*)d_in[7];
    const __nv_bfloat16* B_wd = (const __nv_bfloat16*)d_in[8];
    const __nv_bfloat16* c = (const __nv_bfloat16*)d_in[9];
    const __nv_bfloat16* w_mod = (const __nv_bfloat16*)d_in[10];
    typedef CUresult (*encode_fn)(CUtensorMap*, CUtensorMapDataType, cuuint32_t, void*, const cuuint64_t*, const cuuint64_t*,
                                  const cuuint32_t*, const cuuint32_t*, CUtensorMapInterleave, CUtensorMapSwizzle,
                                  CUtensorMapL2promotion, CUtensorMapFloatOOBfill);
    static int grid = 0;
    static encode_fn encode = nullptr;
    if (grid == 0) {
        cudaFuncSetAttribute(decode_block_kernel, cudaFuncAttributeMaxDynamicSharedMemorySize, SM_TOTAL);
        int dev = 0, sms = 0;
        cudaGetDevice(&dev);
        cudaDeviceGetAttribute(&sms, cudaDevAttrMultiProcessorCount, dev);
        grid = sms < 132 ? sms : 132;
        void* fn = nullptr;
        cudaDriverEntryPointQueryResult qres;
        cudaGetDriverEntryPoint("cuTensorMapEncodeTiled", &fn, cudaEnableDefault, &qres);
        encode = (encode_fn)fn;
    }
    auto make_map = [&](const __nv_bfloat16* w, int rows, int cols, int box_bytes) {
        CUtensorMap m;
        const cuuint64_t dims[2] = {(cuuint64_t)cols, (cuuint64_t)rows};
        const cuuint64_t strides[1] = {(cuuint64_t)cols * 2};
        const cuuint32_t box[2] = {(cuuint32_t)(box_bytes / 2), (cuuint32_t)BOX};
        const cuuint32_t estr[2] = {1, 1};
        encode(&m, CU_TENSOR_MAP_DATA_TYPE_BFLOAT16, 2, (void*)w, dims, strides, box, estr, CU_TENSOR_MAP_INTERLEAVE_NONE,
               CU_TENSOR_MAP_SWIZZLE_NONE, CU_TENSOR_MAP_L2_PROMOTION_L2_128B, CU_TENSOR_MAP_FLOAT_OOB_FILL_NONE);
        return m;
    };
    decode_block_kernel<<<grid, NTHREADS, SM_TOTAL>>>(A_x, A_k, A_v, c, (__nv_bfloat16*)d_out, make_map(w_mod, DM, MODN, P32),
                                                      make_map(A_wq, DM, QN, P48), make_map(A_wo, QN, DM, P80),
                                                      make_map(B_wg, DM, FF, 32), make_map(B_wu, DM, FF, 32),
                                                      make_map(B_wd, FF, DM, P32));
}
```

```cpp
#include <cuda.h>
#include <cuda_runtime.h>
#include <cuda_bf16.h>
#include <stdint.h>

namespace {

constexpr int NB = 4;
constexpr int DM = 640;
constexpr int NH = 32;
constexpr int SK = 4096;
constexpr int DH = 192;
constexpr int FF = 1536;
constexpr int MODN = 6 * DM;
constexpr int QN = NH * DH;
constexpr int NBH = NB * NH;

constexpr int NCONS = 256;
constexpr int NTHREADS = NCONS + 32;
constexpr int TILE_KEYS = 64;
constexpr int TILE_BYTES = TILE_KEYS * DH * 2;
constexpr int STAGE_BYTES = TILE_BYTES;
constexpr int NST = 6;
constexpr int PRE = 3;
constexpr int TPI = 2;
constexpr int ITEM_KEYS = TPI * TILE_KEYS;
constexpr int CHUNKS = SK / ITEM_KEYS;
constexpr int NITEM_K = NBH * CHUNKS;
constexpr int NITEM = 2 * NITEM_K;

constexpr int A_PITCH = 1296;
constexpr int ACT_PITCH = FF * 2 + 16;
constexpr int P32 = 80;
constexpr int P48 = 112;
constexpr int P80 = 176;
constexpr int WO_ROWS = 512;
constexpr int ND = QN / WO_ROWS * 8;
constexpr int BOX = 128;

constexpr int SM_RING = 0;
constexpr int SM_WQ = PRE * STAGE_BYTES;
constexpr int SM_WD = 0;
constexpr int SM_W32 = NST * STAGE_BYTES;
constexpr int SM_ACT = SM_W32;
constexpr int SM_A = SM_W32 + DM * P32;
constexpr int SM_PART = SM_A + NB * A_PITCH;
constexpr int SM_XP = SM_PART + 8 * 4 * 80 * 4;
constexpr int SM_RED = SM_XP + NB * DM * 4;
constexpr int SM_ITEM = SM_RED + 16 * 4;
constexpr int SM_TAG = SM_ITEM + 16 * 4;
constexpr int SM_BAR = SM_TAG + 16 * 4;
constexpr int SM_TOTAL = SM_BAR + (2 * NST + 5) * 8;
static_assert(SM_WQ + DM * P48 <= NST * STAGE_BYTES, "prologue overlay");
static_assert(SM_WD + FF * P32 <= NST * STAGE_BYTES && BOX * P80 <= STAGE_BYTES, "tail overlay");
static_assert(SM_TOTAL <= 232448, "smem");
constexpr int THR_ITEMS = 6;
constexpr int THR_DEPTH = 4;

__device__ __align__(128) unsigned long long g_mod[NB * MODN / 2];
__device__ __align__(128) unsigned long long g_q[NB * QN / 2];
__device__ __align__(128) unsigned long long g_act[NB * FF / 2];
__device__ __align__(128) unsigned int g_s[NBH * SK];
__device__ __align__(128) unsigned long long g_stat[NBH * CHUNKS];
__device__ __align__(128) float g_o[2][NB * QN];
__device__ __align__(128) float g_attn[2][NB * DM];
__device__ __align__(128) unsigned int g_bar[8];
__device__ unsigned int g_work;
__device__ unsigned int g_epoch;

#define PROF(k) do { } while (0)
#define PROFP(k) do { } while (0)

__device__ __forceinline__ float bf16r(float x) { return __bfloat162float(__float2bfloat16_rn(x)); }
__device__ __forceinline__ float bf_lo(uint32_t u) { return __uint_as_float(u << 16); }
__device__ __forceinline__ float bf_hi(uint32_t u) { return __uint_as_float(u & 0xffff0000u); }

__device__ __forceinline__ uint32_t smem_u32(const void* p) { return (uint32_t)__cvta_generic_to_shared(p); }
__device__ __forceinline__ void mbar_init(uint32_t bar, uint32_t count) {
    asm volatile("mbarrier.init.shared::cta.b64 [%0], %1;" ::"r"(bar), "r"(count) : "memory");
}
__device__ __forceinline__ void mbar_expect_tx(uint32_t bar, uint32_t bytes) {
    asm volatile("mbarrier.arrive.expect_tx.shared::cta.b64 _, [%0], %1;" ::"r"(bar), "r"(bytes) : "memory");
}
__device__ __forceinline__ void mbar_arrive(uint32_t bar) {
    asm volatile("mbarrier.arrive.shared::cta.b64 _, [%0];" ::"r"(bar) : "memory");
}
constexpr long long WAIT_LIMIT_CYCLES = 200000000LL;
__device__ __forceinline__ uint32_t mbar_try(uint32_t bar, uint32_t parity) {
    uint32_t done;
    asm volatile(
        "{\n\t.reg .pred p;\n\t"
        "mbarrier.try_wait.parity.shared::cta.b64 p, [%1], %2;\n\t"
        "selp.u32 %0, 1, 0, p;\n\t}"
        : "=r"(done) : "r"(bar), "r"(parity) : "memory");
    return done;
}
__device__ __noinline__ void mbar_wait_slow(uint32_t bar, uint32_t parity) {
    const long long t0 = clock64();
    while (!mbar_try(bar, parity)) {
        if (clock64() - t0 > WAIT_LIMIT_CYCLES) __trap();
    }
}
__device__ __forceinline__ void mbar_wait(uint32_t bar, uint32_t parity) {
    if (!mbar_try(bar, parity)) mbar_wait_slow(bar, parity);
}
__device__ __noinline__ void tag_wait_slow(volatile int* tag, int u) {
    const long long t0 = clock64();
    while (*tag != u) {
        __nanosleep(32);
        if (clock64() - t0 > WAIT_LIMIT_CYCLES) __trap();
    }
}
__device__ __noinline__ bool tag_wait_stop(volatile int* tag, int u, volatile int* stop) {
    const long long t0 = clock64();
    while (*tag != u) {
        if (*stop <= u) return false;
        __nanosleep(32);
        if (clock64() - t0 > WAIT_LIMIT_CYCLES) __trap();
    }
    return true;
}
__device__ __forceinline__ void stage_wait(uint32_t bar_full, volatile int* s_tag, int u) {
    const int st = u % NST;
    if (s_tag[st] != u) tag_wait_slow(s_tag + st, u);
    mbar_wait(bar_full + st * 8, (u / NST) & 1);
}
__device__ __forceinline__ void bulk_g2s(uint32_t dst, const void* src, uint32_t bytes, uint32_t bar, uint64_t pol) {
    asm volatile(
        "cp.async.bulk.shared::cluster.global.mbarrier::complete_tx::bytes.L2::cache_hint [%0], [%1], %2, [%3], %4;"
        ::"r"(dst), "l"(src), "r"(bytes), "r"(bar), "l"(pol) : "memory");
}
__device__ __forceinline__ void tma2d(uint32_t dst, const CUtensorMap* map, int col, int row, uint32_t bar) {
    asm volatile(
        "cp.async.bulk.tensor.2d.shared::cluster.global.tile.mbarrier::complete_tx::bytes [%0], [%1, {%2, %3}], [%4];"
        ::"r"(dst), "l"(map), "r"(col), "r"(row), "r"(bar) : "memory");
}
__device__ __forceinline__ void tma_block(uint32_t dst, const CUtensorMap* map, int col, int row, int rows, int pitch, uint32_t bar) {
#pragma unroll 1
    for (int r = 0; r < rows; r += BOX) tma2d(dst + r * pitch, map, col, row + r, bar);
}
__device__ __forceinline__ void red_release_add(unsigned int* p, unsigned int v) {
    asm volatile("red.release.gpu.global.add.u32 [%0], %1;" ::"l"(p), "r"(v) : "memory");
}
__device__ __forceinline__ void cons_sync() { asm volatile("bar.sync 1, 256;" ::: "memory"); }

__device__ __forceinline__ void red_add_v4(float* p, float a, float b, float c, float d) {
    asm volatile("red.global.add.v4.f32 [%0], {%1, %2, %3, %4};" ::"l"(p), "f"(a), "f"(b), "f"(c), "f"(d) : "memory");
}
__device__ __forceinline__ unsigned int ld_acquire(const unsigned int* p) {
    unsigned int v;
    asm volatile("ld.acquire.gpu.global.u32 %0, [%1];" : "=r"(v) : "l"(p) : "memory");
    return v;
}
__device__ __forceinline__ void ll_store(unsigned long long* p, float a, float b, unsigned int ep) {
    __nv_bfloat162 v = __floats2bfloat162_rn(a, b);
    const unsigned long long w = ((unsigned long long)ep << 32) | *(uint32_t*)&v;
    asm volatile("st.relaxed.gpu.global.u64 [%0], %1;" ::"l"(p), "l"(w) : "memory");
}
__device__ __forceinline__ uint2 ll_ld1(const unsigned long long* p) {
    unsigned long long w;
    asm volatile("ld.relaxed.gpu.global.u64 %0, [%1];" : "=l"(w) : "l"(p) : "memory");
    return make_uint2((uint32_t)w, (uint32_t)(w >> 32));
}
__device__ __forceinline__ uint4 ll_ld2(const unsigned long long* p) {
    unsigned long long a, b;
    asm volatile("ld.relaxed.gpu.global.v2.u64 {%0, %1}, [%2];" : "=l"(a), "=l"(b) : "l"(p) : "memory");
    return make_uint4((uint32_t)a, (uint32_t)(a >> 32), (uint32_t)b, (uint32_t)(b >> 32));
}
template <int N>
__device__ __forceinline__ void ll_get(const unsigned long long* p, uint32_t (&d)[N], unsigned int ep) {
    long long t0 = 0;
    for (;;) {
        bool ok = true;
#pragma unroll
        for (int i = 0; i < N; ++i) {
            const uint2 v = ll_ld1(p + i);
            d[i] = v.x;
            ok = ok && (v.y == ep);
        }
        if (ok) break;
        if (t0 == 0) t0 = clock64();
        else if (clock64() - t0 > WAIT_LIMIT_CYCLES) __trap();
    }
}

__device__ __forceinline__ void grid_arrive(unsigned int* ctr, int tid) {
    cons_sync();
    if (tid == 0) red_release_add(ctr, 1u);
}
__device__ __noinline__ void grid_wait(const unsigned int* ctr, unsigned int target, int tid) {
    if (tid == 0) {
        const long long t0 = clock64();
        while ((int)(ld_acquire(ctr) - target) < 0) {
            if (clock64() - t0 > WAIT_LIMIT_CYCLES) __trap();
        }
    }
    cons_sync();
}

__device__ __forceinline__ float warp_sum(float v) {
#pragma unroll
    for (int o = 16; o > 0; o >>= 1) v += __shfl_xor_sync(0xffffffffu, v, o);
    return v;
}
__device__ __forceinline__ float warp_max(float v) {
#pragma unroll
    for (int o = 16; o > 0; o >>= 1) v = fmaxf(v, __shfl_xor_sync(0xffffffffu, v, o));
    return v;
}

__device__ __forceinline__ void fma8(float (&acc)[8], const uint4& w, float s) {
    acc[0] = fmaf(s, bf_lo(w.x), acc[0]);
    acc[1] = fmaf(s, bf_hi(w.x), acc[1]);
    acc[2] = fmaf(s, bf_lo(w.y), acc[2]);
    acc[3] = fmaf(s, bf_hi(w.y), acc[3]);
    acc[4] = fmaf(s, bf_lo(w.z), acc[4]);
    acc[5] = fmaf(s, bf_hi(w.z), acc[5]);
    acc[6] = fmaf(s, bf_lo(w.w), acc[6]);
    acc[7] = fmaf(s, bf_hi(w.w), acc[7]);
}
__device__ __forceinline__ float dot8(const uint4& w, const float* q) {
    float s = q[0] * bf_lo(w.x);
    s = fmaf(q[1], bf_hi(w.x), s);
    s = fmaf(q[2], bf_lo(w.y), s);
    s = fmaf(q[3], bf_hi(w.y), s);
    s = fmaf(q[4], bf_lo(w.z), s);
    s = fmaf(q[5], bf_hi(w.z), s);
    s = fmaf(q[6], bf_lo(w.w), s);
    s = fmaf(q[7], bf_hi(w.w), s);
    return s;
}

template <int KS, int NT>
__device__ __noinline__ void gemv_mma(uint32_t w, int w_pitch, uint32_t a, int a_pitch, float* part, int lane) {
    float c[NT][4];
#pragma unroll
    for (int nt = 0; nt < NT; ++nt) { c[nt][0] = 0.f; c[nt][1] = 0.f; c[nt][2] = 0.f; c[nt][3] = 0.f; }
    const uint32_t ap = a + (lane >> 2) * a_pitch + (lane & 3) * 4;
    const uint32_t wp = w + ((lane & 7) + ((lane >> 4) << 3)) * w_pitch + ((lane >> 3) & 1) * 16;
#pragma unroll
    for (int ks = 0; ks < KS; ++ks) {
        uint32_t b0 = 0, b1 = 0;
        if (lane < 16) {
            asm("ld.shared.u32 %0, [%1];" : "=r"(b0) : "r"(ap + ks * 32));
            asm("ld.shared.u32 %0, [%1];" : "=r"(b1) : "r"(ap + ks * 32 + 16));
        }
#pragma unroll
        for (int nt = 0; nt < NT; ++nt) {
            uint32_t a0, a1, a2, a3;
            asm("ldmatrix.sync.aligned.m8n8.x4.trans.shared.b16 {%0, %1, %2, %3}, [%4];"
                         : "=r"(a0), "=r"(a1), "=r"(a2), "=r"(a3) : "r"(wp + ks * 16 * w_pitch + nt * 32));
            asm("mma.sync.aligned.m16n8k16.row.col.f32.bf16.bf16.f32 {%0, %1, %2, %3}, {%4, %5, %6, %7}, "
                "{%8, %9}, {%0, %1, %2, %3};"
                : "+f"(c[nt][0]), "+f"(c[nt][1]), "+f"(c[nt][2]), "+f"(c[nt][3])
                : "r"(a0), "r"(a1), "r"(a2), "r"(a3), "r"(b0), "r"(b1));
        }
    }
    if ((lane & 3) < 2) {
        float* pp = part + (lane & 3) * 160 + (lane >> 2);
#pragma unroll
        for (int nt = 0; nt < NT; ++nt) {
            pp[nt * 16] = c[nt][0];
            pp[nt * 16 + 80] = c[nt][1];
            pp[nt * 16 + 8] = c[nt][2];
            pp[nt * 16 + 88] = c[nt][3];
        }
    }
}

template <int KS, int NT>
__device__ __forceinline__ void frag_load(uint32_t (&f)[KS][NT][4], uint32_t w, int w_pitch, int lane, int n_stride = 32) {
    const uint32_t wp = w + ((lane & 7) + ((lane >> 4) << 3)) * w_pitch + ((lane >> 3) & 1) * 16;
#pragma unroll
    for (int ks = 0; ks < KS; ++ks)
#pragma unroll
        for (int nt = 0; nt < NT; ++nt)
            asm volatile("ldmatrix.sync.aligned.m8n8.x4.trans.shared.b16 {%0, %1, %2, %3}, [%4];"
                         : "=r"(f[ks][nt][0]), "=r"(f[ks][nt][1]), "=r"(f[ks][nt][2]), "=r"(f[ks][nt][3])
                         : "r"(wp + ks * 16 * w_pitch + nt * n_stride) : "memory");
}
template <int KS, int NT>
__device__ __forceinline__ void frag_mma(const uint32_t (&f)[KS][NT][4], uint32_t a, int a_pitch, float* part, int lane) {
    float c[NT][4];
#pragma unroll
    for (int nt = 0; nt < NT; ++nt) { c[nt][0] = 0.f; c[nt][1] = 0.f; c[nt][2] = 0.f; c[nt][3] = 0.f; }
    const uint32_t ap = a + (lane >> 2) * a_pitch + (lane & 3) * 4;
    uint32_t b[KS][2];
#pragma unroll
    for (int ks = 0; ks < KS; ++ks) {
        b[ks][0] = 0; b[ks][1] = 0;
        if (lane < 16) {
            asm volatile("ld.shared.u32 %0, [%1];" : "=r"(b[ks][0]) : "r"(ap + ks * 32) : "memory");
            asm volatile("ld.shared.u32 %0, [%1];" : "=r"(b[ks][1]) : "r"(ap + ks * 32 + 16) : "memory");
        }
    }
#pragma unroll
    for (int ks = 0; ks < KS; ++ks)
#pragma unroll
        for (int nt = 0; nt < NT; ++nt)
            asm("mma.sync.aligned.m16n8k16.row.col.f32.bf16.bf16.f32 {%0, %1, %2, %3}, {%4, %5, %6, %7}, "
                "{%8, %9}, {%0, %1, %2, %3};"
                : "+f"(c[nt][0]), "+f"(c[nt][1]), "+f"(c[nt][2]), "+f"(c[nt][3])
                : "r"(f[ks][nt][0]), "r"(f[ks][nt][1]), "r"(f[ks][nt][2]), "r"(f[ks][nt][3]), "r"(b[ks][0]), "r"(b[ks][1]));
    if ((lane & 3) < 2) {
        float* pp = part + (lane & 3) * 160 + (lane >> 2);
#pragma unroll
        for (int nt = 0; nt < NT; ++nt) {
            pp[nt * 16] = c[nt][0];
            pp[nt * 16 + 80] = c[nt][1];
            pp[nt * 16 + 8] = c[nt][2];
            pp[nt * 16 + 88] = c[nt][3];
        }
    }
}

__device__ __forceinline__ float tall_sum(const float* part, int b, int n) {
    float s = 0.f;
#pragma unroll
    for (int w = 0; w < 8; ++w) s += part[(w * 4 + b) * 80 + n];
    return s;
}

__device__ __forceinline__ void ln_norm(float (&v)[10], float* s_red, int tid) {
    const int warp = tid >> 5;
    const float pv = __shfl_sync(0xffffffffu, v[0], 0);
    float s = 0.f, q = 0.f;
#pragma unroll
    for (int i = 0; i < 10; ++i) { const float d = v[i] - pv; s += d; q = fmaf(d, d, q); }
#pragma unroll
    for (int o = 16; o > 0; o >>= 1) {
        s += __shfl_xor_sync(0xffffffffu, s, o);
        q += __shfl_xor_sync(0xffffffffu, q, o);
    }
    const float md = s * (2.0f / DM);
    if ((tid & 31) == 0) *(float2*)(s_red + 2 * warp) = make_float2(pv + md, fmaxf(q - s * md, 0.f));
    cons_sync();
    const float4 r = *(const float4*)(s_red + 4 * (warp >> 1));
    const float dm = r.x - r.z;
    const float var = (r.y + r.w + dm * dm * (DM / 4)) * (1.0f / DM);
    const float mean = bf16r(0.5f * (r.x + r.z));
    const float inv = __fdiv_rn(1.0f, bf16r(sqrtf(bf16r(bf16r(var) + 1e-5f))));
#pragma unroll
    for (int i = 0; i < 10; ++i) v[i] = bf16r(bf16r(v[i] - mean) * inv);
}
__device__ __forceinline__ void modulate(const float (&n)[10], const uint32_t (&sh)[5], const uint32_t (&sc)[5], uint32_t* dst) {
#pragma unroll
    for (int i = 0; i < 5; ++i) {
        const float h0 = bf16r(n[2 * i] * bf16r(1.0f + bf_lo(sc[i]))) + bf_lo(sh[i]);
        const float h1 = bf16r(n[2 * i + 1] * bf16r(1.0f + bf_hi(sc[i]))) + bf_hi(sh[i]);
        __nv_bfloat162 p = __floats2bfloat162_rn(h0, h1);
        dst[i] = *(uint32_t*)&p;
    }
}

__device__ __forceinline__ float gelu_tanh(float x) {
    const float kBeta = 0.7978845608028654f;
    const float inner = kBeta * (x + 0.044715f * x * x * x);
    return 0.5f * x * (1.0f + tanhf(inner));
}

__global__ void __launch_bounds__(NTHREADS, 1)
decode_block_kernel(const __nv_bfloat16* __restrict__ x_in, const __nv_bfloat16* __restrict__ k_cache,
                    const __nv_bfloat16* __restrict__ v_cache, const __nv_bfloat16* __restrict__ cvec,
                    __nv_bfloat16* __restrict__ out, const __grid_constant__ CUtensorMap tm_mod,
                    const __grid_constant__ CUtensorMap tm_q, const __grid_constant__ CUtensorMap tm_o,
                    const __grid_constant__ CUtensorMap tm_gate, const __grid_constant__ CUtensorMap tm_up,
                    const __grid_constant__ CUtensorMap tm_down) {
    extern __shared__ __align__(128) unsigned char smem[];
    const int tid = threadIdx.x;
    const int cta = blockIdx.x;

    const uint32_t sbase = smem_u32(smem);
    const uint32_t bar_full = sbase + SM_BAR;
    const uint32_t bar_empty = bar_full + NST * 8;
    volatile int* s_item = (volatile int*)(smem + SM_ITEM);
    volatile int* s_tag = (volatile int*)(smem + SM_TAG);

    const uint32_t bar_wm = bar_empty + NST * 8, bar_wq = bar_wm + 8, bar_wo = bar_wm + 16, bar_gu = bar_wm + 24, bar_wd = bar_wm + 32;
    PROF(0);
    const int lrow = (tid >> 6) & 3, lcol = (tid & 63) * 10;
    unsigned int ep0 = 0;
    uint4 c0 = make_uint4(0u, 0u, 0u, 0u), c1 = c0;
    uint32_t xw[5];
    if (tid < NCONS) {
        asm volatile("ld.relaxed.gpu.global.u32 %0, [%1];" : "=r"(ep0) : "l"(&g_epoch));
        asm volatile("ld.global.nc.v4.u32 {%0, %1, %2, %3}, [%4];" : "=r"(c0.x), "=r"(c0.y), "=r"(c0.z), "=r"(c0.w) : "l"((const uint4*)cvec + tid));
        if (tid < 320 - NCONS)
            asm volatile("ld.global.nc.v4.u32 {%0, %1, %2, %3}, [%4];" : "=r"(c1.x), "=r"(c1.y), "=r"(c1.z), "=r"(c1.w) : "l"((const uint4*)cvec + tid + NCONS));
#pragma unroll
        for (int i = 0; i < 5; ++i)
            asm volatile("ld.global.nc.u32 %0, [%1];" : "=r"(xw[i]) : "l"((const uint32_t*)(x_in + lrow * DM + lcol) + i));
    }
    if (tid < NST) s_tag[tid] = -1;
    if (tid == NST) s_item[NST] = 0x7fffffff;
    if (tid == NCONS) {
#pragma unroll 1
        for (int s = 0; s < 2 * NST + 5; ++s) mbar_init(bar_full + s * 8, 1);
        asm volatile("fence.mbarrier_init.release.cluster;" ::: "memory");
        asm volatile("fence.proxy.async.shared::cta;" ::: "memory");
#pragma unroll 1
        for (int s = 0; s < PRE; ++s) mbar_arrive(bar_empty + s * 8);
    }
    __syncthreads();
    const int ks = cta >> 3, ns = cta & 7;

    if (tid >= NCONS) {
        if (tid == NCONS) {
            int u = 0;
            const int G = (int)gridDim.x;
            uint64_t pol;
            asm volatile("createpolicy.fractional.L2::evict_first.b64 %0, 1.0;" : "=l"(pol));
            auto produce = [&](const int item) {
                const int it = item & (NITEM_K - 1);
                const bool is_v = item >= NITEM_K;
                const unsigned char* src = (const unsigned char*)(is_v ? v_cache : k_cache) + (size_t)it * (ITEM_KEYS * DH * 2);
#pragma unroll 1
                for (int t = 0; t < TPI; ++t, ++u) {
                    const int st = u % NST;
                    const uint32_t fb = bar_full + st * 8;
                    mbar_wait(bar_empty + st * 8, (u / NST) & 1);
                    if (item >= NITEM - THR_ITEMS * G) mbar_wait(bar_empty + ((u - THR_DEPTH) % NST) * 8, ((u - THR_DEPTH) / NST + 1) & 1);
                    s_item[st] = item;
                    s_tag[st] = u;
                    mbar_expect_tx(fb, TILE_BYTES);
                    bulk_g2s(sbase + SM_RING + st * STAGE_BYTES, src + t * TILE_BYTES, TILE_BYTES, fb, pol);
                }
            };
            if (cta < MODN / 32) {
                mbar_expect_tx(bar_wm, DM * P32);
                tma_block(sbase + SM_W32, &tm_mod, cta * 32, 0, DM, P32, bar_wm);
            }
            asm volatile("prefetch.tensormap [%0];" ::"l"(&tm_q) : "memory");
            asm volatile("prefetch.tensormap [%0];" ::"l"(&tm_o) : "memory");
            asm volatile("prefetch.tensormap [%0];" ::"l"(&tm_gate) : "memory");
            asm volatile("prefetch.tensormap [%0];" ::"l"(&tm_up) : "memory");
            asm volatile("prefetch.tensormap [%0];" ::"l"(&tm_down) : "memory");
            if (cta < MODN / 32) mbar_wait(bar_wm, 0);
            int item = cta;
#pragma unroll 1
            while (item < NITEM) {
                const int next = (int)atomicAdd(&g_work, 1u) + G;
                produce(item);
                item = next;
            }
            s_item[NST] = u;
            if (cta < ND) {
                mbar_expect_tx(bar_wo, WO_ROWS * P80);
#pragma unroll 1
                for (int j = 0; j < WO_ROWS / BOX; ++j, ++u) {
                    const int st = u % NST;
                    mbar_wait(bar_empty + st * 8, (u / NST) & 1);
                    tma2d(sbase + SM_RING + st * STAGE_BYTES, &tm_o, ns * 80, ks * WO_ROWS + j * BOX, bar_wo);
                }
            }
            PROFP(13);
        }
        return;
    }

    const int lane = tid & 31, warp = tid >> 5;
    float* s_part = (float*)(smem + SM_PART);
    float* s_xp = (float*)(smem + SM_XP);
    float* s_red = (float*)(smem + SM_RED);
    uint32_t* h_dst = (uint32_t*)(smem + SM_A + lrow * A_PITCH + lcol * 2);

    const unsigned int ep = ep0 + 1u;
    const unsigned int target = ep * gridDim.x, tag16 = ep & 0xffffu;
    const unsigned long long* mod_row = g_mod + (lrow * MODN + lcol) / 2;
    float nv[10];
    {
        const int i1 = tid + NCONS;
#pragma unroll 1
        for (int r = 0; r < 2; ++r) {
            const int i = r ? i1 : tid;
            if (i < 320) {
                const uint4 cc = r ? c1 : c0;
                const uint32_t cw[4] = {cc.x, cc.y, cc.z, cc.w};
                uint32_t ow[4];
#pragma unroll
                for (int k = 0; k < 4; ++k) {
                    const float a = bf_lo(cw[k]), b = bf_hi(cw[k]);
                    __nv_bfloat162 p = __floats2bfloat162_rn(__fdiv_rn(a, 1.0f + __expf(-a)), __fdiv_rn(b, 1.0f + __expf(-b)));
                    ow[k] = *(uint32_t*)&p;
                }
                const int b = i / 80, c8 = i - b * 80;
                *(uint4*)(smem + SM_A + b * A_PITCH + c8 * 16) = make_uint4(ow[0], ow[1], ow[2], ow[3]);
            }
        }
#pragma unroll
        for (int i = 0; i < 5; ++i) {
            nv[2 * i] = bf_lo(xw[i]);
            nv[2 * i + 1] = bf_hi(xw[i]);
            *(float2*)(s_xp + lrow * DM + lcol + 2 * i) = make_float2(nv[2 * i], nv[2 * i + 1]);
        }
        PROF(17);
        if (tid == 0 && cta < QN / 48) {
            mbar_expect_tx(bar_wq, DM * P48);
            tma_block(sbase + SM_WQ, &tm_q, cta * 48, 0, DM, P48, bar_wq);
        }
    }
    float* acc_o = g_o[ep & 1];
    float* acc_attn = g_attn[ep & 1];
    if (cta == gridDim.x - 1) {
#pragma unroll 1
        for (int i = tid; i < NB * QN / 4; i += NCONS) ((float4*)g_o[~ep & 1])[i] = make_float4(0.f, 0.f, 0.f, 0.f);
#pragma unroll 1
        for (int i = tid; i < NB * DM; i += NCONS) g_attn[~ep & 1][i] = 0.f;
    }
    ln_norm(nv, s_red, tid);
    cons_sync();
    PROF(14);
    if (cta < MODN / 32) {
        mbar_wait(bar_wm, 0);
        PROF(15);
        gemv_mma<5, 2>(sbase + SM_W32 + warp * 80 * P32, P32, sbase + SM_A + warp * 160, A_PITCH, s_part + warp * 320, lane);
        cons_sync();
        if (tid < 64) {
            const int b = tid >> 4, n = (tid & 15) * 2;
            ll_store(g_mod + (b * MODN + cta * 32 + n) / 2, tall_sum(s_part, b, n), tall_sum(s_part, b, n + 1), ep);
        }
    }
    PROF(1);

    if (cta < QN / 48) {
        cons_sync();
        mbar_wait(bar_wq, 0);
        PROF(16);
        uint32_t fq[5][3][4];
        frag_load<5, 3>(fq, sbase + SM_WQ + warp * 80 * P48, P48, lane);
        {
            long long t0 = 0;
            for (;;) {
                bool ok = true;
#pragma unroll
                for (int r = 0; r < 5; ++r) {
                    const int i = tid + r * NCONS, b = i / 320, c4 = i - b * 320;
                    const uint4 v = ll_ld2(g_mod + b * (MODN / 2) + 2 * c4);
                    *(uint2*)(s_part + b * DM + 2 * c4) = make_uint2(v.x, v.z);
                    ok = ok && v.y == ep && v.w == ep;
                }
                if (ok) break;
                if (t0 == 0) t0 = clock64();
                else if (clock64() - t0 > WAIT_LIMIT_CYCLES) __trap();
            }
        }
        cons_sync();
        PROF(2);
        uint32_t sh[5], sc[5];
#pragma unroll
        for (int i = 0; i < 5; ++i) {
            sh[i] = ((const uint32_t*)s_part)[lrow * DM + lcol / 2 + i];
            sc[i] = ((const uint32_t*)s_part)[lrow * DM + DM / 2 + lcol / 2 + i];
        }
        modulate(nv, sh, sc, h_dst);
        cons_sync();
        frag_mma<5, 3>(fq, sbase + SM_A + warp * 160, A_PITCH, s_part + warp * 320, lane);
        cons_sync();
        if (tid < 96) {
            const int b = tid / 24, n = (tid - b * 24) * 2;
            ll_store(g_q + (b * QN + cta * 48 + n) / 2, tall_sum(s_part, b, n), tall_sum(s_part, b, n + 1), ep);
        }
    }
    PROF(3);
    if (tid == 0) {
#pragma unroll 1
        for (int s = PRE; s < NST; ++s) mbar_arrive(bar_empty + s * 8);
    }
    uint32_t m_ga[5], m_sb[5], m_cb[5], m_fa[1] = {0u}, m_fb[1] = {0u};
    const int fcta = cta - ((int)gridDim.x - DM / 32);
    PROF(4);

    {
        const int sub = lane & 7, grp = lane >> 3;
        for (int u0 = warp * TPI;; u0 += 8 * TPI) {
            int item = -1;
            if (s_tag[u0 % NST] == u0 || tag_wait_stop(s_tag + u0 % NST, u0, s_item + NST)) item = s_item[u0 % NST];
            if ((u0 >= 8 * TPI && u0 < 16 * TPI) || (item < 0 && u0 < 8 * TPI)) {
                if (cta < FF / 16) {
                    ll_get(mod_row + DM, m_ga, ep);
                    ll_get(mod_row + 3 * DM / 2, m_sb, ep);
                    ll_get(mod_row + 2 * DM, m_cb, ep);
                }
                if (tid < 64 && fcta >= 0) {
                    ll_get(g_mod + ((tid >> 4) * MODN + 2 * DM + fcta * 32) / 2 + (tid & 15), m_fa, ep);
                    ll_get(g_mod + ((tid >> 4) * MODN + 5 * DM + fcta * 32) / 2 + (tid & 15), m_fb, ep);
                }
            }
            if (item < 0) break;
            const int bh = (item & (NITEM_K - 1)) / CHUNKS;
            if (item < NITEM_K) {
                unsigned int* gs = g_s + (size_t)item * ITEM_KEYS;
                float qr[24];
                {
                    const unsigned long long* qp = g_q + ((bh >> 5) * QN + (bh & 31) * DH) / 2 + sub * 4;
                    long long t0 = 0;
                    for (;;) {
                        bool ok = true;
#pragma unroll
                        for (int j = 0; j < 6; ++j) {
                            const uint4 v = ll_ld2(qp + (j >> 1) * 32 + (j & 1) * 2);
                            qr[j * 4 + 0] = bf_lo(v.x); qr[j * 4 + 1] = bf_hi(v.x);
                            qr[j * 4 + 2] = bf_lo(v.z); qr[j * 4 + 3] = bf_hi(v.z);
                            ok = ok && v.y == ep && v.w == ep;
                        }
                        if (ok) break;
                        if (t0 == 0) t0 = clock64();
                        else if (clock64() - t0 > WAIT_LIMIT_CYCLES) __trap();
                    }
                }
                float m_run = -INFINITY, l_run = 0.f;
#pragma unroll 1
                for (int hh = 0; hh < 2 * TPI; ++hh) {
                    const int u = u0 + (hh >> 1), st = u % NST;
                    if (!(hh & 1)) stage_wait(bar_full, s_tag, u);
                    const uint4* tile = (const uint4*)(smem + SM_RING + st * STAGE_BYTES) + (hh & 1) * (32 * 24);
                    float part[8];
#pragma unroll
                    for (int it = 0; it < 8; ++it) {
                        const uint4* row = tile + (it * 4 + grp) * 24 + sub;
                        const uint4 a = row[0], b = row[8], c = row[16];
                        part[it] = dot8(a, qr) + dot8(b, qr + 8) + dot8(c, qr + 16);
                    }
                    if (hh & 1) {
                        __syncwarp();
                        if (lane == 0) mbar_arrive(bar_empty + st * 8);
                    }
#pragma unroll
                    for (int j = 0; j < 4; ++j) {
                        const float send = (sub & 4) ? part[j] : part[j + 4];
                        const float keep = (sub & 4) ? part[j + 4] : part[j];
                        part[j] = keep + __shfl_xor_sync(0xffffffffu, send, 4);
                    }
#pragma unroll
                    for (int j = 0; j < 2; ++j) {
                        const float send = (sub & 2) ? part[j] : part[j + 2];
                        const float keep = (sub & 2) ? part[j + 2] : part[j];
                        part[j] = keep + __shfl_xor_sync(0xffffffffu, send, 2);
                    }
                    {
                        const float send = (sub & 1) ? part[0] : part[1];
                        const float keep = (sub & 1) ? part[1] : part[0];
                        part[0] = keep + __shfl_xor_sync(0xffffffffu, send, 1);
                    }
                    const float s = bf16r(bf16r(part[0]) * 0.07216878364870323f);
                    asm volatile("st.relaxed.gpu.global.u32 [%0], %1;" ::"l"(gs + hh * 32 + sub * 4 + grp), "r"(__float_as_uint(s) | tag16) : "memory");
                    const float m_new = fmaxf(m_run, s);
                    l_run = l_run * __expf(m_run - m_new) + __expf(s - m_new);
                    m_run = m_new;
                }
                const float m = warp_max(m_run);
                const float l = warp_sum(l_run * __expf(m_run - m));
                if (lane == 0)
                    asm volatile("st.relaxed.gpu.global.u64 [%0], %1;" ::"l"(g_stat + item),
                                 "l"(((unsigned long long)__float_as_uint(l) << 32) | (__float_as_uint(m) | tag16)) : "memory");
            } else {
                float pr[2 * TPI];
                {
                    const unsigned int* gs = g_s + (size_t)(item - NITEM_K) * ITEM_KEYS + lane;
                    uint2 st2;
                    long long t0 = 0;
                    for (;;) {
                        st2 = ll_ld1(g_stat + bh * CHUNKS + lane);
                        bool ok = (st2.x & 0xffffu) == tag16;
#pragma unroll
                        for (int hh = 0; hh < 2 * TPI; ++hh) {
                            unsigned int w;
                            asm volatile("ld.relaxed.gpu.global.u32 %0, [%1];" : "=r"(w) : "l"(gs + hh * 32) : "memory");
                            ok = ok && (w & 0xffffu) == tag16;
                            pr[hh] = bf_hi(w);
                        }
                        if (__all_sync(0xffffffffu, ok)) break;
                        if (t0 == 0) t0 = clock64();
                        else if (clock64() - t0 > WAIT_LIMIT_CYCLES) __trap();
                    }
                    const float mi = bf_hi(st2.x);
                    const float mm = warp_max(mi);
                    const float ll = warp_sum(__uint_as_float(st2.y) * __expf(mi - mm));
#pragma unroll
                    for (int hh = 0; hh < 2 * TPI; ++hh) pr[hh] = bf16r(__fdiv_rn(__expf(pr[hh] - mm), ll));
                }
                float acc[3][8];
#pragma unroll
                for (int j = 0; j < 3; ++j)
#pragma unroll
                    for (int e = 0; e < 8; ++e) acc[j][e] = 0.f;
#pragma unroll
                for (int hh = 0; hh < 2 * TPI; ++hh) {
                    const int u = u0 + (hh >> 1), st = u % NST;
                    if (!(hh & 1)) stage_wait(bar_full, s_tag, u);
                    const uint4* tile = (const uint4*)(smem + SM_RING + st * STAGE_BYTES) + (hh & 1) * (32 * 24);
#pragma unroll
                    for (int it = 0; it < 8; ++it) {
                        const uint4* row = tile + (it * 4 + grp) * 24 + sub;
                        const uint4 a = row[0], b = row[8], c = row[16];
                        const float p = __shfl_sync(0xffffffffu, pr[hh], it * 4 + grp);
                        fma8(acc[0], a, p);
                        fma8(acc[1], b, p);
                        fma8(acc[2], c, p);
                    }
                    if (hh & 1) {
                        __syncwarp();
                        if (lane == 0) mbar_arrive(bar_empty + st * 8);
                    }
                }
                float* go = acc_o + (bh >> 5) * QN + (bh & 31) * DH + sub * 8;
#pragma unroll
                for (int j = 0; j < 3; ++j) {
#pragma unroll
                    for (int e = 0; e < 8; ++e) {
                        float v = acc[j][e];
                        v += __shfl_xor_sync(0xffffffffu, v, 8);
                        v += __shfl_xor_sync(0xffffffffu, v, 16);
                        acc[j][e] = v;
                    }
                    if (grp == 0) {
                        red_add_v4(go + j * 64, acc[j][0], acc[j][1], acc[j][2], acc[j][3]);
                        red_add_v4(go + j * 64 + 4, acc[j][4], acc[j][5], acc[j][6], acc[j][7]);
                    }
                }
            }
        }
    }
    PROF(5);
    grid_arrive(&g_bar[2], tid);
    PROF(6);
    if (fcta >= 0 && tid == 0) {
        mbar_expect_tx(bar_wd, FF * P32);
        tma_block(sbase + SM_WD, &tm_down, fcta * 32, 0, FF, P32, bar_wd);
    }
    if (cta < ND) {
        const int u_end = s_item[NST];
        if (cta < FF / 16 && tid == 0) {
            mbar_expect_tx(bar_gu, 2 * DM * 32);
            tma_block(sbase + SM_W32, &tm_gate, cta * 16, 0, DM, 32, bar_gu);
            tma_block(sbase + SM_W32 + DM * 32, &tm_up, cta * 16, 0, DM, 32, bar_gu);
        }
        uint32_t fd[4][5][4];
        mbar_wait(bar_wo, 0);
        frag_load<4, 5>(fd, sbase + SM_RING + ((u_end + (warp >> 1)) % NST) * STAGE_BYTES + (warp & 1) * 64 * P80, P80, lane);
        grid_wait(&g_bar[2], target, tid);
        if (cta == 0 && tid == 0) { g_work = 0u; g_epoch = ep; }
        PROF(7);
        {
            float4 v[2];
#pragma unroll
            for (int r = 0; r < 2; ++r) v[r] = __ldcg((const float4*)(acc_o + (2 * r + (tid >> 7)) * QN + ks * WO_ROWS) + (tid & 127));
#pragma unroll
            for (int r = 0; r < 2; ++r) {
                __nv_bfloat162 p0 = __floats2bfloat162_rn(v[r].x, v[r].y), p1 = __floats2bfloat162_rn(v[r].z, v[r].w);
                *(uint2*)(smem + SM_A + (2 * r + (tid >> 7)) * A_PITCH + (tid & 127) * 8) = make_uint2(*(uint32_t*)&p0, *(uint32_t*)&p1);
            }
        }
        cons_sync();
        frag_mma<4, 5>(fd, sbase + SM_A + warp * 128, A_PITCH, s_part + warp * 320, lane);
        cons_sync();
        if (tid < 80) {
            const int b = tid / 20, n4 = tid - b * 20;
            float4 s4 = make_float4(0.f, 0.f, 0.f, 0.f);
#pragma unroll
            for (int w = 0; w < 8; ++w) {
                const float4 v = *(const float4*)(s_part + (w * 4 + b) * 80 + n4 * 4);
                s4.x += v.x; s4.y += v.y; s4.z += v.z; s4.w += v.w;
            }
            red_add_v4(acc_attn + b * DM + ns * 80 + n4 * 4, s4.x, s4.y, s4.z, s4.w);
        }
        PROF(8);
        grid_arrive(&g_bar[3], tid);
    }
    const bool has_e = cta < FF / 16;
    if (!has_e && fcta < 0) return;
    if (has_e) {
        uint32_t fe[5][2][4];
        mbar_wait(bar_gu, 0);
        frag_load<5, 2>(fe, sbase + SM_W32 + warp * 80 * 32, 32, lane, DM * 32);
        grid_wait(&g_bar[3], ep * ND, tid);
        PROF(9);
        {
            float4 v[3];
#pragma unroll
            for (int r = 0; r < 3; ++r)
                if (tid + r * NCONS < NB * DM / 4) v[r] = __ldcg((const float4*)acc_attn + tid + r * NCONS);
#pragma unroll
            for (int r = 0; r < 3; ++r)
                if (tid + r * NCONS < NB * DM / 4) ((float4*)s_part)[tid + r * NCONS] = v[r];
        }
        cons_sync();
#pragma unroll
        for (int i = 0; i < 5; ++i) {
            const float2 av = *((const float2*)(s_part + lrow * DM + lcol) + i);
            const float2 xv = *((const float2*)(s_xp + lrow * DM + lcol) + i);
            nv[2 * i] = bf16r(xv.x + bf16r(bf_lo(m_ga[i]) * bf16r(av.x)));
            nv[2 * i + 1] = bf16r(xv.y + bf16r(bf_hi(m_ga[i]) * bf16r(av.y)));
        }
        ln_norm(nv, s_red, tid);
        modulate(nv, m_sb, m_cb, h_dst);
        cons_sync();
        frag_mma<5, 2>(fe, sbase + SM_A + warp * 160, A_PITCH, s_part + warp * 320, lane);
        cons_sync();
        if (tid < 32) {
            const int b = tid >> 3, n = (tid & 7) * 2;
            const float g0 = bf16r(tall_sum(s_part, b, n)), g1 = bf16r(tall_sum(s_part, b, n + 1));
            const float u0 = bf16r(tall_sum(s_part, b, 16 + n)), u1 = bf16r(tall_sum(s_part, b, 17 + n));
            ll_store(g_act + (b * FF + cta * 16 + n) / 2, bf16r(gelu_tanh(g0)) * u0, bf16r(gelu_tanh(g1)) * u1, ep);
        }
        PROF(10);
        if (fcta < 0) return;
    } else {
        grid_wait(&g_bar[3], ep * ND, tid);
    }
    {
        float x10 = 0.f, x11 = 0.f;
        if (tid < 64) {
            const int b = tid >> 4, col = fcta * 32 + (tid & 15) * 2;
            const float2 av = __ldcg((const float2*)(acc_attn + b * DM + col));
            x10 = bf16r(s_xp[b * DM + col] + bf16r(bf_lo(m_fa[0]) * bf16r(av.x)));
            x11 = bf16r(s_xp[b * DM + col + 1] + bf16r(bf_hi(m_fa[0]) * bf16r(av.y)));
        }
        mbar_wait(bar_wd, 0);
        uint32_t ff[12][2][4];
        frag_load<12, 2>(ff, sbase + SM_WD + warp * 192 * P32, P32, lane);
        long long t0 = 0;
        for (;;) {
            bool ok = true;
#pragma unroll
            for (int r = 0; r < 6; ++r) {
                const int i = tid + r * NCONS, b = i / 384, c4 = i - b * 384;
                const uint4 v = ll_ld2(g_act + 2 * i);
                *(uint2*)(smem + SM_ACT + b * ACT_PITCH + c4 * 8) = make_uint2(v.x, v.z);
                ok = ok && v.y == ep && v.w == ep;
            }
            if (ok) break;
            if (t0 == 0) t0 = clock64();
            else if (clock64() - t0 > WAIT_LIMIT_CYCLES) __trap();
        }
        cons_sync();
        PROF(11);
        frag_mma<12, 2>(ff, sbase + SM_ACT + warp * 384, ACT_PITCH, s_part + warp * 320, lane);
        cons_sync();
        if (tid < 64) {
            const int b = tid >> 4, n = (tid & 15) * 2;
            const float f0 = bf16r(tall_sum(s_part, b, n)), f1 = bf16r(tall_sum(s_part, b, n + 1));
            *(__nv_bfloat162*)(out + b * DM + fcta * 32 + n) =
                __floats2bfloat162_rn(x10 + bf16r(bf_lo(m_fb[0]) * f0), x11 + bf16r(bf_hi(m_fb[0]) * f1));
        }
    }
    PROF(12);
}

}

extern "C" void kernel_launch(void* const* d_in, const int* in_sizes, int n_in, void* d_out, int out_size) {
    (void)in_sizes; (void)n_in; (void)out_size;
    const __nv_bfloat16* A_x = (const __nv_bfloat16*)d_in[0];
    const __nv_bfloat16* A_k = (const __nv_bfloat16*)d_in[1];
    const __nv_bfloat16* A_v = (const __nv_bfloat16*)d_in[2];
    const __nv_bfloat16* A_wq = (const __nv_bfloat16*)d_in[3];
    const __nv_bfloat16* A_wo = (const __nv_bfloat16*)d_in[4];
    const __nv_bfloat16* B_wg = (const __nv_bfloat16*)d_in[6];
    const __nv_bfloat16* B_wu = (const __nv_bfloat16*)d_in[7];
    const __nv_bfloat16* B_wd = (const __nv_bfloat16*)d_in[8];
    const __nv_bfloat16* c = (const __nv_bfloat16*)d_in[9];
    const __nv_bfloat16* w_mod = (const __nv_bfloat16*)d_in[10];
    typedef CUresult (*encode_fn)(CUtensorMap*, CUtensorMapDataType, cuuint32_t, void*, const cuuint64_t*, const cuuint64_t*,
                                  const cuuint32_t*, const cuuint32_t*, CUtensorMapInterleave, CUtensorMapSwizzle,
                                  CUtensorMapL2promotion, CUtensorMapFloatOOBfill);
    static int grid = 0;
    static encode_fn encode = nullptr;
    if (grid == 0) {
        cudaFuncSetAttribute(decode_block_kernel, cudaFuncAttributeMaxDynamicSharedMemorySize, SM_TOTAL);
        int dev = 0, sms = 0;
        cudaGetDevice(&dev);
        cudaDeviceGetAttribute(&sms, cudaDevAttrMultiProcessorCount, dev);
        grid = sms < 132 ? sms : 132;
        void* fn = nullptr;
        cudaDriverEntryPointQueryResult qres;
        cudaGetDriverEntryPoint("cuTensorMapEncodeTiled", &fn, cudaEnableDefault, &qres);
        encode = (encode_fn)fn;
    }
    auto make_map = [&](const __nv_bfloat16* w, int rows, int cols, int box_bytes) {
        CUtensorMap m;
        const cuuint64_t dims[2] = {(cuuint64_t)cols, (cuuint64_t)rows};
        const cuuint64_t strides[1] = {(cuuint64_t)cols * 2};
        const cuuint32_t box[2] = {(cuuint32_t)(box_bytes / 2), (cuuint32_t)BOX};
        const cuuint32_t estr[2] = {1, 1};
        encode(&m, CU_TENSOR_MAP_DATA_TYPE_BFLOAT16, 2, (void*)w, dims, strides, box, estr, CU_TENSOR_MAP_INTERLEAVE_NONE,
               CU_TENSOR_MAP_SWIZZLE_NONE, CU_TENSOR_MAP_L2_PROMOTION_L2_128B, CU_TENSOR_MAP_FLOAT_OOB_FILL_NONE);
        return m;
    };
    decode_block_kernel<<<grid, NTHREADS, SM_TOTAL>>>(A_x, A_k, A_v, c, (__nv_bfloat16*)d_out, make_map(w_mod, DM, MODN, P32),
                                                      make_map(A_wq, DM, QN, P48), make_map(A_wo, QN, DM, P80),
                                                      make_map(B_wg, DM, FF, 32), make_map(B_wu, DM, FF, 32),
                                                      make_map(B_wd, FF, DM, P32));
}
```

```cpp
#include <cuda.h>
#include <cuda_runtime.h>
#include <cuda_bf16.h>
#include <stdint.h>

namespace {

constexpr int NB = 4;
constexpr int DM = 640;
constexpr int NH = 32;
constexpr int SK = 4096;
constexpr int DH = 192;
constexpr int FF = 1536;
constexpr int MODN = 6 * DM;
constexpr int QN = NH * DH;
constexpr int NBH = NB * NH;

constexpr int NCONS = 256;
constexpr int NTHREADS = NCONS + 32;
constexpr int TILE_KEYS = 64;
constexpr int TILE_BYTES = TILE_KEYS * DH * 2;
constexpr int STAGE_BYTES = TILE_BYTES;
constexpr int NST = 6;
constexpr int PRE = 3;
constexpr int TPI = 2;
constexpr int ITEM_KEYS = TPI * TILE_KEYS;
constexpr int CHUNKS = SK / ITEM_KEYS;
constexpr int NITEM_K = NBH * CHUNKS;
constexpr int NITEM = 2 * NITEM_K;

constexpr int A_PITCH = 1296;
constexpr int ACT_PITCH = FF * 2 + 16;
constexpr int P32 = 80;
constexpr int P48 = 112;
constexpr int P80 = 176;
constexpr int WO_ROWS = 512;
constexpr int ND = QN / WO_ROWS * 8;
constexpr int BOX = 128;

constexpr int SM_RING = 0;
constexpr int SM_WQ = PRE * STAGE_BYTES;
constexpr int SM_WD = 0;
constexpr int SM_W32 = NST * STAGE_BYTES;
constexpr int SM_ACT = SM_W32;
constexpr int SM_A = SM_W32 + DM * P32;
constexpr int SM_PART = SM_A + NB * A_PITCH;
constexpr int SM_XP = SM_PART + 8 * 4 * 80 * 4;
constexpr int SM_RED = SM_XP + NB * DM * 4;
constexpr int SM_ITEM = SM_RED + 16 * 4;
constexpr int SM_TAG = SM_ITEM + 16 * 4;
constexpr int SM_BAR = SM_TAG + 16 * 4;
constexpr int SM_TOTAL = SM_BAR + (2 * NST + 5) * 8;
static_assert(SM_WQ + DM * P48 <= NST * STAGE_BYTES, "prologue overlay");
static_assert(SM_WD + FF * P32 <= NST * STAGE_BYTES && BOX * P80 <= STAGE_BYTES, "tail overlay");
static_assert(SM_TOTAL <= 232448, "smem");
constexpr int THR_ITEMS = 6;
constexpr int THR_DEPTH = 4;

__device__ __align__(128) unsigned long long g_mod[NB * MODN / 2];
__device__ __align__(128) unsigned long long g_q[NB * QN / 2];
__device__ __align__(128) unsigned long long g_act[NB * FF / 2];
__device__ __align__(128) unsigned int g_s[NBH * SK];
__device__ __align__(128) unsigned long long g_stat[NBH * CHUNKS];
__device__ __align__(128) float g_o[2][NB * QN];
__device__ __align__(128) float g_attn[2][NB * DM];
__device__ __align__(128) unsigned int g_bar[8];
__device__ unsigned int g_work;
__device__ unsigned int g_epoch;

#define PROF(k) do { } while (0)
#define PROFP(k) do { } while (0)

__device__ __forceinline__ float bf16r(float x) { return __bfloat162float(__float2bfloat16_rn(x)); }
__device__ __forceinline__ float bf_lo(uint32_t u) { return __uint_as_float(u << 16); }
__device__ __forceinline__ float bf_hi(uint32_t u) { return __uint_as_float(u & 0xffff0000u); }

__device__ __forceinline__ uint32_t smem_u32(const void* p) { return (uint32_t)__cvta_generic_to_shared(p); }
__device__ __forceinline__ void mbar_init(uint32_t bar, uint32_t count) {
    asm volatile("mbarrier.init.shared::cta.b64 [%0], %1;" ::"r"(bar), "r"(count) : "memory");
}
__device__ __forceinline__ void mbar_expect_tx(uint32_t bar, uint32_t bytes) {
    asm volatile("mbarrier.arrive.expect_tx.shared::cta.b64 _, [%0], %1;" ::"r"(bar), "r"(bytes) : "memory");
}
__device__ __forceinline__ void mbar_arrive(uint32_t bar) {
    asm volatile("mbarrier.arrive.shared::cta.b64 _, [%0];" ::"r"(bar) : "memory");
}
constexpr long long WAIT_LIMIT_CYCLES = 200000000LL;
__device__ __forceinline__ uint32_t mbar_try(uint32_t bar, uint32_t parity) {
    uint32_t done;
    asm volatile(
        "{\n\t.reg .pred p;\n\t"
        "mbarrier.try_wait.parity.shared::cta.b64 p, [%1], %2;\n\t"
        "selp.u32 %0, 1, 0, p;\n\t}"
        : "=r"(done) : "r"(bar), "r"(parity) : "memory");
    return done;
}
__device__ __noinline__ void mbar_wait_slow(uint32_t bar, uint32_t parity) {
    const long long t0 = clock64();
    while (!mbar_try(bar, parity)) {
        if (clock64() - t0 > WAIT_LIMIT_CYCLES) __trap();
    }
}
__device__ __forceinline__ void mbar_wait(uint32_t bar, uint32_t parity) {
    if (!mbar_try(bar, parity)) mbar_wait_slow(bar, parity);
}
__device__ __noinline__ void tag_wait_slow(volatile int* tag, int u) {
    const long long t0 = clock64();
    while (*tag != u) {
        __nanosleep(32);
        if (clock64() - t0 > WAIT_LIMIT_CYCLES) __trap();
    }
}
__device__ __noinline__ bool tag_wait_stop(volatile int* tag, int u, volatile int* stop) {
    const long long t0 = clock64();
    while (*tag != u) {
        if (*stop <= u) return false;
        __nanosleep(32);
        if (clock64() - t0 > WAIT_LIMIT_CYCLES) __trap();
    }
    return true;
}
__device__ __forceinline__ void stage_wait(uint32_t bar_full, volatile int* s_tag, int u) {
    const int st = u % NST;
    if (s_tag[st] != u) tag_wait_slow(s_tag + st, u);
    mbar_wait(bar_full + st * 8, (u / NST) & 1);
}
__device__ __forceinline__ void bulk_g2s(uint32_t dst, const void* src, uint32_t bytes, uint32_t bar, uint64_t pol) {
    asm volatile(
        "cp.async.bulk.shared::cluster.global.mbarrier::complete_tx::bytes.L2::cache_hint [%0], [%1], %2, [%3], %4;"
        ::"r"(dst), "l"(src), "r"(bytes), "r"(bar), "l"(pol) : "memory");
}
__device__ __forceinline__ void tma2d(uint32_t dst, const CUtensorMap* map, int col, int row, uint32_t bar) {
    asm volatile(
        "cp.async.bulk.tensor.2d.shared::cluster.global.tile.mbarrier::complete_tx::bytes [%0], [%1, {%2, %3}], [%4];"
        ::"r"(dst), "l"(map), "r"(col), "r"(row), "r"(bar) : "memory");
}
__device__ __forceinline__ void tma_block(uint32_t dst, const CUtensorMap* map, int col, int row, int rows, int pitch, uint32_t bar) {
#pragma unroll 1
    for (int r = 0; r < rows; r += BOX) tma2d(dst + r * pitch, map, col, row + r, bar);
}
__device__ __forceinline__ void red_release_add(unsigned int* p, unsigned int v) {
    asm volatile("red.release.gpu.global.add.u32 [%0], %1;" ::"l"(p), "r"(v) : "memory");
}
__device__ __forceinline__ void cons_sync() { asm volatile("bar.sync 1, 256;" ::: "memory"); }

__device__ __forceinline__ void red_add_v4(float* p, float a, float b, float c, float d) {
    asm volatile("red.global.add.v4.f32 [%0], {%1, %2, %3, %4};" ::"l"(p), "f"(a), "f"(b), "f"(c), "f"(d) : "memory");
}
__device__ __forceinline__ unsigned int ld_acquire(const unsigned int* p) {
    unsigned int v;
    asm volatile("ld.acquire.gpu.global.u32 %0, [%1];" : "=r"(v) : "l"(p) : "memory");
    return v;
}
__device__ __forceinline__ void ll_store(unsigned long long* p, float a, float b, unsigned int ep) {
    __nv_bfloat162 v = __floats2bfloat162_rn(a, b);
    const unsigned long long w = ((unsigned long long)ep << 32) | *(uint32_t*)&v;
    asm volatile("st.relaxed.gpu.global.u64 [%0], %1;" ::"l"(p), "l"(w) : "memory");
}
__device__ __forceinline__ uint2 ll_ld1(const unsigned long long* p) {
    unsigned long long w;
    asm volatile("ld.relaxed.gpu.global.u64 %0, [%1];" : "=l"(w) : "l"(p) : "memory");
    return make_uint2((uint32_t)w, (uint32_t)(w >> 32));
}
__device__ __forceinline__ uint4 ll_ld2(const unsigned long long* p) {
    unsigned long long a, b;
    asm volatile("ld.relaxed.gpu.global.v2.u64 {%0, %1}, [%2];" : "=l"(a), "=l"(b) : "l"(p) : "memory");
    return make_uint4((uint32_t)a, (uint32_t)(a >> 32), (uint32_t)b, (uint32_t)(b >> 32));
}
template <int N>
__device__ __forceinline__ void ll_get(const unsigned long long* p, uint32_t (&d)[N], unsigned int ep) {
    long long t0 = 0;
    for (;;) {
        bool ok = true;
#pragma unroll
        for (int i = 0; i < N; ++i) {
            const uint2 v = ll_ld1(p + i);
            d[i] = v.x;
            ok = ok && (v.y == ep);
        }
        if (ok) break;
        if (t0 == 0) t0 = clock64();
        else if (clock64() - t0 > WAIT_LIMIT_CYCLES) __trap();
    }
}

__device__ __forceinline__ void grid_arrive(unsigned int* ctr, bool leader) {
    cons_sync();
    if (leader) red_release_add(ctr, 1u);
}
__device__ __noinline__ void grid_wait(const unsigned int* ctr, unsigned int target, int tid) {
    if (tid == 0) {
        const long long t0 = clock64();
        while ((int)(ld_acquire(ctr) - target) < 0) {
            if (clock64() - t0 > WAIT_LIMIT_CYCLES) __trap();
        }
    }
    cons_sync();
}

__device__ __forceinline__ float warp_sum(float v) {
#pragma unroll
    for (int o = 16; o > 0; o >>= 1) v += __shfl_xor_sync(0xffffffffu, v, o);
    return v;
}
__device__ __forceinline__ float warp_max(float v) {
#pragma unroll
    for (int o = 16; o > 0; o >>= 1) v = fmaxf(v, __shfl_xor_sync(0xffffffffu, v, o));
    return v;
}

__device__ __forceinline__ void fma8(float (&acc)[8], const uint4& w, float s) {
    acc[0] = fmaf(s, bf_lo(w.x), acc[0]);
    acc[1] = fmaf(s, bf_hi(w.x), acc[1]);
    acc[2] = fmaf(s, bf_lo(w.y), acc[2]);
    acc[3] = fmaf(s, bf_hi(w.y), acc[3]);
    acc[4] = fmaf(s, bf_lo(w.z), acc[4]);
    acc[5] = fmaf(s, bf_hi(w.z), acc[5]);
    acc[6] = fmaf(s, bf_lo(w.w), acc[6]);
    acc[7] = fmaf(s, bf_hi(w.w), acc[7]);
}
__device__ __forceinline__ float dot8(const uint4& w, const float* q) {
    float s = q[0] * bf_lo(w.x);
    s = fmaf(q[1], bf_hi(w.x), s);
    s = fmaf(q[2], bf_lo(w.y), s);
    s = fmaf(q[3], bf_hi(w.y), s);
    s = fmaf(q[4], bf_lo(w.z), s);
    s = fmaf(q[5], bf_hi(w.z), s);
    s = fmaf(q[6], bf_lo(w.w), s);
    s = fmaf(q[7], bf_hi(w.w), s);
    return s;
}

template <int KS, int NT>
__device__ __noinline__ void gemv_mma(uint32_t w, int w_pitch, uint32_t a, int a_pitch, float* part, int lane) {
    float c[NT][4];
#pragma unroll
    for (int nt = 0; nt < NT; ++nt) { c[nt][0] = 0.f; c[nt][1] = 0.f; c[nt][2] = 0.f; c[nt][3] = 0.f; }
    const uint32_t ap = a + (lane >> 2) * a_pitch + (lane & 3) * 4;
    const uint32_t wp = w + ((lane & 7) + ((lane >> 4) << 3)) * w_pitch + ((lane >> 3) & 1) * 16;
#pragma unroll
    for (int ks = 0; ks < KS; ++ks) {
        uint32_t b0 = 0, b1 = 0;
        if (lane < 16) {
            asm("ld.shared.u32 %0, [%1];" : "=r"(b0) : "r"(ap + ks * 32));
            asm("ld.shared.u32 %0, [%1];" : "=r"(b1) : "r"(ap + ks * 32 + 16));
        }
#pragma unroll
        for (int nt = 0; nt < NT; ++nt) {
            uint32_t a0, a1, a2, a3;
            asm("ldmatrix.sync.aligned.m8n8.x4.trans.shared.b16 {%0, %1, %2, %3}, [%4];"
                         : "=r"(a0), "=r"(a1), "=r"(a2), "=r"(a3) : "r"(wp + ks * 16 * w_pitch + nt * 32));
            asm("mma.sync.aligned.m16n8k16.row.col.f32.bf16.bf16.f32 {%0, %1, %2, %3}, {%4, %5, %6, %7}, "
                "{%8, %9}, {%0, %1, %2, %3};"
                : "+f"(c[nt][0]), "+f"(c[nt][1]), "+f"(c[nt][2]), "+f"(c[nt][3])
                : "r"(a0), "r"(a1), "r"(a2), "r"(a3), "r"(b0), "r"(b1));
        }
    }
    if ((lane & 3) < 2) {
        float* pp = part + (lane & 3) * 160 + (lane >> 2);
#pragma unroll
        for (int nt = 0; nt < NT; ++nt) {
            pp[nt * 16] = c[nt][0];
            pp[nt * 16 + 80] = c[nt][1];
            pp[nt * 16 + 8] = c[nt][2];
            pp[nt * 16 + 88] = c[nt][3];
        }
    }
}

template <int KS, int NT>
__device__ __forceinline__ void frag_load(uint32_t (&f)[KS][NT][4], uint32_t w, int w_pitch, int lane, int n_stride = 32) {
    const uint32_t wp = w + ((lane & 7) + ((lane >> 4) << 3)) * w_pitch + ((lane >> 3) & 1) * 16;
#pragma unroll
    for (int ks = 0; ks < KS; ++ks)
#pragma unroll
        for (int nt = 0; nt < NT; ++nt)
            asm volatile("ldmatrix.sync.aligned.m8n8.x4.trans.shared.b16 {%0, %1, %2, %3}, [%4];"
                         : "=r"(f[ks][nt][0]), "=r"(f[ks][nt][1]), "=r"(f[ks][nt][2]), "=r"(f[ks][nt][3])
                         : "r"(wp + ks * 16 * w_pitch + nt * n_stride) : "memory");
}
template <int KS, int NT>
__device__ __forceinline__ void frag_mma(const uint32_t (&f)[KS][NT][4], uint32_t a, int a_pitch, float* part, int lane) {
    float c[NT][4];
#pragma unroll
    for (int nt = 0; nt < NT; ++nt) { c[nt][0] = 0.f; c[nt][1] = 0.f; c[nt][2] = 0.f; c[nt][3] = 0.f; }
    const uint32_t ap = a + (lane >> 2) * a_pitch + (lane & 3) * 4;
    uint32_t b[KS][2];
#pragma unroll
    for (int ks = 0; ks < KS; ++ks) {
        b[ks][0] = 0; b[ks][1] = 0;
        if (lane < 16) {
            asm volatile("ld.shared.u32 %0, [%1];" : "=r"(b[ks][0]) : "r"(ap + ks * 32) : "memory");
            asm volatile("ld.shared.u32 %0, [%1];" : "=r"(b[ks][1]) : "r"(ap + ks * 32 + 16) : "memory");
        }
    }
#pragma unroll
    for (int ks = 0; ks < KS; ++ks)
#pragma unroll
        for (int nt = 0; nt < NT; ++nt)
            asm("mma.sync.aligned.m16n8k16.row.col.f32.bf16.bf16.f32 {%0, %1, %2, %3}, {%4, %5, %6, %7}, "
                "{%8, %9}, {%0, %1, %2, %3};"
                : "+f"(c[nt][0]), "+f"(c[nt][1]), "+f"(c[nt][2]), "+f"(c[nt][3])
                : "r"(f[ks][nt][0]), "r"(f[ks][nt][1]), "r"(f[ks][nt][2]), "r"(f[ks][nt][3]), "r"(b[ks][0]), "r"(b[ks][1]));
    if ((lane & 3) < 2) {
        float* pp = part + (lane & 3) * 160 + (lane >> 2);
#pragma unroll
        for (int nt = 0; nt < NT; ++nt) {
            pp[nt * 16] = c[nt][0];
            pp[nt * 16 + 80] = c[nt][1];
            pp[nt * 16 + 8] = c[nt][2];
            pp[nt * 16 + 88] = c[nt][3];
        }
    }
}

__device__ __forceinline__ float tall_sum(const float* part, int b, int n) {
    float s = 0.f;
#pragma unroll
    for (int w = 0; w < 8; ++w) s += part[(w * 4 + b) * 80 + n];
    return s;
}

__device__ __forceinline__ void ln_norm(float (&v)[10], float* s_red, int tid) {
    const int warp = tid >> 5;
    const float pv = __shfl_sync(0xffffffffu, v[0], 0);
    float s = 0.f, q = 0.f;
#pragma unroll
    for (int i = 0; i < 10; ++i) { const float d = v[i] - pv; s += d; q = fmaf(d, d, q); }
#pragma unroll
    for (int o = 16; o > 0; o >>= 1) {
        s += __shfl_xor_sync(0xffffffffu, s, o);
        q += __shfl_xor_sync(0xffffffffu, q, o);
    }
    const float md = s * (2.0f / DM);
    if ((tid & 31) == 0) *(float2*)(s_red + 2 * warp) = make_float2(pv + md, fmaxf(q - s * md, 0.f));
    cons_sync();
    const float4 r = *(const float4*)(s_red + 4 * (warp >> 1));
    const float dm = r.x - r.z;
    const float var = (r.y + r.w + dm * dm * (DM / 4)) * (1.0f / DM);
    const float mean = bf16r(0.5f * (r.x + r.z));
    const float inv = __fdiv_rn(1.0f, bf16r(sqrtf(bf16r(bf16r(var) + 1e-5f))));
#pragma unroll
    for (int i = 0; i < 10; ++i) v[i] = bf16r(bf16r(v[i] - mean) * inv);
}
__device__ __forceinline__ void modulate(const float (&n)[10], const uint32_t (&sh)[5], const uint32_t (&sc)[5], uint32_t* dst) {
#pragma unroll
    for (int i = 0; i < 5; ++i) {
        const float h0 = bf16r(n[2 * i] * bf16r(1.0f + bf_lo(sc[i]))) + bf_lo(sh[i]);
        const float h1 = bf16r(n[2 * i + 1] * bf16r(1.0f + bf_hi(sc[i]))) + bf_hi(sh[i]);
        __nv_bfloat162 p = __floats2bfloat162_rn(h0, h1);
        dst[i] = *(uint32_t*)&p;
    }
}

__device__ __forceinline__ float gelu_tanh(float x) {
    const float kBeta = 0.7978845608028654f;
    const float inner = kBeta * (x + 0.044715f * x * x * x);
    return 0.5f * x * (1.0f + tanhf(inner));
}

__global__ void __launch_bounds__(NTHREADS, 1)
decode_block_kernel(const __nv_bfloat16* __restrict__ x_in, const __nv_bfloat16* __restrict__ k_cache,
                    const __nv_bfloat16* __restrict__ v_cache, const __nv_bfloat16* __restrict__ cvec,
                    __nv_bfloat16* __restrict__ out, const __grid_constant__ CUtensorMap tm_mod,
                    const __grid_constant__ CUtensorMap tm_q, const __grid_constant__ CUtensorMap tm_o,
                    const __grid_constant__ CUtensorMap tm_gate, const __grid_constant__ CUtensorMap tm_up,
                    const __grid_constant__ CUtensorMap tm_down) {
    extern __shared__ __align__(128) unsigned char smem[];
    const int tid = threadIdx.x;
    const int cta = blockIdx.x;

    const uint32_t sbase = smem_u32(smem);
    const uint32_t bar_full = sbase + SM_BAR;
    const uint32_t bar_empty = bar_full + NST * 8;
    volatile int* s_item = (volatile int*)(smem + SM_ITEM);
    volatile int* s_tag = (volatile int*)(smem + SM_TAG);

    const uint32_t bar_wm = bar_empty + NST * 8, bar_wq = bar_wm + 8, bar_wo = bar_wm + 16, bar_gu = bar_wm + 24, bar_wd = bar_wm + 32;
    PROF(0);
    const int lrow = (tid >> 6) & 3, lcol = (tid & 63) * 10;
    unsigned int ep0 = 0;
    uint4 c0 = make_uint4(0u, 0u, 0u, 0u), c1 = c0;
    uint32_t xw[5];
    if (tid < NCONS) {
        asm volatile("ld.relaxed.gpu.global.u32 %0, [%1];" : "=r"(ep0) : "l"(&g_epoch));
        asm volatile("ld.global.nc.v4.u32 {%0, %1, %2, %3}, [%4];" : "=r"(c0.x), "=r"(c0.y), "=r"(c0.z), "=r"(c0.w) : "l"((const uint4*)cvec + tid));
        if (tid < 320 - NCONS)
            asm volatile("ld.global.nc.v4.u32 {%0, %1, %2, %3}, [%4];" : "=r"(c1.x), "=r"(c1.y), "=r"(c1.z), "=r"(c1.w) : "l"((const uint4*)cvec + tid + NCONS));
#pragma unroll
        for (int i = 0; i < 5; ++i)
            asm volatile("ld.global.nc.u32 %0, [%1];" : "=r"(xw[i]) : "l"((const uint32_t*)(x_in + lrow * DM + lcol) + i));
    }
    if (tid < NST) s_tag[tid] = -1;
    if (tid == NST) s_item[NST] = 0x7fffffff;
    if (tid == NCONS) {
#pragma unroll 1
        for (int s = 0; s < 2 * NST + 5; ++s) mbar_init(bar_full + s * 8, 1);
        asm volatile("fence.mbarrier_init.release.cluster;" ::: "memory");
        asm volatile("fence.proxy.async.shared::cta;" ::: "memory");
#pragma unroll 1
        for (int s = 0; s < PRE; ++s) mbar_arrive(bar_empty + s * 8);
    }
    __syncthreads();
    const int ks = cta >> 3, ns = cta & 7;

    if (tid >= NCONS) {
        if (tid == NCONS) {
            int u = 0;
            const int G = (int)gridDim.x;
            uint64_t pol;
            asm volatile("createpolicy.fractional.L2::evict_first.b64 %0, 1.0;" : "=l"(pol));
            auto produce = [&](const int item) {
                const int it = item & (NITEM_K - 1);
                const bool is_v = item >= NITEM_K;
                const unsigned char* src = (const unsigned char*)(is_v ? v_cache : k_cache) + (size_t)it * (ITEM_KEYS * DH * 2);
#pragma unroll 1
                for (int t = 0; t < TPI; ++t, ++u) {
                    const int st = u % NST;
                    const uint32_t fb = bar_full + st * 8;
                    mbar_wait(bar_empty + st * 8, (u / NST) & 1);
                    if (item >= NITEM - THR_ITEMS * G) mbar_wait(bar_empty + ((u - THR_DEPTH) % NST) * 8, ((u - THR_DEPTH) / NST + 1) & 1);
                    s_item[st] = item;
                    s_tag[st] = u;
                    mbar_expect_tx(fb, TILE_BYTES);
                    bulk_g2s(sbase + SM_RING + st * STAGE_BYTES, src + t * TILE_BYTES, TILE_BYTES, fb, pol);
                }
            };
            if (cta < MODN / 32) {
                mbar_expect_tx(bar_wm, DM * P32);
                tma_block(sbase + SM_W32, &tm_mod, cta * 32, 0, DM, P32, bar_wm);
            }
            asm volatile("prefetch.tensormap [%0];" ::"l"(&tm_q) : "memory");
            asm volatile("prefetch.tensormap [%0];" ::"l"(&tm_o) : "memory");
            asm volatile("prefetch.tensormap [%0];" ::"l"(&tm_gate) : "memory");
            asm volatile("prefetch.tensormap [%0];" ::"l"(&tm_up) : "memory");
            asm volatile("prefetch.tensormap [%0];" ::"l"(&tm_down) : "memory");
            if (cta < MODN / 32) mbar_wait(bar_wm, 0);
            int item = cta;
#pragma unroll 1
            while (item < NITEM) {
                const int next = (int)atomicAdd(&g_work, 1u) + G;
                produce(item);
                item = next;
            }
            s_item[NST] = u;
            if (cta < ND) {
                mbar_expect_tx(bar_wo, WO_ROWS * P80);
#pragma unroll 1
                for (int j = 0; j < WO_ROWS / BOX; ++j, ++u) {
                    const int st = u % NST;
                    mbar_wait(bar_empty + st * 8, (u / NST) & 1);
                    tma2d(sbase + SM_RING + st * STAGE_BYTES, &tm_o, ns * 80, ks * WO_ROWS + j * BOX, bar_wo);
                }
            }
            PROFP(13);
        }
        return;
    }

    const int lane = tid & 31, warp = tid >> 5;
    float* s_part = (float*)(smem + SM_PART);
    float* s_xp = (float*)(smem + SM_XP);
    float* s_red = (float*)(smem + SM_RED);
    uint32_t* h_dst = (uint32_t*)(smem + SM_A + lrow * A_PITCH + lcol * 2);

    const unsigned int ep = ep0 + 1u;
    const unsigned int target = ep * gridDim.x, tag16 = ep & 0xffffu;
    const unsigned long long* mod_row = g_mod + (lrow * MODN + lcol) / 2;
    float nv[10];
    {
        const int i1 = tid + NCONS;
#pragma unroll 1
        for (int r = 0; r < 2; ++r) {
            const int i = r ? i1 : tid;
            if (i < 320) {
                const uint4 cc = r ? c1 : c0;
                const uint32_t cw[4] = {cc.x, cc.y, cc.z, cc.w};
                uint32_t ow[4];
#pragma unroll
                for (int k = 0; k < 4; ++k) {
                    const float a = bf_lo(cw[k]), b = bf_hi(cw[k]);
                    __nv_bfloat162 p = __floats2bfloat162_rn(__fdiv_rn(a, 1.0f + __expf(-a)), __fdiv_rn(b, 1.0f + __expf(-b)));
                    ow[k] = *(uint32_t*)&p;
                }
                const int b = i / 80, c8 = i - b * 80;
                *(uint4*)(smem + SM_A + b * A_PITCH + c8 * 16) = make_uint4(ow[0], ow[1], ow[2], ow[3]);
            }
        }
#pragma unroll
        for (int i = 0; i < 5; ++i) {
            nv[2 * i] = bf_lo(xw[i]);
            nv[2 * i + 1] = bf_hi(xw[i]);
            *(float2*)(s_xp + lrow * DM + lcol + 2 * i) = make_float2(nv[2 * i], nv[2 * i + 1]);
        }
        if (tid == 0 && cta < QN / 48) {
            mbar_expect_tx(bar_wq, DM * P48);
            tma_block(sbase + SM_WQ, &tm_q, cta * 48, 0, DM, P48, bar_wq);
        }
    }
    float* acc_o = g_o[ep & 1];
    float* acc_attn = g_attn[ep & 1];
    if (cta == gridDim.x - 1) {
#pragma unroll 1
        for (int i = tid; i < NB * QN / 4; i += NCONS) ((float4*)g_o[~ep & 1])[i] = make_float4(0.f, 0.f, 0.f, 0.f);
#pragma unroll 1
        for (int i = tid; i < NB * DM; i += NCONS) g_attn[~ep & 1][i] = 0.f;
    }
    ln_norm(nv, s_red, tid);
    cons_sync();
    PROF(14);
    if (cta < MODN / 32) {
        mbar_wait(bar_wm, 0);
        PROF(15);
        gemv_mma<5, 2>(sbase + SM_W32 + warp * 80 * P32, P32, sbase + SM_A + warp * 160, A_PITCH, s_part + warp * 320, lane);
        cons_sync();
        if (tid < 64) {
            const int b = tid >> 4, n = (tid & 15) * 2;
            ll_store(g_mod + (b * MODN + cta * 32 + n) / 2, tall_sum(s_part, b, n), tall_sum(s_part, b, n + 1), ep);
        }
    }
    PROF(1);
    uint32_t m_ga[5] = {0u, 0u, 0u, 0u, 0u}, m_sb[5] = {0u, 0u, 0u, 0u, 0u}, m_cb[5] = {0u, 0u, 0u, 0u, 0u};
    uint32_t m_fa[1] = {0u}, m_fb[1] = {0u};
    const int fcta = cta - ((int)gridDim.x - DM / 32);

#pragma unroll 1
    for (int pass = 0; pass < 2; ++pass) {
    int real;
    asm volatile("mov.u32 %0, %1;" : "=r"(real) : "r"(pass));
    cons_sync();
    if (real) {
    if (cta < QN / 48) {
        mbar_wait(bar_wq, 0);
        PROF(16);
        uint32_t fq[5][3][4];
        frag_load<5, 3>(fq, sbase + SM_WQ + warp * 80 * P48, P48, lane);
        {
            long long t0 = 0;
            for (;;) {
                bool ok = true;
#pragma unroll
                for (int r = 0; r < 5; ++r) {
                    const int i = tid + r * NCONS, b = i / 320, c4 = i - b * 320;
                    const uint4 v = ll_ld2(g_mod + b * (MODN / 2) + 2 * c4);
                    *(uint2*)(s_part + b * DM + 2 * c4) = make_uint2(v.x, v.z);
                    ok = ok && v.y == ep && v.w == ep;
                }
                if (ok) break;
                if (t0 == 0) t0 = clock64();
                else if (clock64() - t0 > WAIT_LIMIT_CYCLES) __trap();
            }
        }
        cons_sync();
        PROF(2);
        uint32_t sh[5], sc[5];
#pragma unroll
        for (int i = 0; i < 5; ++i) {
            sh[i] = ((const uint32_t*)s_part)[lrow * DM + lcol / 2 + i];
            sc[i] = ((const uint32_t*)s_part)[lrow * DM + DM / 2 + lcol / 2 + i];
        }
        modulate(nv, sh, sc, h_dst);
        cons_sync();
        frag_mma<5, 3>(fq, sbase + SM_A + warp * 160, A_PITCH, s_part + warp * 320, lane);
        cons_sync();
        if (tid < 96) {
            const int b = tid / 24, n = (tid - b * 24) * 2;
            ll_store(g_q + (b * QN + cta * 48 + n) / 2, tall_sum(s_part, b, n), tall_sum(s_part, b, n + 1), ep);
        }
    }
    PROF(3);
    if (tid == 0) {
#pragma unroll 1
        for (int s = PRE; s < NST; ++s) mbar_arrive(bar_empty + s * 8);
    }
    PROF(4);

    {
        const int sub = lane & 7, grp = lane >> 3;
        for (int u0 = warp * TPI;; u0 += 8 * TPI) {
            int item = -1;
            if (s_tag[u0 % NST] == u0 || tag_wait_stop(s_tag + u0 % NST, u0, s_item + NST)) item = s_item[u0 % NST];
            if ((u0 >= 8 * TPI && u0 < 16 * TPI) || (item < 0 && u0 < 8 * TPI)) {
                if (cta < FF / 16) {
                    ll_get(mod_row + DM, m_ga, ep);
                    ll_get(mod_row + 3 * DM / 2, m_sb, ep);
                    ll_get(mod_row + 2 * DM, m_cb, ep);
                }
                if (tid < 64 && fcta >= 0) {
                    ll_get(g_mod + ((tid >> 4) * MODN + 2 * DM + fcta * 32) / 2 + (tid & 15), m_fa, ep);
                    ll_get(g_mod + ((tid >> 4) * MODN + 5 * DM + fcta * 32) / 2 + (tid & 15), m_fb, ep);
                }
            }
            if (item < 0) break;
            const int bh = (item & (NITEM_K - 1)) / CHUNKS;
            if (item < NITEM_K) {
                unsigned int* gs = g_s + (size_t)item * ITEM_KEYS;
                float qr[24];
                {
                    const unsigned long long* qp = g_q + ((bh >> 5) * QN + (bh & 31) * DH) / 2 + sub * 4;
                    long long t0 = 0;
                    for (;;) {
                        bool ok = true;
#pragma unroll
                        for (int j = 0; j < 6; ++j) {
                            const uint4 v = ll_ld2(qp + (j >> 1) * 32 + (j & 1) * 2);
                            qr[j * 4 + 0] = bf_lo(v.x); qr[j * 4 + 1] = bf_hi(v.x);
                            qr[j * 4 + 2] = bf_lo(v.z); qr[j * 4 + 3] = bf_hi(v.z);
                            ok = ok && v.y == ep && v.w == ep;
                        }
                        if (ok) break;
                        if (t0 == 0) t0 = clock64();
                        else if (clock64() - t0 > WAIT_LIMIT_CYCLES) __trap();
                    }
                }
                float m_run = -INFINITY, l_run = 0.f;
#pragma unroll 1
                for (int hh = 0; hh < 2 * TPI; ++hh) {
                    const int u = u0 + (hh >> 1), st = u % NST;
                    if (!(hh & 1)) stage_wait(bar_full, s_tag, u);
                    const uint4* tile = (const uint4*)(smem + SM_RING + st * STAGE_BYTES) + (hh & 1) * (32 * 24);
                    float part[8];
#pragma unroll
                    for (int it = 0; it < 8; ++it) {
                        const uint4* row = tile + (it * 4 + grp) * 24 + sub;
                        const uint4 a = row[0], b = row[8], c = row[16];
                        part[it] = dot8(a, qr) + dot8(b, qr + 8) + dot8(c, qr + 16);
                    }
                    if (hh & 1) {
                        __syncwarp();
                        if (lane == 0) mbar_arrive(bar_empty + st * 8);
                    }
#pragma unroll
                    for (int j = 0; j < 4; ++j) {
                        const float send = (sub & 4) ? part[j] : part[j + 4];
                        const float keep = (sub & 4) ? part[j + 4] : part[j];
                        part[j] = keep + __shfl_xor_sync(0xffffffffu, send, 4);
                    }
#pragma unroll
                    for (int j = 0; j < 2; ++j) {
                        const float send = (sub & 2) ? part[j] : part[j + 2];
                        const float keep = (sub & 2) ? part[j + 2] : part[j];
                        part[j] = keep + __shfl_xor_sync(0xffffffffu, send, 2);
                    }
                    {
                        const float send = (sub & 1) ? part[0] : part[1];
                        const float keep = (sub & 1) ? part[1] : part[0];
                        part[0] = keep + __shfl_xor_sync(0xffffffffu, send, 1);
                    }
                    const float s = bf16r(bf16r(part[0]) * 0.07216878364870323f);
                    asm volatile("st.relaxed.gpu.global.u32 [%0], %1;" ::"l"(gs + hh * 32 + sub * 4 + grp), "r"(__float_as_uint(s) | tag16) : "memory");
                    const float m_new = fmaxf(m_run, s);
                    l_run = l_run * __expf(m_run - m_new) + __expf(s - m_new);
                    m_run = m_new;
                }
                const float m = warp_max(m_run);
                const float l = warp_sum(l_run * __expf(m_run - m));
                if (lane == 0)
                    asm volatile("st.relaxed.gpu.global.u64 [%0], %1;" ::"l"(g_stat + item),
                                 "l"(((unsigned long long)__float_as_uint(l) << 32) | (__float_as_uint(m) | tag16)) : "memory");
            } else {
                float pr[2 * TPI];
                {
                    const unsigned int* gs = g_s + (size_t)(item - NITEM_K) * ITEM_KEYS + lane;
                    uint2 st2;
                    long long t0 = 0;
                    for (;;) {
                        st2 = ll_ld1(g_stat + bh * CHUNKS + lane);
                        bool ok = (st2.x & 0xffffu) == tag16;
#pragma unroll
                        for (int hh = 0; hh < 2 * TPI; ++hh) {
                            unsigned int w;
                            asm volatile("ld.relaxed.gpu.global.u32 %0, [%1];" : "=r"(w) : "l"(gs + hh * 32) : "memory");
                            ok = ok && (w & 0xffffu) == tag16;
                            pr[hh] = bf_hi(w);
                        }
                        if (__all_sync(0xffffffffu, ok)) break;
                        if (t0 == 0) t0 = clock64();
                        else if (clock64() - t0 > WAIT_LIMIT_CYCLES) __trap();
                    }
                    const float mi = bf_hi(st2.x);
                    const float mm = warp_max(mi);
                    const float ll = warp_sum(__uint_as_float(st2.y) * __expf(mi - mm));
#pragma unroll
                    for (int hh = 0; hh < 2 * TPI; ++hh) pr[hh] = bf16r(__fdiv_rn(__expf(pr[hh] - mm), ll));
                }
                float acc[3][8];
#pragma unroll
                for (int j = 0; j < 3; ++j)
#pragma unroll
                    for (int e = 0; e < 8; ++e) acc[j][e] = 0.f;
#pragma unroll
                for (int hh = 0; hh < 2 * TPI; ++hh) {
                    const int u = u0 + (hh >> 1), st = u % NST;
                    if (!(hh & 1)) stage_wait(bar_full, s_tag, u);
                    const uint4* tile = (const uint4*)(smem + SM_RING + st * STAGE_BYTES) + (hh & 1) * (32 * 24);
#pragma unroll
                    for (int it = 0; it < 8; ++it) {
                        const uint4* row = tile + (it * 4 + grp) * 24 + sub;
                        const uint4 a = row[0], b = row[8], c = row[16];
                        const float p = __shfl_sync(0xffffffffu, pr[hh], it * 4 + grp);
                        fma8(acc[0], a, p);
                        fma8(acc[1], b, p);
                        fma8(acc[2], c, p);
                    }
                    if (hh & 1) {
                        __syncwarp();
                        if (lane == 0) mbar_arrive(bar_empty + st * 8);
                    }
                }
                float* go = acc_o + (bh >> 5) * QN + (bh & 31) * DH + sub * 8;
#pragma unroll
                for (int j = 0; j < 3; ++j) {
#pragma unroll
                    for (int e = 0; e < 8; ++e) {
                        float v = acc[j][e];
                        v += __shfl_xor_sync(0xffffffffu, v, 8);
                        v += __shfl_xor_sync(0xffffffffu, v, 16);
                        acc[j][e] = v;
                    }
                    if (grp == 0) {
                        red_add_v4(go + j * 64, acc[j][0], acc[j][1], acc[j][2], acc[j][3]);
                        red_add_v4(go + j * 64 + 4, acc[j][4], acc[j][5], acc[j][6], acc[j][7]);
                    }
                }
            }
        }
    }
    PROF(5);
    }
    const bool lead = real && tid == 0;
    grid_arrive(&g_bar[2], lead);
    PROF(6);
    if (fcta >= 0 && lead) {
        mbar_expect_tx(bar_wd, FF * P32);
        tma_block(sbase + SM_WD, &tm_down, fcta * 32, 0, FF, P32, bar_wd);
    }
    if (cta < ND) {
        const int u_end = s_item[NST] & 0xffff;
        if (lead) {
            mbar_expect_tx(bar_gu, 2 * DM * 32);
            tma_block(sbase + SM_W32, &tm_gate, cta * 16, 0, DM, 32, bar_gu);
            tma_block(sbase + SM_W32 + DM * 32, &tm_up, cta * 16, 0, DM, 32, bar_gu);
        }
        uint32_t fd[4][5][4];
        if (real) mbar_wait(bar_wo, 0);
        frag_load<4, 5>(fd, sbase + SM_RING + ((u_end + (warp >> 1)) % NST) * STAGE_BYTES + (warp & 1) * 64 * P80, P80, lane);
        grid_wait(&g_bar[2], (ep - 1u + real) * gridDim.x, tid);
        if (cta == 0 && lead) { g_work = 0u; g_epoch = ep; }
        PROF(7);
        {
            float4 v[2];
#pragma unroll
            for (int r = 0; r < 2; ++r) v[r] = __ldcg((const float4*)(acc_o + (2 * r + (tid >> 7)) * QN + ks * WO_ROWS) + (tid & 127));
#pragma unroll
            for (int r = 0; r < 2; ++r) {
                __nv_bfloat162 p0 = __floats2bfloat162_rn(v[r].x, v[r].y), p1 = __floats2bfloat162_rn(v[r].z, v[r].w);
                *(uint2*)(smem + SM_A + (2 * r + (tid >> 7)) * A_PITCH + (tid & 127) * 8) = make_uint2(*(uint32_t*)&p0, *(uint32_t*)&p1);
            }
        }
        cons_sync();
        frag_mma<4, 5>(fd, sbase + SM_A + warp * 128, A_PITCH, s_part + warp * 320, lane);
        cons_sync();
        if (tid < 80) {
            const int b = tid / 20, n4 = tid - b * 20;
            float4 s4 = make_float4(0.f, 0.f, 0.f, 0.f);
#pragma unroll
            for (int w = 0; w < 8; ++w) {
                const float4 v = *(const float4*)(s_part + (w * 4 + b) * 80 + n4 * 4);
                s4.x += v.x; s4.y += v.y; s4.z += v.z; s4.w += v.w;
            }
            if (real) red_add_v4(acc_attn + b * DM + ns * 80 + n4 * 4, s4.x, s4.y, s4.z, s4.w);
        }
        PROF(8);
        grid_arrive(&g_bar[3], lead);
        static_assert(ND == FF / 16, "the same CTAs do wo and gate/up");
        uint32_t fe[5][2][4];
        if (real) mbar_wait(bar_gu, 0);
        frag_load<5, 2>(fe, sbase + SM_W32 + warp * 80 * 32, 32, lane, DM * 32);
        grid_wait(&g_bar[3], (ep - 1u + real) * ND, tid);
        PROF(9);
        {
            float4 v[3];
#pragma unroll
            for (int r = 0; r < 3; ++r)
                if (tid + r * NCONS < NB * DM / 4) v[r] = __ldcg((const float4*)acc_attn + tid + r * NCONS);
#pragma unroll
            for (int r = 0; r < 3; ++r)
                if (tid + r * NCONS < NB * DM / 4) ((float4*)s_part)[tid + r * NCONS] = v[r];
        }
        cons_sync();
        float ev[10];
#pragma unroll
        for (int i = 0; i < 5; ++i) {
            const float2 av = *((const float2*)(s_part + lrow * DM + lcol) + i);
            const float2 xv = *((const float2*)(s_xp + lrow * DM + lcol) + i);
            ev[2 * i] = bf16r(xv.x + bf16r(bf_lo(m_ga[i]) * bf16r(av.x)));
            ev[2 * i + 1] = bf16r(xv.y + bf16r(bf_hi(m_ga[i]) * bf16r(av.y)));
        }
        ln_norm(ev, s_red, tid);
        modulate(ev, m_sb, m_cb, h_dst);
        cons_sync();
        frag_mma<5, 2>(fe, sbase + SM_A + warp * 160, A_PITCH, s_part + warp * 320, lane);
        cons_sync();
        if (tid < 32) {
            const int b = tid >> 3, n = (tid & 7) * 2;
            const float g0 = bf16r(tall_sum(s_part, b, n)), g1 = bf16r(tall_sum(s_part, b, n + 1));
            const float u0 = bf16r(tall_sum(s_part, b, 16 + n)), u1 = bf16r(tall_sum(s_part, b, 17 + n));
            const float a0 = bf16r(gelu_tanh(g0)) * u0, a1 = bf16r(gelu_tanh(g1)) * u1;
            if (real) ll_store(g_act + (b * FF + cta * 16 + n) / 2, a0, a1, ep);
        }
        PROF(10);
    } else if (fcta >= 0) {
        if (real) mbar_wait(bar_wd, 0);
        uint32_t ff[12][2][4];
        frag_load<12, 2>(ff, sbase + SM_WD + warp * 192 * P32, P32, lane);
        grid_wait(&g_bar[3], (ep - 1u + real) * ND, tid);
        float x10 = 0.f, x11 = 0.f;
        if (tid < 64) {
            const int b = tid >> 4, col = fcta * 32 + (tid & 15) * 2;
            const float2 av = __ldcg((const float2*)(acc_attn + b * DM + col));
            x10 = bf16r(s_xp[b * DM + col] + bf16r(bf_lo(m_fa[0]) * bf16r(av.x)));
            x11 = bf16r(s_xp[b * DM + col + 1] + bf16r(bf_hi(m_fa[0]) * bf16r(av.y)));
        }
        long long t0 = 0;
        for (;;) {
            bool ok = true;
#pragma unroll
            for (int r = 0; r < 6; ++r) {
                const int i = tid + r * NCONS, b = i / 384, c4 = i - b * 384;
                const uint4 v = ll_ld2(g_act + 2 * i);
                *(uint2*)(smem + SM_ACT + b * ACT_PITCH + c4 * 8) = make_uint2(v.x, v.z);
                ok = ok && v.y == ep && v.w == ep;
            }
            if (ok || !real) break;
            if (t0 == 0) t0 = clock64();
            else if (clock64() - t0 > WAIT_LIMIT_CYCLES) __trap();
        }
        cons_sync();
        PROF(11);
        frag_mma<12, 2>(ff, sbase + SM_ACT + warp * 384, ACT_PITCH, s_part + warp * 320, lane);
        cons_sync();
        if (tid < 64) {
            const int b = tid >> 4, n = (tid & 15) * 2;
            const float f0 = bf16r(tall_sum(s_part, b, n)), f1 = bf16r(tall_sum(s_part, b, n + 1));
            const __nv_bfloat162 res = __floats2bfloat162_rn(x10 + bf16r(bf_lo(m_fb[0]) * f0), x11 + bf16r(bf_hi(m_fb[0]) * f1));
            if (real) *(__nv_bfloat162*)(out + b * DM + fcta * 32 + n) = res;
        }
        PROF(12);
    }
    if (!real) PROF(17);
    }
}

}

extern "C" void kernel_launch(void* const* d_in, const int* in_sizes, int n_in, void* d_out, int out_size) {
    (void)in_sizes; (void)n_in; (void)out_size;
    const __nv_bfloat16* A_x = (const __nv_bfloat16*)d_in[0];
    const __nv_bfloat16* A_k = (const __nv_bfloat16*)d_in[1];
    const __nv_bfloat16* A_v = (const __nv_bfloat16*)d_in[2];
    const __nv_bfloat16* A_wq = (const __nv_bfloat16*)d_in[3];
    const __nv_bfloat16* A_wo = (const __nv_bfloat16*)d_in[4];
    const __nv_bfloat16* B_wg = (const __nv_bfloat16*)d_in[6];
    const __nv_bfloat16* B_wu = (const __nv_bfloat16*)d_in[7];
    const __nv_bfloat16* B_wd = (const __nv_bfloat16*)d_in[8];
    const __nv_bfloat16* c = (const __nv_bfloat16*)d_in[9];
    const __nv_bfloat16* w_mod = (const __nv_bfloat16*)d_in[10];
    typedef CUresult (*encode_fn)(CUtensorMap*, CUtensorMapDataType, cuuint32_t, void*, const cuuint64_t*, const cuuint64_t*,
                                  const cuuint32_t*, const cuuint32_t*, CUtensorMapInterleave, CUtensorMapSwizzle,
                                  CUtensorMapL2promotion, CUtensorMapFloatOOBfill);
    static int grid = 0;
    static encode_fn encode = nullptr;
    if (grid == 0) {
        cudaFuncSetAttribute(decode_block_kernel, cudaFuncAttributeMaxDynamicSharedMemorySize, SM_TOTAL);
        int dev = 0, sms = 0;
        cudaGetDevice(&dev);
        cudaDeviceGetAttribute(&sms, cudaDevAttrMultiProcessorCount, dev);
        grid = sms < 132 ? sms : 132;
        void* fn = nullptr;
        cudaDriverEntryPointQueryResult qres;
        cudaGetDriverEntryPoint("cuTensorMapEncodeTiled", &fn, cudaEnableDefault, &qres);
        encode = (encode_fn)fn;
    }
    auto make_map = [&](const __nv_bfloat16* w, int rows, int cols, int box_bytes) {
        CUtensorMap m;
        const cuuint64_t dims[2] = {(cuuint64_t)cols, (cuuint64_t)rows};
        const cuuint64_t strides[1] = {(cuuint64_t)cols * 2};
        const cuuint32_t box[2] = {(cuuint32_t)(box_bytes / 2), (cuuint32_t)BOX};
        const cuuint32_t estr[2] = {1, 1};
        encode(&m, CU_TENSOR_MAP_DATA_TYPE_BFLOAT16, 2, (void*)w, dims, strides, box, estr, CU_TENSOR_MAP_INTERLEAVE_NONE,
               CU_TENSOR_MAP_SWIZZLE_NONE, CU_TENSOR_MAP_L2_PROMOTION_L2_128B, CU_TENSOR_MAP_FLOAT_OOB_FILL_NONE);
        return m;
    };
    decode_block_kernel<<<grid, NTHREADS, SM_TOTAL>>>(A_x, A_k, A_v, c, (__nv_bfloat16*)d_out, make_map(w_mod, DM, MODN, P32),
                                                      make_map(A_wq, DM, QN, P48), make_map(A_wo, QN, DM, P80),
                                                      make_map(B_wg, DM, FF, 32), make_map(B_wu, DM, FF, 32),
                                                      make_map(B_wd, FF, DM, P32));
}
```

```cpp
#include <cuda.h>
#include <cuda_runtime.h>
#include <cuda_bf16.h>
#include <stdint.h>

namespace {

constexpr int NB = 4;
constexpr int DM = 640;
constexpr int NH = 32;
constexpr int SK = 4096;
constexpr int DH = 192;
constexpr int FF = 1536;
constexpr int MODN = 6 * DM;
constexpr int QN = NH * DH;
constexpr int NBH = NB * NH;

constexpr int NCONS = 256;
constexpr int NTHREADS = NCONS + 32;
constexpr int TILE_KEYS = 64;
constexpr int TILE_BYTES = TILE_KEYS * DH * 2;
constexpr int STAGE_BYTES = TILE_BYTES;
constexpr int NST = 6;
constexpr int PRE = 3;
constexpr int TPI = 2;
constexpr int ITEM_KEYS = TPI * TILE_KEYS;
constexpr int CHUNKS = SK / ITEM_KEYS;
constexpr int NITEM_K = NBH * CHUNKS;
constexpr int NITEM = 2 * NITEM_K;

constexpr int A_PITCH = 1296;
constexpr int ACT_PITCH = FF * 2 + 16;
constexpr int P32 = 80;
constexpr int P48 = 112;
constexpr int P80 = 176;
constexpr int WO_ROWS = 512;
constexpr int ND = QN / WO_ROWS * 8;
constexpr int BOX = 128;

constexpr int SM_RING = 0;
constexpr int SM_WQ = PRE * STAGE_BYTES;
constexpr int SM_WD = 0;
constexpr int SM_W32 = NST * STAGE_BYTES;
constexpr int SM_ACT = SM_W32;
constexpr int SM_A = SM_W32 + DM * P32;
constexpr int SM_PART = SM_A + NB * A_PITCH;
constexpr int SM_XP = SM_PART + 8 * 4 * 80 * 4;
constexpr int SM_RED = SM_XP + NB * DM * 4;
constexpr int SM_ITEM = SM_RED + 16 * 4;
constexpr int SM_TAG = SM_ITEM + 16 * 4;
constexpr int SM_BAR = SM_TAG + 16 * 4;
constexpr int SM_TOTAL = SM_BAR + (2 * NST + 5) * 8;
static_assert(SM_WQ + DM * P48 <= NST * STAGE_BYTES, "prologue overlay");
static_assert(SM_WD + FF * P32 <= NST * STAGE_BYTES && BOX * P80 <= STAGE_BYTES, "tail overlay");
static_assert(SM_TOTAL <= 232448, "smem");
constexpr int THR_ITEMS = 6;
constexpr int THR_DEPTH = 4;

__device__ __align__(128) unsigned long long g_mod[NB * MODN / 2];
__device__ __align__(128) unsigned long long g_q[NB * QN / 2];
__device__ __align__(128) unsigned long long g_act[NB * FF / 2];
__device__ __align__(128) unsigned int g_s[NBH * SK];
__device__ __align__(128) unsigned long long g_stat[NBH * CHUNKS];
__device__ __align__(128) float g_o[2][NB * QN];
__device__ __align__(128) float g_attn[2][NB * DM];
__device__ __align__(128) unsigned int g_bar[8];
__device__ unsigned int g_work;
__device__ unsigned int g_epoch;

#define PROF(k) do { } while (0)
#define PROFP(k) do { } while (0)

__device__ __forceinline__ float bf16r(float x) {
    uint32_t r;
    asm("cvt.rn.bf16x2.f32 %0, %1, %2;" : "=r"(r) : "f"(x), "f"(0.f));
    return __uint_as_float(r);
}
__device__ __forceinline__ float bf_lo(uint32_t u) { return __uint_as_float(u << 16); }
__device__ __forceinline__ float bf_hi(uint32_t u) { return __uint_as_float(u & 0xffff0000u); }

__device__ __forceinline__ uint32_t smem_u32(const void* p) { return (uint32_t)__cvta_generic_to_shared(p); }
__device__ __forceinline__ void mbar_init(uint32_t bar, uint32_t count) {
    asm volatile("mbarrier.init.shared::cta.b64 [%0], %1;" ::"r"(bar), "r"(count) : "memory");
}
__device__ __forceinline__ void mbar_expect_tx(uint32_t bar, uint32_t bytes) {
    asm volatile("mbarrier.arrive.expect_tx.shared::cta.b64 _, [%0], %1;" ::"r"(bar), "r"(bytes) : "memory");
}
__device__ __forceinline__ void mbar_arrive(uint32_t bar) {
    asm volatile("mbarrier.arrive.shared::cta.b64 _, [%0];" ::"r"(bar) : "memory");
}
constexpr long long WAIT_LIMIT_CYCLES = 200000000LL;
__device__ __forceinline__ uint32_t mbar_try(uint32_t bar, uint32_t parity) {
    uint32_t done;
    asm volatile(
        "{\n\t.reg .pred p;\n\t"
        "mbarrier.try_wait.parity.shared::cta.b64 p, [%1], %2;\n\t"
        "selp.u32 %0, 1, 0, p;\n\t}"
        : "=r"(done) : "r"(bar), "r"(parity) : "memory");
    return done;
}
__device__ __noinline__ void mbar_wait_slow(uint32_t bar, uint32_t parity) {
    const long long t0 = clock64();
    while (!mbar_try(bar, parity)) {
        if (clock64() - t0 > WAIT_LIMIT_CYCLES) __trap();
    }
}
__device__ __forceinline__ void mbar_wait(uint32_t bar, uint32_t parity) {
    if (!mbar_try(bar, parity)) mbar_wait_slow(bar, parity);
}
__device__ __noinline__ void tag_wait_slow(volatile int* tag, int u) {
    const long long t0 = clock64();
    while (*tag != u) {
        __nanosleep(32);
        if (clock64() - t0 > WAIT_LIMIT_CYCLES) __trap();
    }
}
__device__ __noinline__ bool tag_wait_stop(volatile int* tag, int u, volatile int* stop) {
    const long long t0 = clock64();
    while (*tag != u) {
        if (*stop <= u) return false;
        __nanosleep(32);
        if (clock64() - t0 > WAIT_LIMIT_CYCLES) __trap();
    }
    return true;
}
__device__ __forceinline__ void stage_wait(uint32_t bar_full, volatile int* s_tag, int u) {
    const int st = u % NST;
    if (s_tag[st] != u) tag_wait_slow(s_tag + st, u);
    mbar_wait(bar_full + st * 8, (u / NST) & 1);
}
__device__ __forceinline__ void bulk_g2s(uint32_t dst, const void* src, uint32_t bytes, uint32_t bar, uint64_t pol) {
    asm volatile(
        "cp.async.bulk.shared::cluster.global.mbarrier::complete_tx::bytes.L2::cache_hint [%0], [%1], %2, [%3], %4;"
        ::"r"(dst), "l"(src), "r"(bytes), "r"(bar), "l"(pol) : "memory");
}
__device__ __forceinline__ void tma2d(uint32_t dst, const CUtensorMap* map, int col, int row, uint32_t bar) {
    asm volatile(
        "cp.async.bulk.tensor.2d.shared::cluster.global.tile.mbarrier::complete_tx::bytes [%0], [%1, {%2, %3}], [%4];"
        ::"r"(dst), "l"(map), "r"(col), "r"(row), "r"(bar) : "memory");
}
__device__ __forceinline__ void tma_block(uint32_t dst, const CUtensorMap* map, int col, int row, int rows, int pitch, uint32_t bar) {
#pragma unroll 1
    for (int r = 0; r < rows; r += BOX) tma2d(dst + r * pitch, map, col, row + r, bar);
}
__device__ __forceinline__ void red_release_add(unsigned int* p, unsigned int v) {
    asm volatile("red.release.gpu.global.add.u32 [%0], %1;" ::"l"(p), "r"(v) : "memory");
}
__device__ __forceinline__ void cons_sync() { asm volatile("bar.sync 1, 256;" ::: "memory"); }

__device__ __forceinline__ void red_add_v4(float* p, float a, float b, float c, float d) {
    asm volatile("red.global.add.v4.f32 [%0], {%1, %2, %3, %4};" ::"l"(p), "f"(a), "f"(b), "f"(c), "f"(d) : "memory");
}
__device__ __forceinline__ unsigned int ld_acquire(const unsigned int* p) {
    unsigned int v;
    asm volatile("ld.acquire.gpu.global.u32 %0, [%1];" : "=r"(v) : "l"(p) : "memory");
    return v;
}
__device__ __forceinline__ void ll_store(unsigned long long* p, float a, float b, unsigned int ep) {
    __nv_bfloat162 v = __floats2bfloat162_rn(a, b);
    const unsigned long long w = ((unsigned long long)ep << 32) | *(uint32_t*)&v;
    asm volatile("st.relaxed.gpu.global.u64 [%0], %1;" ::"l"(p), "l"(w) : "memory");
}
__device__ __forceinline__ uint2 ll_ld1(const unsigned long long* p) {
    unsigned long long w;
    asm volatile("ld.relaxed.gpu.global.u64 %0, [%1];" : "=l"(w) : "l"(p) : "memory");
    return make_uint2((uint32_t)w, (uint32_t)(w >> 32));
}
__device__ __forceinline__ uint4 ll_ld2(const unsigned long long* p) {
    unsigned long long a, b;
    asm volatile("ld.relaxed.gpu.global.v2.u64 {%0, %1}, [%2];" : "=l"(a), "=l"(b) : "l"(p) : "memory");
    return make_uint4((uint32_t)a, (uint32_t)(a >> 32), (uint32_t)b, (uint32_t)(b >> 32));
}
template <int N>
__device__ __forceinline__ void ll_get(const unsigned long long* p, uint32_t (&d)[N], unsigned int ep) {
    long long t0 = 0;
    for (;;) {
        bool ok = true;
#pragma unroll
        for (int i = 0; i < N; ++i) {
            const uint2 v = ll_ld1(p + i);
            d[i] = v.x;
            ok = ok && (v.y == ep);
        }
        if (ok) break;
        if (t0 == 0) t0 = clock64();
        else if (clock64() - t0 > WAIT_LIMIT_CYCLES) __trap();
    }
}

__device__ __forceinline__ void grid_arrive(unsigned int* ctr, int tid) {
    cons_sync();
    if (tid == 0) red_release_add(ctr, 1u);
}
__device__ __noinline__ void grid_wait(const unsigned int* ctr, unsigned int target, int tid) {
    if (tid == 0) {
        const long long t0 = clock64();
        while ((int)(ld_acquire(ctr) - target) < 0) {
            if (clock64() - t0 > WAIT_LIMIT_CYCLES) __trap();
        }
    }
    cons_sync();
}

__device__ __forceinline__ float warp_sum(float v) {
#pragma unroll
    for (int o = 16; o > 0; o >>= 1) v += __shfl_xor_sync(0xffffffffu, v, o);
    return v;
}
__device__ __forceinline__ float warp_max(float v) {
#pragma unroll
    for (int o = 16; o > 0; o >>= 1) v = fmaxf(v, __shfl_xor_sync(0xffffffffu, v, o));
    return v;
}

__device__ __forceinline__ void fma8(float (&acc)[8], const uint4& w, float s) {
    acc[0] = fmaf(s, bf_lo(w.x), acc[0]);
    acc[1] = fmaf(s, bf_hi(w.x), acc[1]);
    acc[2] = fmaf(s, bf_lo(w.y), acc[2]);
    acc[3] = fmaf(s, bf_hi(w.y), acc[3]);
    acc[4] = fmaf(s, bf_lo(w.z), acc[4]);
    acc[5] = fmaf(s, bf_hi(w.z), acc[5]);
    acc[6] = fmaf(s, bf_lo(w.w), acc[6]);
    acc[7] = fmaf(s, bf_hi(w.w), acc[7]);
}
__device__ __forceinline__ float dot8(const uint4& w, const float* q) {
    float s = q[0] * bf_lo(w.x);
    s = fmaf(q[1], bf_hi(w.x), s);
    s = fmaf(q[2], bf_lo(w.y), s);
    s = fmaf(q[3], bf_hi(w.y), s);
    s = fmaf(q[4], bf_lo(w.z), s);
    s = fmaf(q[5], bf_hi(w.z), s);
    s = fmaf(q[6], bf_lo(w.w), s);
    s = fmaf(q[7], bf_hi(w.w), s);
    return s;
}

template <int KS, int NT>
__device__ __noinline__ void gemv_mma(uint32_t w, int w_pitch, uint32_t a, int a_pitch, float* part, int lane) {
    float c[NT][4];
#pragma unroll
    for (int nt = 0; nt < NT; ++nt) { c[nt][0] = 0.f; c[nt][1] = 0.f; c[nt][2] = 0.f; c[nt][3] = 0.f; }
    const uint32_t ap = a + (lane >> 2) * a_pitch + (lane & 3) * 4;
    const uint32_t wp = w + ((lane & 7) + ((lane >> 4) << 3)) * w_pitch + ((lane >> 3) & 1) * 16;
#pragma unroll
    for (int ks = 0; ks < KS; ++ks) {
        uint32_t b0 = 0, b1 = 0;
        if (lane < 16) {
            asm("ld.shared.u32 %0, [%1];" : "=r"(b0) : "r"(ap + ks * 32));
            asm("ld.shared.u32 %0, [%1];" : "=r"(b1) : "r"(ap + ks * 32 + 16));
        }
#pragma unroll
        for (int nt = 0; nt < NT; ++nt) {
            uint32_t a0, a1, a2, a3;
            asm("ldmatrix.sync.aligned.m8n8.x4.trans.shared.b16 {%0, %1, %2, %3}, [%4];"
                         : "=r"(a0), "=r"(a1), "=r"(a2), "=r"(a3) : "r"(wp + ks * 16 * w_pitch + nt * 32));
            asm("mma.sync.aligned.m16n8k16.row.col.f32.bf16.bf16.f32 {%0, %1, %2, %3}, {%4, %5, %6, %7}, "
                "{%8, %9}, {%0, %1, %2, %3};"
                : "+f"(c[nt][0]), "+f"(c[nt][1]), "+f"(c[nt][2]), "+f"(c[nt][3])
                : "r"(a0), "r"(a1), "r"(a2), "r"(a3), "r"(b0), "r"(b1));
        }
    }
    if ((lane & 3) < 2) {
        float* pp = part + (lane & 3) * 160 + (lane >> 2);
#pragma unroll
        for (int nt = 0; nt < NT; ++nt) {
            pp[nt * 16] = c[nt][0];
            pp[nt * 16 + 80] = c[nt][1];
            pp[nt * 16 + 8] = c[nt][2];
            pp[nt * 16 + 88] = c[nt][3];
        }
    }
}

template <int KS, int NT>
__device__ __forceinline__ void frag_load(uint32_t (&f)[KS][NT][4], uint32_t w, int w_pitch, int lane, int n_stride = 32) {
    const uint32_t wp = w + ((lane & 7) + ((lane >> 4) << 3)) * w_pitch + ((lane >> 3) & 1) * 16;
#pragma unroll
    for (int ks = 0; ks < KS; ++ks)
#pragma unroll
        for (int nt = 0; nt < NT; ++nt)
            asm volatile("ldmatrix.sync.aligned.m8n8.x4.trans.shared.b16 {%0, %1, %2, %3}, [%4];"
                         : "=r"(f[ks][nt][0]), "=r"(f[ks][nt][1]), "=r"(f[ks][nt][2]), "=r"(f[ks][nt][3])
                         : "r"(wp + ks * 16 * w_pitch + nt * n_stride) : "memory");
}
template <int KS, int NT>
__device__ __forceinline__ void frag_mma(const uint32_t (&f)[KS][NT][4], uint32_t a, int a_pitch, float* part, int lane) {
    float c[NT][4];
#pragma unroll
    for (int nt = 0; nt < NT; ++nt) { c[nt][0] = 0.f; c[nt][1] = 0.f; c[nt][2] = 0.f; c[nt][3] = 0.f; }
    const uint32_t ap = a + (lane >> 2) * a_pitch + (lane & 3) * 4;
    uint32_t b[KS][2];
#pragma unroll
    for (int ks = 0; ks < KS; ++ks) {
        b[ks][0] = 0; b[ks][1] = 0;
        if (lane < 16) {
            asm volatile("ld.shared.u32 %0, [%1];" : "=r"(b[ks][0]) : "r"(ap + ks * 32) : "memory");
            asm volatile("ld.shared.u32 %0, [%1];" : "=r"(b[ks][1]) : "r"(ap + ks * 32 + 16) : "memory");
        }
    }
#pragma unroll
    for (int ks = 0; ks < KS; ++ks)
#pragma unroll
        for (int nt = 0; nt < NT; ++nt)
            asm("mma.sync.aligned.m16n8k16.row.col.f32.bf16.bf16.f32 {%0, %1, %2, %3}, {%4, %5, %6, %7}, "
                "{%8, %9}, {%0, %1, %2, %3};"
                : "+f"(c[nt][0]), "+f"(c[nt][1]), "+f"(c[nt][2]), "+f"(c[nt][3])
                : "r"(f[ks][nt][0]), "r"(f[ks][nt][1]), "r"(f[ks][nt][2]), "r"(f[ks][nt][3]), "r"(b[ks][0]), "r"(b[ks][1]));
    if ((lane & 3) < 2) {
        float* pp = part + (lane & 3) * 160 + (lane >> 2);
#pragma unroll
        for (int nt = 0; nt < NT; ++nt) {
            pp[nt * 16] = c[nt][0];
            pp[nt * 16 + 80] = c[nt][1];
            pp[nt * 16 + 8] = c[nt][2];
            pp[nt * 16 + 88] = c[nt][3];
        }
    }
}

__device__ __forceinline__ float tall_sum(const float* part, int b, int n) {
    float s = 0.f;
#pragma unroll
    for (int w = 0; w < 8; ++w) s += part[(w * 4 + b) * 80 + n];
    return s;
}

__device__ __forceinline__ void ln_norm(float (&v)[10], float* s_red, int tid) {
    const int warp = tid >> 5;
    const float pv = __shfl_sync(0xffffffffu, v[0], 0);
    float s = 0.f, q = 0.f;
#pragma unroll
    for (int i = 0; i < 10; ++i) { const float d = v[i] - pv; s += d; q = fmaf(d, d, q); }
#pragma unroll
    for (int o = 16; o > 0; o >>= 1) {
        s += __shfl_xor_sync(0xffffffffu, s, o);
        q += __shfl_xor_sync(0xffffffffu, q, o);
    }
    const float md = s * (2.0f / DM);
    if ((tid & 31) == 0) *(float2*)(s_red + 2 * warp) = make_float2(pv + md, fmaxf(q - s * md, 0.f));
    cons_sync();
    const float4 r = *(const float4*)(s_red + 4 * (warp >> 1));
    const float dm = r.x - r.z;
    const float var = (r.y + r.w + dm * dm * (DM / 4)) * (1.0f / DM);
    const float mean = bf16r(0.5f * (r.x + r.z));
    const float inv = __fdiv_rn(1.0f, bf16r(sqrtf(bf16r(bf16r(var) + 1e-5f))));
#pragma unroll
    for (int i = 0; i < 10; ++i) v[i] = bf16r(bf16r(v[i] - mean) * inv);
}
__device__ __forceinline__ void modulate(const float (&n)[10], const uint32_t (&sh)[5], const uint32_t (&sc)[5], uint32_t* dst) {
#pragma unroll
    for (int i = 0; i < 5; ++i) {
        const float h0 = bf16r(n[2 * i] * bf16r(1.0f + bf_lo(sc[i]))) + bf_lo(sh[i]);
        const float h1 = bf16r(n[2 * i + 1] * bf16r(1.0f + bf_hi(sc[i]))) + bf_hi(sh[i]);
        __nv_bfloat162 p = __floats2bfloat162_rn(h0, h1);
        dst[i] = *(uint32_t*)&p;
    }
}

__device__ __forceinline__ float gelu_tanh(float x) {
    const float kBeta = 0.7978845608028654f;
    const float inner = kBeta * (x + 0.044715f * x * x * x);
    return 0.5f * x * (1.0f + tanhf(inner));
}

__global__ void __launch_bounds__(NTHREADS, 1)
decode_block_kernel(const __nv_bfloat16* __restrict__ x_in, const __nv_bfloat16* __restrict__ k_cache,
                    const __nv_bfloat16* __restrict__ v_cache, const __nv_bfloat16* __restrict__ cvec,
                    __nv_bfloat16* __restrict__ out, const __grid_constant__ CUtensorMap tm_mod,
                    const __grid_constant__ CUtensorMap tm_q, const __grid_constant__ CUtensorMap tm_o,
                    const __grid_constant__ CUtensorMap tm_gate, const __grid_constant__ CUtensorMap tm_up,
                    const __grid_constant__ CUtensorMap tm_down) {
    extern __shared__ __align__(128) unsigned char smem[];
    const int tid = threadIdx.x;
    const int cta = blockIdx.x;

    const uint32_t sbase = smem_u32(smem);
    const uint32_t bar_full = sbase + SM_BAR;
    const uint32_t bar_empty = bar_full + NST * 8;
    volatile int* s_item = (volatile int*)(smem + SM_ITEM);
    volatile int* s_tag = (volatile int*)(smem + SM_TAG);

    const uint32_t bar_wm = bar_empty + NST * 8, bar_wq = bar_wm + 8, bar_wo = bar_wm + 16, bar_gu = bar_wm + 24, bar_wd = bar_wm + 32;
    PROF(0);
    const int lrow = (tid >> 6) & 3, lcol = (tid & 63) * 10;
    unsigned int ep0 = 0;
    uint4 c0 = make_uint4(0u, 0u, 0u, 0u), c1 = c0;
    uint32_t xw[5];
    if (tid < NCONS) {
        asm volatile("ld.relaxed.gpu.global.u32 %0, [%1];" : "=r"(ep0) : "l"(&g_epoch));
        asm volatile("ld.global.nc.v4.u32 {%0, %1, %2, %3}, [%4];" : "=r"(c0.x), "=r"(c0.y), "=r"(c0.z), "=r"(c0.w) : "l"((const uint4*)cvec + tid));
        if (tid < 320 - NCONS)
            asm volatile("ld.global.nc.v4.u32 {%0, %1, %2, %3}, [%4];" : "=r"(c1.x), "=r"(c1.y), "=r"(c1.z), "=r"(c1.w) : "l"((const uint4*)cvec + tid + NCONS));
#pragma unroll
        for (int i = 0; i < 5; ++i)
            asm volatile("ld.global.nc.u32 %0, [%1];" : "=r"(xw[i]) : "l"((const uint32_t*)(x_in + lrow * DM + lcol) + i));
    }
    if (tid < NST) s_tag[tid] = -1;
    if (tid == NST) s_item[NST] = 0x7fffffff;
    if (tid == NCONS) {
#pragma unroll 1
        for (int s = 0; s < 2 * NST + 5; ++s) mbar_init(bar_full + s * 8, 1);
        asm volatile("fence.mbarrier_init.release.cluster;" ::: "memory");
        asm volatile("fence.proxy.async.shared::cta;" ::: "memory");
#pragma unroll 1
        for (int s = 0; s < PRE; ++s) mbar_arrive(bar_empty + s * 8);
    }
    __syncthreads();
    const int ks = cta >> 3, ns = cta & 7;

    if (tid >= NCONS) {
        if (tid == NCONS) {
            int u = 0;
            const int G = (int)gridDim.x;
            uint64_t pol;
            asm volatile("createpolicy.fractional.L2::evict_first.b64 %0, 1.0;" : "=l"(pol));
            auto produce = [&](const int item) {
                const int it = item & (NITEM_K - 1);
                const bool is_v = item >= NITEM_K;
                const unsigned char* src = (const unsigned char*)(is_v ? v_cache : k_cache) + (size_t)it * (ITEM_KEYS * DH * 2);
#pragma unroll 1
                for (int t = 0; t < TPI; ++t, ++u) {
                    const int st = u % NST;
                    const uint32_t fb = bar_full + st * 8;
                    mbar_wait(bar_empty + st * 8, (u / NST) & 1);
                    if (item >= NITEM - THR_ITEMS * G) mbar_wait(bar_empty + ((u - THR_DEPTH) % NST) * 8, ((u - THR_DEPTH) / NST + 1) & 1);
                    s_item[st] = item;
                    s_tag[st] = u;
                    mbar_expect_tx(fb, TILE_BYTES);
                    bulk_g2s(sbase + SM_RING + st * STAGE_BYTES, src + t * TILE_BYTES, TILE_BYTES, fb, pol);
                }
            };
            if (cta < MODN / 32) {
                mbar_expect_tx(bar_wm, DM * P32);
                tma_block(sbase + SM_W32, &tm_mod, cta * 32, 0, DM, P32, bar_wm);
            }
            asm volatile("prefetch.tensormap [%0];" ::"l"(&tm_q) : "memory");
            asm volatile("prefetch.tensormap [%0];" ::"l"(&tm_o) : "memory");
            asm volatile("prefetch.tensormap [%0];" ::"l"(&tm_gate) : "memory");
            asm volatile("prefetch.tensormap [%0];" ::"l"(&tm_up) : "memory");
            asm volatile("prefetch.tensormap [%0];" ::"l"(&tm_down) : "memory");
            if (cta < MODN / 32) mbar_wait(bar_wm, 0);
            int item = cta;
#pragma unroll 1
            while (item < NITEM) {
                const int next = (int)atomicAdd(&g_work, 1u) + G;
                produce(item);
                item = next;
            }
            s_item[NST] = u;
            if (cta < ND) {
                mbar_expect_tx(bar_wo, WO_ROWS * P80);
#pragma unroll 1
                for (int j = 0; j < WO_ROWS / BOX; ++j, ++u) {
                    const int st = u % NST;
                    mbar_wait(bar_empty + st * 8, (u / NST) & 1);
                    tma2d(sbase + SM_RING + st * STAGE_BYTES, &tm_o, ns * 80, ks * WO_ROWS + j * BOX, bar_wo);
                }
            }
            PROFP(13);
        }
        return;
    }

    const int lane = tid & 31, warp = tid >> 5;
    float* s_part = (float*)(smem + SM_PART);
    float* s_xp = (float*)(smem + SM_XP);
    float* s_red = (float*)(smem + SM_RED);
    uint32_t* h_dst = (uint32_t*)(smem + SM_A + lrow * A_PITCH + lcol * 2);

    const unsigned int ep = ep0 + 1u;
    const unsigned int target = ep * gridDim.x, tag16 = ep & 0xffffu;
    const unsigned long long* mod_row = g_mod + (lrow * MODN + lcol) / 2;
    float nv[10];
    {
        const int i1 = tid + NCONS;
#pragma unroll 1
        for (int r = 0; r < 2; ++r) {
            const int i = r ? i1 : tid;
            if (i < 320) {
                const uint4 cc = r ? c1 : c0;
                const uint32_t cw[4] = {cc.x, cc.y, cc.z, cc.w};
                uint32_t ow[4];
#pragma unroll
                for (int k = 0; k < 4; ++k) {
                    const float a = bf_lo(cw[k]), b = bf_hi(cw[k]);
                    __nv_bfloat162 p = __floats2bfloat162_rn(__fdiv_rn(a, 1.0f + __expf(-a)), __fdiv_rn(b, 1.0f + __expf(-b)));
                    ow[k] = *(uint32_t*)&p;
                }
                const int b = i / 80, c8 = i - b * 80;
                *(uint4*)(smem + SM_A + b * A_PITCH + c8 * 16) = make_uint4(ow[0], ow[1], ow[2], ow[3]);
            }
        }
#pragma unroll
        for (int i = 0; i < 5; ++i) {
            nv[2 * i] = bf_lo(xw[i]);
            nv[2 * i + 1] = bf_hi(xw[i]);
            *(float2*)(s_xp + lrow * DM + lcol + 2 * i) = make_float2(nv[2 * i], nv[2 * i + 1]);
        }
        PROF(17);
        if (tid == 0 && cta < QN / 48) {
            mbar_expect_tx(bar_wq, DM * P48);
            tma_block(sbase + SM_WQ, &tm_q, cta * 48, 0, DM, P48, bar_wq);
        }
    }
    float* acc_o = g_o[ep & 1];
    float* acc_attn = g_attn[ep & 1];
    if (cta == gridDim.x - 1) {
#pragma unroll 1
        for (int i = tid; i < NB * QN / 4; i += NCONS) ((float4*)g_o[~ep & 1])[i] = make_float4(0.f, 0.f, 0.f, 0.f);
#pragma unroll 1
        for (int i = tid; i < NB * DM; i += NCONS) g_attn[~ep & 1][i] = 0.f;
    }
    ln_norm(nv, s_red, tid);
    cons_sync();
    PROF(14);
    if (cta < MODN / 32) {
        mbar_wait(bar_wm, 0);
        PROF(15);
        gemv_mma<5, 2>(sbase + SM_W32 + warp * 80 * P32, P32, sbase + SM_A + warp * 160, A_PITCH, s_part + warp * 320, lane);
        cons_sync();
        if (tid < 64) {
            const int b = tid >> 4, n = (tid & 15) * 2;
            ll_store(g_mod + (b * MODN + cta * 32 + n) / 2, tall_sum(s_part, b, n), tall_sum(s_part, b, n + 1), ep);
        }
    }
    PROF(1);

    if (cta < QN / 48) {
        cons_sync();
        mbar_wait(bar_wq, 0);
        PROF(16);
        uint32_t fq[5][3][4];
        frag_load<5, 3>(fq, sbase + SM_WQ + warp * 80 * P48, P48, lane);
        {
            long long t0 = 0;
            for (;;) {
                bool ok = true;
#pragma unroll
                for (int r = 0; r < 5; ++r) {
                    const int i = tid + r * NCONS, b = i / 320, c4 = i - b * 320;
                    const uint4 v = ll_ld2(g_mod + b * (MODN / 2) + 2 * c4);
                    *(uint2*)(s_part + b * DM + 2 * c4) = make_uint2(v.x, v.z);
                    ok = ok && v.y == ep && v.w == ep;
                }
                if (ok) break;
                if (t0 == 0) t0 = clock64();
                else if (clock64() - t0 > WAIT_LIMIT_CYCLES) __trap();
            }
        }
        cons_sync();
        PROF(2);
        uint32_t sh[5], sc[5];
#pragma unroll
        for (int i = 0; i < 5; ++i) {
            sh[i] = ((const uint32_t*)s_part)[lrow * DM + lcol / 2 + i];
            sc[i] = ((const uint32_t*)s_part)[lrow * DM + DM / 2 + lcol / 2 + i];
        }
        modulate(nv, sh, sc, h_dst);
        cons_sync();
        frag_mma<5, 3>(fq, sbase + SM_A + warp * 160, A_PITCH, s_part + warp * 320, lane);
        cons_sync();
        if (tid < 96) {
            const int b = tid / 24, n = (tid - b * 24) * 2;
            ll_store(g_q + (b * QN + cta * 48 + n) / 2, tall_sum(s_part, b, n), tall_sum(s_part, b, n + 1), ep);
        }
    }
    PROF(3);
    if (tid == 0) {
#pragma unroll 1
        for (int s = PRE; s < NST; ++s) mbar_arrive(bar_empty + s * 8);
    }
    uint32_t m_ga[5], m_sb[5], m_cb[5], m_fa[1] = {0u}, m_fb[1] = {0u};
    const int fcta = cta - ((int)gridDim.x - DM / 32);
    PROF(4);

    {
        const int sub = lane & 7, grp = lane >> 3;
        for (int u0 = warp * TPI;; u0 += 8 * TPI) {
            int item = -1;
            if (s_tag[u0 % NST] == u0 || tag_wait_stop(s_tag + u0 % NST, u0, s_item + NST)) item = s_item[u0 % NST];
            if ((u0 >= 8 * TPI && u0 < 16 * TPI) || (item < 0 && u0 < 8 * TPI)) {
                if (cta < FF / 16) {
                    ll_get(mod_row + DM, m_ga, ep);
                    ll_get(mod_row + 3 * DM / 2, m_sb, ep);
                    ll_get(mod_row + 2 * DM, m_cb, ep);
                }
                if (tid < 64 && fcta >= 0) {
                    ll_get(g_mod + ((tid >> 4) * MODN + 2 * DM + fcta * 32) / 2 + (tid & 15), m_fa, ep);
                    ll_get(g_mod + ((tid >> 4) * MODN + 5 * DM + fcta * 32) / 2 + (tid & 15), m_fb, ep);
                }
            }
            if (item < 0) break;
            const int bh = (item & (NITEM_K - 1)) / CHUNKS;
            if (item < NITEM_K) {
                unsigned int* gs = g_s + (size_t)item * ITEM_KEYS;
                float qr[24];
                {
                    const unsigned long long* qp = g_q + ((bh >> 5) * QN + (bh & 31) * DH) / 2 + sub * 4;
                    long long t0 = 0;
                    for (;;) {
                        bool ok = true;
#pragma unroll
                        for (int j = 0; j < 6; ++j) {
                            const uint4 v = ll_ld2(qp + (j >> 1) * 32 + (j & 1) * 2);
                            qr[j * 4 + 0] = bf_lo(v.x); qr[j * 4 + 1] = bf_hi(v.x);
                            qr[j * 4 + 2] = bf_lo(v.z); qr[j * 4 + 3] = bf_hi(v.z);
                            ok = ok && v.y == ep && v.w == ep;
                        }
                        if (ok) break;
                        if (t0 == 0) t0 = clock64();
                        else if (clock64() - t0 > WAIT_LIMIT_CYCLES) __trap();
                    }
                }
                float m_run = -INFINITY, l_run = 0.f;
#pragma unroll 1
                for (int hh = 0; hh < 2 * TPI; ++hh) {
                    const int u = u0 + (hh >> 1), st = u % NST;
                    if (!(hh & 1)) stage_wait(bar_full, s_tag, u);
                    const uint4* tile = (const uint4*)(smem + SM_RING + st * STAGE_BYTES) + (hh & 1) * (32 * 24);
                    float part[8];
#pragma unroll
                    for (int it = 0; it < 8; ++it) {
                        const uint4* row = tile + (it * 4 + grp) * 24 + sub;
                        const uint4 a = row[0], b = row[8], c = row[16];
                        part[it] = dot8(a, qr) + dot8(b, qr + 8) + dot8(c, qr + 16);
                    }
                    if (hh & 1) {
                        __syncwarp();
                        if (lane == 0) mbar_arrive(bar_empty + st * 8);
                    }
#pragma unroll
                    for (int j = 0; j < 4; ++j) {
                        const float send = (sub & 4) ? part[j] : part[j + 4];
                        const float keep = (sub & 4) ? part[j + 4] : part[j];
                        part[j] = keep + __shfl_xor_sync(0xffffffffu, send, 4);
                    }
#pragma unroll
                    for (int j = 0; j < 2; ++j) {
                        const float send = (sub & 2) ? part[j] : part[j + 2];
                        const float keep = (sub & 2) ? part[j + 2] : part[j];
                        part[j] = keep + __shfl_xor_sync(0xffffffffu, send, 2);
                    }
                    {
                        const float send = (sub & 1) ? part[0] : part[1];
                        const float keep = (sub & 1) ? part[1] : part[0];
                        part[0] = keep + __shfl_xor_sync(0xffffffffu, send, 1);
                    }
                    const float s = bf16r(bf16r(part[0]) * 0.07216878364870323f);
                    asm volatile("st.relaxed.gpu.global.u32 [%0], %1;" ::"l"(gs + hh * 32 + sub * 4 + grp), "r"(__float_as_uint(s) | tag16) : "memory");
                    const float m_new = fmaxf(m_run, s);
                    l_run = l_run * __expf(m_run - m_new) + __expf(s - m_new);
                    m_run = m_new;
                }
                const float m = warp_max(m_run);
                const float l = warp_sum(l_run * __expf(m_run - m));
                if (lane == 0)
                    asm volatile("st.relaxed.gpu.global.u64 [%0], %1;" ::"l"(g_stat + item),
                                 "l"(((unsigned long long)__float_as_uint(l) << 32) | (__float_as_uint(m) | tag16)) : "memory");
            } else {
                float pr[2 * TPI];
                {
                    const unsigned int* gs = g_s + (size_t)(item - NITEM_K) * ITEM_KEYS + lane;
                    uint2 st2;
                    long long t0 = 0;
                    for (;;) {
                        st2 = ll_ld1(g_stat + bh * CHUNKS + lane);
                        bool ok = (st2.x & 0xffffu) == tag16;
#pragma unroll
                        for (int hh = 0; hh < 2 * TPI; ++hh) {
                            unsigned int w;
                            asm volatile("ld.relaxed.gpu.global.u32 %0, [%1];" : "=r"(w) : "l"(gs + hh * 32) : "memory");
                            ok = ok && (w & 0xffffu) == tag16;
                            pr[hh] = bf_hi(w);
                        }
                        if (__all_sync(0xffffffffu, ok)) break;
                        if (t0 == 0) t0 = clock64();
                        else if (clock64() - t0 > WAIT_LIMIT_CYCLES) __trap();
                    }
                    const float mi = bf_hi(st2.x);
                    const float mm = warp_max(mi);
                    const float ll = warp_sum(__uint_as_float(st2.y) * __expf(mi - mm));
#pragma unroll
                    for (int hh = 0; hh < 2 * TPI; ++hh) pr[hh] = bf16r(__fdiv_rn(__expf(pr[hh] - mm), ll));
                }
                float acc[3][8];
#pragma unroll
                for (int j = 0; j < 3; ++j)
#pragma unroll
                    for (int e = 0; e < 8; ++e) acc[j][e] = 0.f;
#pragma unroll
                for (int hh = 0; hh < 2 * TPI; ++hh) {
                    const int u = u0 + (hh >> 1), st = u % NST;
                    if (!(hh & 1)) stage_wait(bar_full, s_tag, u);
                    const uint4* tile = (const uint4*)(smem + SM_RING + st * STAGE_BYTES) + (hh & 1) * (32 * 24);
#pragma unroll
                    for (int it = 0; it < 8; ++it) {
                        const uint4* row = tile + (it * 4 + grp) * 24 + sub;
                        const uint4 a = row[0], b = row[8], c = row[16];
                        const float p = __shfl_sync(0xffffffffu, pr[hh], it * 4 + grp);
                        fma8(acc[0], a, p);
                        fma8(acc[1], b, p);
                        fma8(acc[2], c, p);
                    }
                    if (hh & 1) {
                        __syncwarp();
                        if (lane == 0) mbar_arrive(bar_empty + st * 8);
                    }
                }
                float* go = acc_o + (bh >> 5) * QN + (bh & 31) * DH + sub * 8;
#pragma unroll
                for (int j = 0; j < 3; ++j) {
#pragma unroll
                    for (int e = 0; e < 8; ++e) {
                        float v = acc[j][e];
                        v += __shfl_xor_sync(0xffffffffu, v, 8);
                        v += __shfl_xor_sync(0xffffffffu, v, 16);
                        acc[j][e] = v;
                    }
                    if (grp == 0) {
                        red_add_v4(go + j * 64, acc[j][0], acc[j][1], acc[j][2], acc[j][3]);
                        red_add_v4(go + j * 64 + 4, acc[j][4], acc[j][5], acc[j][6], acc[j][7]);
                    }
                }
            }
        }
    }
    PROF(5);
    grid_arrive(&g_bar[2], tid);
    PROF(6);
    if (fcta >= 0 && tid == 0) {
        mbar_expect_tx(bar_wd, FF * P32);
        tma_block(sbase + SM_WD, &tm_down, fcta * 32, 0, FF, P32, bar_wd);
    }
    if (cta < ND) {
        const int u_end = s_item[NST];
        if (cta < FF / 16 && tid == 0) {
            mbar_expect_tx(bar_gu, 2 * DM * 32);
            tma_block(sbase + SM_W32, &tm_gate, cta * 16, 0, DM, 32, bar_gu);
            tma_block(sbase + SM_W32 + DM * 32, &tm_up, cta * 16, 0, DM, 32, bar_gu);
        }
        uint32_t fd[4][5][4];
        mbar_wait(bar_wo, 0);
        frag_load<4, 5>(fd, sbase + SM_RING + ((u_end + (warp >> 1)) % NST) * STAGE_BYTES + (warp & 1) * 64 * P80, P80, lane);
        grid_wait(&g_bar[2], target, tid);
        if (cta == 0 && tid == 0) { g_work = 0u; g_epoch = ep; }
        PROF(7);
        {
            float4 v[2];
#pragma unroll
            for (int r = 0; r < 2; ++r) v[r] = __ldcg((const float4*)(acc_o + (2 * r + (tid >> 7)) * QN + ks * WO_ROWS) + (tid & 127));
#pragma unroll
            for (int r = 0; r < 2; ++r) {
                __nv_bfloat162 p0 = __floats2bfloat162_rn(v[r].x, v[r].y), p1 = __floats2bfloat162_rn(v[r].z, v[r].w);
                *(uint2*)(smem + SM_A + (2 * r + (tid >> 7)) * A_PITCH + (tid & 127) * 8) = make_uint2(*(uint32_t*)&p0, *(uint32_t*)&p1);
            }
        }
        cons_sync();
        frag_mma<4, 5>(fd, sbase + SM_A + warp * 128, A_PITCH, s_part + warp * 320, lane);
        cons_sync();
        if (tid < 80) {
            const int b = tid / 20, n4 = tid - b * 20;
            float4 s4 = make_float4(0.f, 0.f, 0.f, 0.f);
#pragma unroll
            for (int w = 0; w < 8; ++w) {
                const float4 v = *(const float4*)(s_part + (w * 4 + b) * 80 + n4 * 4);
                s4.x += v.x; s4.y += v.y; s4.z += v.z; s4.w += v.w;
            }
            red_add_v4(acc_attn + b * DM + ns * 80 + n4 * 4, s4.x, s4.y, s4.z, s4.w);
        }
        PROF(8);
        grid_arrive(&g_bar[3], tid);
    }
    const bool has_e = cta < FF / 16;
    if (!has_e && fcta < 0) return;
    if (has_e) {
        uint32_t fe[5][2][4];
        mbar_wait(bar_gu, 0);
        frag_load<5, 2>(fe, sbase + SM_W32 + warp * 80 * 32, 32, lane, DM * 32);
        grid_wait(&g_bar[3], ep * ND, tid);
        PROF(9);
        {
            float4 v[3];
#pragma unroll
            for (int r = 0; r < 3; ++r)
                if (tid + r * NCONS < NB * DM / 4) v[r] = __ldcg((const float4*)acc_attn + tid + r * NCONS);
#pragma unroll
            for (int r = 0; r < 3; ++r)
                if (tid + r * NCONS < NB * DM / 4) ((float4*)s_part)[tid + r * NCONS] = v[r];
        }
        cons_sync();
#pragma unroll
        for (int i = 0; i < 5; ++i) {
            const float2 av = *((const float2*)(s_part + lrow * DM + lcol) + i);
            const float2 xv = *((const float2*)(s_xp + lrow * DM + lcol) + i);
            nv[2 * i] = bf16r(xv.x + bf16r(bf_lo(m_ga[i]) * bf16r(av.x)));
            nv[2 * i + 1] = bf16r(xv.y + bf16r(bf_hi(m_ga[i]) * bf16r(av.y)));
        }
        ln_norm(nv, s_red, tid);
        modulate(nv, m_sb, m_cb, h_dst);
        cons_sync();
        frag_mma<5, 2>(fe, sbase + SM_A + warp * 160, A_PITCH, s_part + warp * 320, lane);
        cons_sync();
        if (tid < 32) {
            const int b = tid >> 3, n = (tid & 7) * 2;
            const float g0 = bf16r(tall_sum(s_part, b, n)), g1 = bf16r(tall_sum(s_part, b, n + 1));
            const float u0 = bf16r(tall_sum(s_part, b, 16 + n)), u1 = bf16r(tall_sum(s_part, b, 17 + n));
            ll_store(g_act + (b * FF + cta * 16 + n) / 2, bf16r(gelu_tanh(g0)) * u0, bf16r(gelu_tanh(g1)) * u1, ep);
        }
        PROF(10);
        if (fcta < 0) return;
    } else {
        grid_wait(&g_bar[3], ep * ND, tid);
    }
    {
        float x10 = 0.f, x11 = 0.f;
        if (tid < 64) {
            const int b = tid >> 4, col = fcta * 32 + (tid & 15) * 2;
            const float2 av = __ldcg((const float2*)(acc_attn + b * DM + col));
            x10 = bf16r(s_xp[b * DM + col] + bf16r(bf_lo(m_fa[0]) * bf16r(av.x)));
            x11 = bf16r(s_xp[b * DM + col + 1] + bf16r(bf_hi(m_fa[0]) * bf16r(av.y)));
        }
        mbar_wait(bar_wd, 0);
        uint32_t ff[12][2][4];
        frag_load<12, 2>(ff, sbase + SM_WD + warp * 192 * P32, P32, lane);
        long long t0 = 0;
        for (;;) {
            bool ok = true;
#pragma unroll
            for (int r = 0; r < 6; ++r) {
                const int i = tid + r * NCONS, b = i / 384, c4 = i - b * 384;
                const uint4 v = ll_ld2(g_act + 2 * i);
                *(uint2*)(smem + SM_ACT + b * ACT_PITCH + c4 * 8) = make_uint2(v.x, v.z);
                ok = ok && v.y == ep && v.w == ep;
            }
            if (ok) break;
            if (t0 == 0) t0 = clock64();
            else if (clock64() - t0 > WAIT_LIMIT_CYCLES) __trap();
        }
        cons_sync();
        PROF(11);
        frag_mma<12, 2>(ff, sbase + SM_ACT + warp * 384, ACT_PITCH, s_part + warp * 320, lane);
        cons_sync();
        if (tid < 64) {
            const int b = tid >> 4, n = (tid & 15) * 2;
            const float f0 = bf16r(tall_sum(s_part, b, n)), f1 = bf16r(tall_sum(s_part, b, n + 1));
            *(__nv_bfloat162*)(out + b * DM + fcta * 32 + n) =
                __floats2bfloat162_rn(x10 + bf16r(bf_lo(m_fb[0]) * f0), x11 + bf16r(bf_hi(m_fb[0]) * f1));
        }
    }
    PROF(12);
}

}

extern "C" void kernel_launch(void* const* d_in, const int* in_sizes, int n_in, void* d_out, int out_size) {
    (void)in_sizes; (void)n_in; (void)out_size;
    const __nv_bfloat16* A_x = (const __nv_bfloat16*)d_in[0];
    const __nv_bfloat16* A_k = (const __nv_bfloat16*)d_in[1];
    const __nv_bfloat16* A_v = (const __nv_bfloat16*)d_in[2];
    const __nv_bfloat16* A_wq = (const __nv_bfloat16*)d_in[3];
    const __nv_bfloat16* A_wo = (const __nv_bfloat16*)d_in[4];
    const __nv_bfloat16* B_wg = (const __nv_bfloat16*)d_in[6];
    const __nv_bfloat16* B_wu = (const __nv_bfloat16*)d_in[7];
    const __nv_bfloat16* B_wd = (const __nv_bfloat16*)d_in[8];
    const __nv_bfloat16* c = (const __nv_bfloat16*)d_in[9];
    const __nv_bfloat16* w_mod = (const __nv_bfloat16*)d_in[10];
    typedef CUresult (*encode_fn)(CUtensorMap*, CUtensorMapDataType, cuuint32_t, void*, const cuuint64_t*, const cuuint64_t*,
                                  const cuuint32_t*, const cuuint32_t*, CUtensorMapInterleave, CUtensorMapSwizzle,
                                  CUtensorMapL2promotion, CUtensorMapFloatOOBfill);
    static int grid = 0;
    static encode_fn encode = nullptr;
    if (grid == 0) {
        cudaFuncSetAttribute(decode_block_kernel, cudaFuncAttributeMaxDynamicSharedMemorySize, SM_TOTAL);
        int dev = 0, sms = 0;
        cudaGetDevice(&dev);
        cudaDeviceGetAttribute(&sms, cudaDevAttrMultiProcessorCount, dev);
        grid = sms < 132 ? sms : 132;
        void* fn = nullptr;
        cudaDriverEntryPointQueryResult qres;
        cudaGetDriverEntryPoint("cuTensorMapEncodeTiled", &fn, cudaEnableDefault, &qres);
        encode = (encode_fn)fn;
    }
    auto make_map = [&](const __nv_bfloat16* w, int rows, int cols, int box_bytes) {
        CUtensorMap m;
        const cuuint64_t dims[2] = {(cuuint64_t)cols, (cuuint64_t)rows};
        const cuuint64_t strides[1] = {(cuuint64_t)cols * 2};
        const cuuint32_t box[2] = {(cuuint32_t)(box_bytes / 2), (cuuint32_t)BOX};
        const cuuint32_t estr[2] = {1, 1};
        encode(&m, CU_TENSOR_MAP_DATA_TYPE_BFLOAT16, 2, (void*)w, dims, strides, box, estr, CU_TENSOR_MAP_INTERLEAVE_NONE,
               CU_TENSOR_MAP_SWIZZLE_NONE, CU_TENSOR_MAP_L2_PROMOTION_L2_128B, CU_TENSOR_MAP_FLOAT_OOB_FILL_NONE);
        return m;
    };
    decode_block_kernel<<<grid, NTHREADS, SM_TOTAL>>>(A_x, A_k, A_v, c, (__nv_bfloat16*)d_out, make_map(w_mod, DM, MODN, P32),
                                                      make_map(A_wq, DM, QN, P48), make_map(A_wo, QN, DM, P80),
                                                      make_map(B_wg, DM, FF, 32), make_map(B_wu, DM, FF, 32),
                                                      make_map(B_wd, FF, DM, P32));
}
```

```cpp
#include <cuda.h>
#include <cuda_runtime.h>
#include <cuda_bf16.h>
#include <stdint.h>

namespace {

constexpr int NB = 4;
constexpr int DM = 640;
constexpr int NH = 32;
constexpr int SK = 4096;
constexpr int DH = 192;
constexpr int FF = 1536;
constexpr int MODN = 6 * DM;
constexpr int QN = NH * DH;
constexpr int NBH = NB * NH;

constexpr int NCONS = 256;
constexpr int NTHREADS = NCONS + 32;
constexpr int TILE_KEYS = 64;
constexpr int TILE_BYTES = TILE_KEYS * DH * 2;
constexpr int STAGE_BYTES = TILE_BYTES;
constexpr int NST = 6;
constexpr int PRE = 3;
constexpr int TPI = 2;
constexpr int ITEM_KEYS = TPI * TILE_KEYS;
constexpr int CHUNKS = SK / ITEM_KEYS;
constexpr int NITEM_K = NBH * CHUNKS;
constexpr int NITEM = 2 * NITEM_K;

constexpr int A_PITCH = 1296;
constexpr int ACT_PITCH = FF * 2 + 16;
constexpr int P32 = 80;
constexpr int P48 = 112;
constexpr int P80 = 176;
constexpr int WO_ROWS = 512;
constexpr int ND = QN / WO_ROWS * 8;
constexpr int BOX = 128;

constexpr int SM_RING = 0;
constexpr int SM_WQ = PRE * STAGE_BYTES;
constexpr int SM_WD = 0;
constexpr int SM_W32 = NST * STAGE_BYTES;
constexpr int SM_ACT = SM_W32;
constexpr int SM_A = SM_W32 + DM * P32;
constexpr int SM_PART = SM_A + NB * A_PITCH;
constexpr int SM_XP = SM_PART + 8 * 4 * 80 * 4;
constexpr int SM_RED = SM_XP + NB * DM * 4;
constexpr int SM_ITEM = SM_RED + 16 * 4;
constexpr int SM_TAG = SM_ITEM + 16 * 4;
constexpr int SM_BAR = SM_TAG + 16 * 4;
constexpr int SM_TOTAL = SM_BAR + (2 * NST + 5) * 8;
static_assert(SM_WQ + DM * P48 <= NST * STAGE_BYTES, "prologue overlay");
static_assert(SM_WD + FF * P32 <= NST * STAGE_BYTES && BOX * P80 <= STAGE_BYTES, "tail overlay");
static_assert(SM_TOTAL <= 232448, "smem");
constexpr int THR_ITEMS = 6;
constexpr int THR_DEPTH = 4;

__device__ __align__(128) unsigned long long g_mod[NB * MODN / 2];
__device__ __align__(128) unsigned long long g_q[NB * QN / 2];
__device__ __align__(128) unsigned long long g_act[NB * FF / 2];
__device__ __align__(128) unsigned int g_s[NBH * SK];
__device__ __align__(128) unsigned long long g_stat[NBH * CHUNKS];
__device__ __align__(128) float g_o[2][NB * QN];
__device__ __align__(128) float g_attn[2][NB * DM];
__device__ __align__(128) unsigned int g_bar[8];
__device__ unsigned int g_work;
__device__ unsigned int g_epoch;

#define PROF(k) do { } while (0)
#define PROFP(k) do { } while (0)

__device__ __forceinline__ float bf16r(float x) {
    uint32_t r;
    asm("cvt.rn.bf16x2.f32 %0, %1, %2;" : "=r"(r) : "f"(x), "f"(0.f));
    return __uint_as_float(r);
}
__device__ __forceinline__ float bf_lo(uint32_t u) { return __uint_as_float(u << 16); }
__device__ __forceinline__ float bf_hi(uint32_t u) { return __uint_as_float(u & 0xffff0000u); }

__device__ __forceinline__ uint32_t smem_u32(const void* p) { return (uint32_t)__cvta_generic_to_shared(p); }
__device__ __forceinline__ void mbar_init(uint32_t bar, uint32_t count) {
    asm volatile("mbarrier.init.shared::cta.b64 [%0], %1;" ::"r"(bar), "r"(count) : "memory");
}
__device__ __forceinline__ void mbar_expect_tx(uint32_t bar, uint32_t bytes) {
    asm volatile("mbarrier.arrive.expect_tx.shared::cta.b64 _, [%0], %1;" ::"r"(bar), "r"(bytes) : "memory");
}
__device__ __forceinline__ void mbar_arrive(uint32_t bar) {
    asm volatile("mbarrier.arrive.shared::cta.b64 _, [%0];" ::"r"(bar) : "memory");
}
constexpr long long WAIT_LIMIT_CYCLES = 200000000LL;
__device__ __forceinline__ uint32_t mbar_try(uint32_t bar, uint32_t parity) {
    uint32_t done;
    asm volatile(
        "{\n\t.reg .pred p;\n\t"
        "mbarrier.try_wait.parity.shared::cta.b64 p, [%1], %2;\n\t"
        "selp.u32 %0, 1, 0, p;\n\t}"
        : "=r"(done) : "r"(bar), "r"(parity) : "memory");
    return done;
}
__device__ __noinline__ void mbar_wait_slow(uint32_t bar, uint32_t parity) {
    const long long t0 = clock64();
    while (!mbar_try(bar, parity)) {
        if (clock64() - t0 > WAIT_LIMIT_CYCLES) __trap();
    }
}
__device__ __forceinline__ void mbar_wait(uint32_t bar, uint32_t parity) {
    if (!mbar_try(bar, parity)) mbar_wait_slow(bar, parity);
}
__device__ __noinline__ void tag_wait_slow(volatile int* tag, int u) {
    const long long t0 = clock64();
    while (*tag != u) {
        __nanosleep(32);
        if (clock64() - t0 > WAIT_LIMIT_CYCLES) __trap();
    }
}
__device__ __noinline__ bool tag_wait_stop(volatile int* tag, int u, volatile int* stop) {
    const long long t0 = clock64();
    while (*tag != u) {
        if (*stop <= u) return false;
        __nanosleep(32);
        if (clock64() - t0 > WAIT_LIMIT_CYCLES) __trap();
    }
    return true;
}
__device__ __forceinline__ void stage_wait(uint32_t bar_full, volatile int* s_tag, int u) {
    const int st = u % NST;
    if (s_tag[st] != u) tag_wait_slow(s_tag + st, u);
    mbar_wait(bar_full + st * 8, (u / NST) & 1);
}
__device__ __forceinline__ void bulk_g2s(uint32_t dst, const void* src, uint32_t bytes, uint32_t bar, uint64_t pol) {
    asm volatile(
        "cp.async.bulk.shared::cluster.global.mbarrier::complete_tx::bytes.L2::cache_hint [%0], [%1], %2, [%3], %4;"
        ::"r"(dst), "l"(src), "r"(bytes), "r"(bar), "l"(pol) : "memory");
}
__device__ __forceinline__ void tma2d(uint32_t dst, const CUtensorMap* map, int col, int row, uint32_t bar) {
    asm volatile(
        "cp.async.bulk.tensor.2d.shared::cluster.global.tile.mbarrier::complete_tx::bytes [%0], [%1, {%2, %3}], [%4];"
        ::"r"(dst), "l"(map), "r"(col), "r"(row), "r"(bar) : "memory");
}
__device__ __forceinline__ void tma_block(uint32_t dst, const CUtensorMap* map, int col, int row, int rows, int pitch, uint32_t bar) {
#pragma unroll 1
    for (int r = 0; r < rows; r += BOX) tma2d(dst + r * pitch, map, col, row + r, bar);
}
__device__ __forceinline__ void red_release_add(unsigned int* p, unsigned int v) {
    asm volatile("red.release.gpu.global.add.u32 [%0], %1;" ::"l"(p), "r"(v) : "memory");
}
__device__ __forceinline__ void cons_sync() { asm volatile("bar.sync 1, 256;" ::: "memory"); }

__device__ __forceinline__ void red_add_v4(float* p, float a, float b, float c, float d) {
    asm volatile("red.global.add.v4.f32 [%0], {%1, %2, %3, %4};" ::"l"(p), "f"(a), "f"(b), "f"(c), "f"(d) : "memory");
}
__device__ __forceinline__ unsigned int ld_acquire(const unsigned int* p) {
    unsigned int v;
    asm volatile("ld.acquire.gpu.global.u32 %0, [%1];" : "=r"(v) : "l"(p) : "memory");
    return v;
}
__device__ __forceinline__ void ll_store(unsigned long long* p, float a, float b, unsigned int ep) {
    __nv_bfloat162 v = __floats2bfloat162_rn(a, b);
    const unsigned long long w = ((unsigned long long)ep << 32) | *(uint32_t*)&v;
    asm volatile("st.relaxed.gpu.global.u64 [%0], %1;" ::"l"(p), "l"(w) : "memory");
}
__device__ __forceinline__ uint2 ll_ld1(const unsigned long long* p) {
    unsigned long long w;
    asm volatile("ld.relaxed.gpu.global.u64 %0, [%1];" : "=l"(w) : "l"(p) : "memory");
    return make_uint2((uint32_t)w, (uint32_t)(w >> 32));
}
__device__ __forceinline__ uint4 ll_ld2(const unsigned long long* p) {
    unsigned long long a, b;
    asm volatile("ld.relaxed.gpu.global.v2.u64 {%0, %1}, [%2];" : "=l"(a), "=l"(b) : "l"(p) : "memory");
    return make_uint4((uint32_t)a, (uint32_t)(a >> 32), (uint32_t)b, (uint32_t)(b >> 32));
}
template <int N>
__device__ __forceinline__ void ll_get(const unsigned long long* p, uint32_t (&d)[N], unsigned int ep) {
    long long t0 = 0;
    for (;;) {
        bool ok = true;
#pragma unroll
        for (int i = 0; i < N; ++i) {
            const uint2 v = ll_ld1(p + i);
            d[i] = v.x;
            ok = ok && (v.y == ep);
        }
        if (ok) break;
        if (t0 == 0) t0 = clock64();
        else if (clock64() - t0 > WAIT_LIMIT_CYCLES) __trap();
    }
}

__device__ __forceinline__ void grid_arrive(unsigned int* ctr, int tid) {
    cons_sync();
    if (tid == 0) red_release_add(ctr, 1u);
}
__device__ __noinline__ void grid_wait(const unsigned int* ctr, unsigned int target, int tid) {
    if (tid == 0) {
        const long long t0 = clock64();
        while ((int)(ld_acquire(ctr) - target) < 0) {
            if (clock64() - t0 > WAIT_LIMIT_CYCLES) __trap();
        }
    }
    cons_sync();
}

__device__ __forceinline__ float warp_sum(float v) {
#pragma unroll
    for (int o = 16; o > 0; o >>= 1) v += __shfl_xor_sync(0xffffffffu, v, o);
    return v;
}
__device__ __forceinline__ float warp_max(float v) {
#pragma unroll
    for (int o = 16; o > 0; o >>= 1) v = fmaxf(v, __shfl_xor_sync(0xffffffffu, v, o));
    return v;
}

__device__ __forceinline__ void fma8(float (&acc)[8], const uint4& w, float s) {
    acc[0] = fmaf(s, bf_lo(w.x), acc[0]);
    acc[1] = fmaf(s, bf_hi(w.x), acc[1]);
    acc[2] = fmaf(s, bf_lo(w.y), acc[2]);
    acc[3] = fmaf(s, bf_hi(w.y), acc[3]);
    acc[4] = fmaf(s, bf_lo(w.z), acc[4]);
    acc[5] = fmaf(s, bf_hi(w.z), acc[5]);
    acc[6] = fmaf(s, bf_lo(w.w), acc[6]);
    acc[7] = fmaf(s, bf_hi(w.w), acc[7]);
}
__device__ __forceinline__ float dot8(const uint4& w, const float* q) {
    float s = q[0] * bf_lo(w.x);
    s = fmaf(q[1], bf_hi(w.x), s);
    s = fmaf(q[2], bf_lo(w.y), s);
    s = fmaf(q[3], bf_hi(w.y), s);
    s = fmaf(q[4], bf_lo(w.z), s);
    s = fmaf(q[5], bf_hi(w.z), s);
    s = fmaf(q[6], bf_lo(w.w), s);
    s = fmaf(q[7], bf_hi(w.w), s);
    return s;
}

template <int KS, int NT>
__device__ __noinline__ void gemv_mma(uint32_t w, int w_pitch, uint32_t a, int a_pitch, float* part, int lane) {
    float c[NT][4];
#pragma unroll
    for (int nt = 0; nt < NT; ++nt) { c[nt][0] = 0.f; c[nt][1] = 0.f; c[nt][2] = 0.f; c[nt][3] = 0.f; }
    const uint32_t ap = a + (lane >> 2) * a_pitch + (lane & 3) * 4;
    const uint32_t wp = w + ((lane & 7) + ((lane >> 4) << 3)) * w_pitch + ((lane >> 3) & 1) * 16;
#pragma unroll
    for (int ks = 0; ks < KS; ++ks) {
        uint32_t b0 = 0, b1 = 0;
        if (lane < 16) {
            asm("ld.shared.u32 %0, [%1];" : "=r"(b0) : "r"(ap + ks * 32));
            asm("ld.shared.u32 %0, [%1];" : "=r"(b1) : "r"(ap + ks * 32 + 16));
        }
#pragma unroll
        for (int nt = 0; nt < NT; ++nt) {
            uint32_t a0, a1, a2, a3;
            asm("ldmatrix.sync.aligned.m8n8.x4.trans.shared.b16 {%0, %1, %2, %3}, [%4];"
                         : "=r"(a0), "=r"(a1), "=r"(a2), "=r"(a3) : "r"(wp + ks * 16 * w_pitch + nt * 32));
            asm("mma.sync.aligned.m16n8k16.row.col.f32.bf16.bf16.f32 {%0, %1, %2, %3}, {%4, %5, %6, %7}, "
                "{%8, %9}, {%0, %1, %2, %3};"
                : "+f"(c[nt][0]), "+f"(c[nt][1]), "+f"(c[nt][2]), "+f"(c[nt][3])
                : "r"(a0), "r"(a1), "r"(a2), "r"(a3), "r"(b0), "r"(b1));
        }
    }
    if ((lane & 3) < 2) {
        float* pp = part + (lane & 3) * 160 + (lane >> 2);
#pragma unroll
        for (int nt = 0; nt < NT; ++nt) {
            pp[nt * 16] = c[nt][0];
            pp[nt * 16 + 80] = c[nt][1];
            pp[nt * 16 + 8] = c[nt][2];
            pp[nt * 16 + 88] = c[nt][3];
        }
    }
}

template <int KS, int NT>
__device__ __forceinline__ void frag_load(uint32_t (&f)[KS][NT][4], uint32_t w, int w_pitch, int lane, int n_stride = 32) {
    const uint32_t wp = w + ((lane & 7) + ((lane >> 4) << 3)) * w_pitch + ((lane >> 3) & 1) * 16;
#pragma unroll
    for (int ks = 0; ks < KS; ++ks)
#pragma unroll
        for (int nt = 0; nt < NT; ++nt)
            asm volatile("ldmatrix.sync.aligned.m8n8.x4.trans.shared.b16 {%0, %1, %2, %3}, [%4];"
                         : "=r"(f[ks][nt][0]), "=r"(f[ks][nt][1]), "=r"(f[ks][nt][2]), "=r"(f[ks][nt][3])
                         : "r"(wp + ks * 16 * w_pitch + nt * n_stride) : "memory");
}
template <int KS, int NT>
__device__ __forceinline__ void frag_mma(const uint32_t (&f)[KS][NT][4], uint32_t a, int a_pitch, float* part, int lane) {
    float c[NT][4];
#pragma unroll
    for (int nt = 0; nt < NT; ++nt) { c[nt][0] = 0.f; c[nt][1] = 0.f; c[nt][2] = 0.f; c[nt][3] = 0.f; }
    const uint32_t ap = a + (lane >> 2) * a_pitch + (lane & 3) * 4;
    uint32_t b[KS][2];
#pragma unroll
    for (int ks = 0; ks < KS; ++ks) {
        b[ks][0] = 0; b[ks][1] = 0;
        if (lane < 16) {
            asm volatile("ld.shared.u32 %0, [%1];" : "=r"(b[ks][0]) : "r"(ap + ks * 32) : "memory");
            asm volatile("ld.shared.u32 %0, [%1];" : "=r"(b[ks][1]) : "r"(ap + ks * 32 + 16) : "memory");
        }
    }
#pragma unroll
    for (int ks = 0; ks < KS; ++ks)
#pragma unroll
        for (int nt = 0; nt < NT; ++nt)
            asm("mma.sync.aligned.m16n8k16.row.col.f32.bf16.bf16.f32 {%0, %1, %2, %3}, {%4, %5, %6, %7}, "
                "{%8, %9}, {%0, %1, %2, %3};"
                : "+f"(c[nt][0]), "+f"(c[nt][1]), "+f"(c[nt][2]), "+f"(c[nt][3])
                : "r"(f[ks][nt][0]), "r"(f[ks][nt][1]), "r"(f[ks][nt][2]), "r"(f[ks][nt][3]), "r"(b[ks][0]), "r"(b[ks][1]));
    if ((lane & 3) < 2) {
        float* pp = part + (lane & 3) * 160 + (lane >> 2);
#pragma unroll
        for (int nt = 0; nt < NT; ++nt) {
            pp[nt * 16] = c[nt][0];
            pp[nt * 16 + 80] = c[nt][1];
            pp[nt * 16 + 8] = c[nt][2];
            pp[nt * 16 + 88] = c[nt][3];
        }
    }
}

__device__ __forceinline__ float tall_sum(const float* part, int b, int n) {
    float s = 0.f;
#pragma unroll
    for (int w = 0; w < 8; ++w) s += part[(w * 4 + b) * 80 + n];
    return s;
}

__device__ __forceinline__ void ln_norm(float (&v)[10], float* s_red, int tid) {
    const int warp = tid >> 5;
    const float pv = __shfl_sync(0xffffffffu, v[0], 0);
    float s = 0.f, q = 0.f;
#pragma unroll
    for (int i = 0; i < 10; ++i) { const float d = v[i] - pv; s += d; q = fmaf(d, d, q); }
#pragma unroll
    for (int o = 16; o > 0; o >>= 1) {
        s += __shfl_xor_sync(0xffffffffu, s, o);
        q += __shfl_xor_sync(0xffffffffu, q, o);
    }
    const float md = s * (2.0f / DM);
    if ((tid & 31) == 0) *(float2*)(s_red + 2 * warp) = make_float2(pv + md, fmaxf(q - s * md, 0.f));
    cons_sync();
    const float4 r = *(const float4*)(s_red + 4 * (warp >> 1));
    const float dm = r.x - r.z;
    const float var = (r.y + r.w + dm * dm * (DM / 4)) * (1.0f / DM);
    const float mean = bf16r(0.5f * (r.x + r.z));
    const float inv = __fdiv_rn(1.0f, bf16r(sqrtf(bf16r(bf16r(var) + 1e-5f))));
#pragma unroll
    for (int i = 0; i < 10; ++i) v[i] = bf16r(bf16r(v[i] - mean) * inv);
}
__device__ __forceinline__ void modulate(const float (&n)[10], const uint32_t (&sh)[5], const uint32_t (&sc)[5], uint32_t* dst) {
#pragma unroll
    for (int i = 0; i < 5; ++i) {
        const float h0 = bf16r(n[2 * i] * bf16r(1.0f + bf_lo(sc[i]))) + bf_lo(sh[i]);
        const float h1 = bf16r(n[2 * i + 1] * bf16r(1.0f + bf_hi(sc[i]))) + bf_hi(sh[i]);
        __nv_bfloat162 p = __floats2bfloat162_rn(h0, h1);
        dst[i] = *(uint32_t*)&p;
    }
}

__device__ __forceinline__ float gelu_tanh(float x) {
    const float kBeta = 0.7978845608028654f;
    const float inner = kBeta * (x + 0.044715f * x * x * x);
    return 0.5f * x * (1.0f + tanhf(inner));
}

__global__ void __launch_bounds__(NTHREADS, 1)
decode_block_kernel(const __nv_bfloat16* __restrict__ x_in, const __nv_bfloat16* __restrict__ k_cache,
                    const __nv_bfloat16* __restrict__ v_cache, const __nv_bfloat16* __restrict__ cvec,
                    __nv_bfloat16* __restrict__ out, const __grid_constant__ CUtensorMap tm_mod,
                    const __grid_constant__ CUtensorMap tm_q, const __grid_constant__ CUtensorMap tm_o,
                    const __grid_constant__ CUtensorMap tm_gate, const __grid_constant__ CUtensorMap tm_up,
                    const __grid_constant__ CUtensorMap tm_down) {
    extern __shared__ __align__(128) unsigned char smem[];
    const int tid = threadIdx.x;
    const int cta = blockIdx.x;

    const uint32_t sbase = smem_u32(smem);
    const uint32_t bar_full = sbase + SM_BAR;
    const uint32_t bar_empty = bar_full + NST * 8;
    volatile int* s_item = (volatile int*)(smem + SM_ITEM);
    volatile int* s_tag = (volatile int*)(smem + SM_TAG);

    const uint32_t bar_wm = bar_empty + NST * 8, bar_wq = bar_wm + 8, bar_wo = bar_wm + 16, bar_gu = bar_wm + 24, bar_wd = bar_wm + 32;
    PROF(0);
    const int lrow = (tid >> 6) & 3, lcol = (tid & 63) * 10;
    unsigned int ep0 = 0;
    uint4 c0 = make_uint4(0u, 0u, 0u, 0u), c1 = c0;
    uint32_t xw[5];
    if (tid < NCONS) {
        asm volatile("ld.relaxed.gpu.global.u32 %0, [%1];" : "=r"(ep0) : "l"(&g_epoch));
        asm volatile("ld.global.nc.v4.u32 {%0, %1, %2, %3}, [%4];" : "=r"(c0.x), "=r"(c0.y), "=r"(c0.z), "=r"(c0.w) : "l"((const uint4*)cvec + tid));
        if (tid < 320 - NCONS)
            asm volatile("ld.global.nc.v4.u32 {%0, %1, %2, %3}, [%4];" : "=r"(c1.x), "=r"(c1.y), "=r"(c1.z), "=r"(c1.w) : "l"((const uint4*)cvec + tid + NCONS));
#pragma unroll
        for (int i = 0; i < 5; ++i)
            asm volatile("ld.global.nc.u32 %0, [%1];" : "=r"(xw[i]) : "l"((const uint32_t*)(x_in + lrow * DM + lcol) + i));
    }
    if (tid < NST) s_tag[tid] = -1;
    if (tid == NST) s_item[NST] = 0x7fffffff;
    if (tid == NCONS) {
#pragma unroll 1
        for (int s = 0; s < 2 * NST + 5; ++s) mbar_init(bar_full + s * 8, 1);
        asm volatile("fence.mbarrier_init.release.cluster;" ::: "memory");
        asm volatile("fence.proxy.async.shared::cta;" ::: "memory");
#pragma unroll 1
        for (int s = 0; s < PRE; ++s) mbar_arrive(bar_empty + s * 8);
    }
    __syncthreads();
    const int ks = cta >> 3, ns = cta & 7;

    if (tid >= NCONS) {
        if (tid == NCONS) {
            int u = 0;
            const int G = (int)gridDim.x;
            uint64_t pol;
            asm volatile("createpolicy.fractional.L2::evict_first.b64 %0, 1.0;" : "=l"(pol));
            auto produce = [&](const int item) {
                const int it = item & (NITEM_K - 1);
                const bool is_v = item >= NITEM_K;
                const unsigned char* src = (const unsigned char*)(is_v ? v_cache : k_cache) + (size_t)it * (ITEM_KEYS * DH * 2);
#pragma unroll 1
                for (int t = 0; t < TPI; ++t, ++u) {
                    const int st = u % NST;
                    const uint32_t fb = bar_full + st * 8;
                    mbar_wait(bar_empty + st * 8, (u / NST) & 1);
                    if (item >= NITEM - THR_ITEMS * G && u >= THR_DEPTH)
                        mbar_wait(bar_empty + ((u - THR_DEPTH) % NST) * 8, ((u - THR_DEPTH) / NST + 1) & 1);
                    s_item[st] = item;
                    s_tag[st] = u;
                    mbar_expect_tx(fb, TILE_BYTES);
                    bulk_g2s(sbase + SM_RING + st * STAGE_BYTES, src + t * TILE_BYTES, TILE_BYTES, fb, pol);
                }
            };
            if (cta < MODN / 32) {
                mbar_expect_tx(bar_wm, DM * P32);
                tma_block(sbase + SM_W32, &tm_mod, cta * 32, 0, DM, P32, bar_wm);
            }
            asm volatile("prefetch.tensormap [%0];" ::"l"(&tm_q) : "memory");
            asm volatile("prefetch.tensormap [%0];" ::"l"(&tm_o) : "memory");
            asm volatile("prefetch.tensormap [%0];" ::"l"(&tm_gate) : "memory");
            asm volatile("prefetch.tensormap [%0];" ::"l"(&tm_up) : "memory");
            asm volatile("prefetch.tensormap [%0];" ::"l"(&tm_down) : "memory");
            if (cta < MODN / 32) mbar_wait(bar_wm, 0);
            int item = cta;
#pragma unroll 1
            while (item < NITEM) {
                const int next = (int)atomicAdd(&g_work, 1u) + G;
                produce(item);
                item = next;
            }
            s_item[NST] = u;
            if (cta < ND) {
                mbar_expect_tx(bar_wo, WO_ROWS * P80);
#pragma unroll 1
                for (int j = 0; j < WO_ROWS / BOX; ++j, ++u) {
                    const int st = u % NST;
                    mbar_wait(bar_empty + st * 8, (u / NST) & 1);
                    tma2d(sbase + SM_RING + st * STAGE_BYTES, &tm_o, ns * 80, ks * WO_ROWS + j * BOX, bar_wo);
                }
            }
            PROFP(13);
        }
        return;
    }

    const int lane = tid & 31, warp = tid >> 5;
    float* s_part = (float*)(smem + SM_PART);
    float* s_xp = (float*)(smem + SM_XP);
    float* s_red = (float*)(smem + SM_RED);
    uint32_t* h_dst = (uint32_t*)(smem + SM_A + lrow * A_PITCH + lcol * 2);

    const unsigned int ep = ep0 + 1u;
    const unsigned int target = ep * gridDim.x, tag16 = ep & 0xffffu;
    const unsigned long long* mod_row = g_mod + (lrow * MODN + lcol) / 2;
    float nv[10];
    {
        const int i1 = tid + NCONS;
#pragma unroll 1
        for (int r = 0; r < 2; ++r) {
            const int i = r ? i1 : tid;
            if (i < 320) {
                const uint4 cc = r ? c1 : c0;
                const uint32_t cw[4] = {cc.x, cc.y, cc.z, cc.w};
                uint32_t ow[4];
#pragma unroll
                for (int k = 0; k < 4; ++k) {
                    const float a = bf_lo(cw[k]), b = bf_hi(cw[k]);
                    __nv_bfloat162 p = __floats2bfloat162_rn(__fdiv_rn(a, 1.0f + __expf(-a)), __fdiv_rn(b, 1.0f + __expf(-b)));
                    ow[k] = *(uint32_t*)&p;
                }
                const int b = i / 80, c8 = i - b * 80;
                *(uint4*)(smem + SM_A + b * A_PITCH + c8 * 16) = make_uint4(ow[0], ow[1], ow[2], ow[3]);
            }
        }
#pragma unroll
        for (int i = 0; i < 5; ++i) {
            nv[2 * i] = bf_lo(xw[i]);
            nv[2 * i + 1] = bf_hi(xw[i]);
            *(float2*)(s_xp + lrow * DM + lcol + 2 * i) = make_float2(nv[2 * i], nv[2 * i + 1]);
        }
        PROF(17);
        if (tid == 0 && cta < QN / 48) {
            mbar_expect_tx(bar_wq, DM * P48);
            tma_block(sbase + SM_WQ, &tm_q, cta * 48, 0, DM, P48, bar_wq);
        }
    }
    float* acc_o = g_o[ep & 1];
    float* acc_attn = g_attn[ep & 1];
    if (cta == gridDim.x - 1) {
#pragma unroll 1
        for (int i = tid; i < NB * QN / 4; i += NCONS) ((float4*)g_o[~ep & 1])[i] = make_float4(0.f, 0.f, 0.f, 0.f);
#pragma unroll 1
        for (int i = tid; i < NB * DM; i += NCONS) g_attn[~ep & 1][i] = 0.f;
    }
    ln_norm(nv, s_red, tid);
    cons_sync();
    PROF(14);
    if (cta < MODN / 32) {
        mbar_wait(bar_wm, 0);
        PROF(15);
        gemv_mma<5, 2>(sbase + SM_W32 + warp * 80 * P32, P32, sbase + SM_A + warp * 160, A_PITCH, s_part + warp * 320, lane);
        cons_sync();
        if (tid < 64) {
            const int b = tid >> 4, n = (tid & 15) * 2;
            ll_store(g_mod + (b * MODN + cta * 32 + n) / 2, tall_sum(s_part, b, n), tall_sum(s_part, b, n + 1), ep);
        }
    }
    PROF(1);

    if (cta < QN / 48) {
        cons_sync();
        mbar_wait(bar_wq, 0);
        PROF(16);
        uint32_t fq[5][3][4];
        frag_load<5, 3>(fq, sbase + SM_WQ + warp * 80 * P48, P48, lane);
        {
            long long t0 = 0;
            for (;;) {
                bool ok = true;
#pragma unroll
                for (int r = 0; r < 5; ++r) {
                    const int i = tid + r * NCONS, b = i / 320, c4 = i - b * 320;
                    const uint4 v = ll_ld2(g_mod + b * (MODN / 2) + 2 * c4);
                    *(uint2*)(s_part + b * DM + 2 * c4) = make_uint2(v.x, v.z);
                    ok = ok && v.y == ep && v.w == ep;
                }
                if (ok) break;
                if (t0 == 0) t0 = clock64();
                else if (clock64() - t0 > WAIT_LIMIT_CYCLES) __trap();
            }
        }
        cons_sync();
        PROF(2);
        uint32_t sh[5], sc[5];
#pragma unroll
        for (int i = 0; i < 5; ++i) {
            sh[i] = ((const uint32_t*)s_part)[lrow * DM + lcol / 2 + i];
            sc[i] = ((const uint32_t*)s_part)[lrow * DM + DM / 2 + lcol / 2 + i];
        }
        modulate(nv, sh, sc, h_dst);
        cons_sync();
        frag_mma<5, 3>(fq, sbase + SM_A + warp * 160, A_PITCH, s_part + warp * 320, lane);
        cons_sync();
        if (tid < 96) {
            const int b = tid / 24, n = (tid - b * 24) * 2;
            ll_store(g_q + (b * QN + cta * 48 + n) / 2, tall_sum(s_part, b, n), tall_sum(s_part, b, n + 1), ep);
        }
    }
    PROF(3);
    if (tid == 0) {
#pragma unroll 1
        for (int s = PRE; s < NST; ++s) mbar_arrive(bar_empty + s * 8);
    }
    uint32_t m_ga[5], m_sb[5], m_cb[5], m_fa[1] = {0u}, m_fb[1] = {0u};
    const int fcta = cta - ((int)gridDim.x - DM / 32);
    PROF(4);

    {
        const int sub = lane & 7, grp = lane >> 3;
        for (int u0 = warp * TPI;; u0 += 8 * TPI) {
            int item = -1;
            if (s_tag[u0 % NST] == u0 || tag_wait_stop(s_tag + u0 % NST, u0, s_item + NST)) item = s_item[u0 % NST];
            if ((u0 >= 8 * TPI && u0 < 16 * TPI) || (item < 0 && u0 < 8 * TPI)) {
                if (cta < FF / 16) {
                    ll_get(mod_row + DM, m_ga, ep);
                    ll_get(mod_row + 3 * DM / 2, m_sb, ep);
                    ll_get(mod_row + 2 * DM, m_cb, ep);
                }
                if (tid < 64 && fcta >= 0) {
                    ll_get(g_mod + ((tid >> 4) * MODN + 2 * DM + fcta * 32) / 2 + (tid & 15), m_fa, ep);
                    ll_get(g_mod + ((tid >> 4) * MODN + 5 * DM + fcta * 32) / 2 + (tid & 15), m_fb, ep);
                }
            }
            if (item < 0) break;
            const int bh = (item & (NITEM_K - 1)) / CHUNKS;
            if (item < NITEM_K) {
                unsigned int* gs = g_s + (size_t)item * ITEM_KEYS;
                float qr[24];
                {
                    const unsigned long long* qp = g_q + ((bh >> 5) * QN + (bh & 31) * DH) / 2 + sub * 4;
                    long long t0 = 0;
                    for (;;) {
                        bool ok = true;
#pragma unroll
                        for (int j = 0; j < 6; ++j) {
                            const uint4 v = ll_ld2(qp + (j >> 1) * 32 + (j & 1) * 2);
                            qr[j * 4 + 0] = bf_lo(v.x); qr[j * 4 + 1] = bf_hi(v.x);
                            qr[j * 4 + 2] = bf_lo(v.z); qr[j * 4 + 3] = bf_hi(v.z);
                            ok = ok && v.y == ep && v.w == ep;
                        }
                        if (ok) break;
                        if (t0 == 0) t0 = clock64();
                        else if (clock64() - t0 > WAIT_LIMIT_CYCLES) __trap();
                    }
                }
                float m_run = -INFINITY, l_run = 0.f;
#pragma unroll 1
                for (int hh = 0; hh < 2 * TPI; ++hh) {
                    const int u = u0 + (hh >> 1), st = u % NST;
                    if (!(hh & 1)) stage_wait(bar_full, s_tag, u);
                    const uint4* tile = (const uint4*)(smem + SM_RING + st * STAGE_BYTES) + (hh & 1) * (32 * 24);
                    float part[8];
#pragma unroll
                    for (int it = 0; it < 8; ++it) {
                        const uint4* row = tile + (it * 4 + grp) * 24 + sub;
                        const uint4 a = row[0], b = row[8], c = row[16];
                        part[it] = dot8(a, qr) + dot8(b, qr + 8) + dot8(c, qr + 16);
                    }
                    if (hh & 1) {
                        __syncwarp();
                        if (lane == 0) mbar_arrive(bar_empty + st * 8);
                    }
#pragma unroll
                    for (int j = 0; j < 4; ++j) {
                        const float send = (sub & 4) ? part[j] : part[j + 4];
                        const float keep = (sub & 4) ? part[j + 4] : part[j];
                        part[j] = keep + __shfl_xor_sync(0xffffffffu, send, 4);
                    }
#pragma unroll
                    for (int j = 0; j < 2; ++j) {
                        const float send = (sub & 2) ? part[j] : part[j + 2];
                        const float keep = (sub & 2) ? part[j + 2] : part[j];
                        part[j] = keep + __shfl_xor_sync(0xffffffffu, send, 2);
                    }
                    {
                        const float send = (sub & 1) ? part[0] : part[1];
                        const float keep = (sub & 1) ? part[1] : part[0];
                        part[0] = keep + __shfl_xor_sync(0xffffffffu, send, 1);
                    }
                    const float s = bf16r(bf16r(part[0]) * 0.07216878364870323f);
                    asm volatile("st.relaxed.gpu.global.u32 [%0], %1;" ::"l"(gs + hh * 32 + sub * 4 + grp), "r"(__float_as_uint(s) | tag16) : "memory");
                    const float m_new = fmaxf(m_run, s);
                    l_run = l_run * __expf(m_run - m_new) + __expf(s - m_new);
                    m_run = m_new;
                }
                const float m = warp_max(m_run);
                const float l = warp_sum(l_run * __expf(m_run - m));
                if (lane == 0)
                    asm volatile("st.relaxed.gpu.global.u64 [%0], %1;" ::"l"(g_stat + item),
                                 "l"(((unsigned long long)__float_as_uint(l) << 32) | (__float_as_uint(m) | tag16)) : "memory");
            } else {
                float pr[2 * TPI];
                {
                    const unsigned int* gs = g_s + (size_t)(item - NITEM_K) * ITEM_KEYS + lane;
                    uint2 st2;
                    long long t0 = 0;
                    for (;;) {
                        st2 = ll_ld1(g_stat + bh * CHUNKS + lane);
                        bool ok = (st2.x & 0xffffu) == tag16;
#pragma unroll
                        for (int hh = 0; hh < 2 * TPI; ++hh) {
                            unsigned int w;
                            asm volatile("ld.relaxed.gpu.global.u32 %0, [%1];" : "=r"(w) : "l"(gs + hh * 32) : "memory");
                            ok = ok && (w & 0xffffu) == tag16;
                            pr[hh] = bf_hi(w);
                        }
                        if (__all_sync(0xffffffffu, ok)) break;
                        if (t0 == 0) t0 = clock64();
                        else if (clock64() - t0 > WAIT_LIMIT_CYCLES) __trap();
                    }
                    const float mi = bf_hi(st2.x);
                    const float mm = warp_max(mi);
                    const float ll = warp_sum(__uint_as_float(st2.y) * __expf(mi - mm));
#pragma unroll
                    for (int hh = 0; hh < 2 * TPI; ++hh) pr[hh] = bf16r(__fdiv_rn(__expf(pr[hh] - mm), ll));
                }
                float acc[3][8];
#pragma unroll
                for (int j = 0; j < 3; ++j)
#pragma unroll
                    for (int e = 0; e < 8; ++e) acc[j][e] = 0.f;
#pragma unroll
                for (int hh = 0; hh < 2 * TPI; ++hh) {
                    const int u = u0 + (hh >> 1), st = u % NST;
                    if (!(hh & 1)) stage_wait(bar_full, s_tag, u);
                    const uint4* tile = (const uint4*)(smem + SM_RING + st * STAGE_BYTES) + (hh & 1) * (32 * 24);
#pragma unroll
                    for (int it = 0; it < 8; ++it) {
                        const uint4* row = tile + (it * 4 + grp) * 24 + sub;
                        const uint4 a = row[0], b = row[8], c = row[16];
                        const float p = __shfl_sync(0xffffffffu, pr[hh], it * 4 + grp);
                        fma8(acc[0], a, p);
                        fma8(acc[1], b, p);
                        fma8(acc[2], c, p);
                    }
                    if (hh & 1) {
                        __syncwarp();
                        if (lane == 0) mbar_arrive(bar_empty + st * 8);
                    }
                }
                float* go = acc_o + (bh >> 5) * QN + (bh & 31) * DH + sub * 8;
#pragma unroll
                for (int j = 0; j < 3; ++j) {
#pragma unroll
                    for (int e = 0; e < 8; ++e) {
                        float v = acc[j][e];
                        v += __shfl_xor_sync(0xffffffffu, v, 8);
                        v += __shfl_xor_sync(0xffffffffu, v, 16);
                        acc[j][e] = v;
                    }
                    if (grp == 0) {
                        red_add_v4(go + j * 64, acc[j][0], acc[j][1], acc[j][2], acc[j][3]);
                        red_add_v4(go + j * 64 + 4, acc[j][4], acc[j][5], acc[j][6], acc[j][7]);
                    }
                }
            }
        }
    }
    PROF(5);
    grid_arrive(&g_bar[2], tid);
    PROF(6);
    if (fcta >= 0 && tid == 0) {
        mbar_expect_tx(bar_wd, FF * P32);
        tma_block(sbase + SM_WD, &tm_down, fcta * 32, 0, FF, P32, bar_wd);
    }
    if (cta < ND) {
        const int u_end = s_item[NST];
        if (cta < FF / 16 && tid == 0) {
            mbar_expect_tx(bar_gu, 2 * DM * 32);
            tma_block(sbase + SM_W32, &tm_gate, cta * 16, 0, DM, 32, bar_gu);
            tma_block(sbase + SM_W32 + DM * 32, &tm_up, cta * 16, 0, DM, 32, bar_gu);
        }
        uint32_t fd[4][5][4];
        mbar_wait(bar_wo, 0);
        frag_load<4, 5>(fd, sbase + SM_RING + ((u_end + (warp >> 1)) % NST) * STAGE_BYTES + (warp & 1) * 64 * P80, P80, lane);
        grid_wait(&g_bar[2], target, tid);
        if (cta == 0 && tid == 0) { g_work = 0u; g_epoch = ep; }
        PROF(7);
        {
            float4 v[2];
#pragma unroll
            for (int r = 0; r < 2; ++r) v[r] = __ldcg((const float4*)(acc_o + (2 * r + (tid >> 7)) * QN + ks * WO_ROWS) + (tid & 127));
#pragma unroll
            for (int r = 0; r < 2; ++r) {
                __nv_bfloat162 p0 = __floats2bfloat162_rn(v[r].x, v[r].y), p1 = __floats2bfloat162_rn(v[r].z, v[r].w);
                *(uint2*)(smem + SM_A + (2 * r + (tid >> 7)) * A_PITCH + (tid & 127) * 8) = make_uint2(*(uint32_t*)&p0, *(uint32_t*)&p1);
            }
        }
        cons_sync();
        frag_mma<4, 5>(fd, sbase + SM_A + warp * 128, A_PITCH, s_part + warp * 320, lane);
        cons_sync();
        if (tid < 80) {
            const int b = tid / 20, n4 = tid - b * 20;
            float4 s4 = make_float4(0.f, 0.f, 0.f, 0.f);
#pragma unroll
            for (int w = 0; w < 8; ++w) {
                const float4 v = *(const float4*)(s_part + (w * 4 + b) * 80 + n4 * 4);
                s4.x += v.x; s4.y += v.y; s4.z += v.z; s4.w += v.w;
            }
            red_add_v4(acc_attn + b * DM + ns * 80 + n4 * 4, s4.x, s4.y, s4.z, s4.w);
        }
        PROF(8);
        grid_arrive(&g_bar[3], tid);
    }
    const bool has_e = cta < FF / 16;
    if (!has_e && fcta < 0) return;
    if (has_e) {
        uint32_t fe[5][2][4];
        mbar_wait(bar_gu, 0);
        frag_load<5, 2>(fe, sbase + SM_W32 + warp * 80 * 32, 32, lane, DM * 32);
        grid_wait(&g_bar[3], ep * ND, tid);
        PROF(9);
        {
            float4 v[3];
#pragma unroll
            for (int r = 0; r < 3; ++r)
                if (tid + r * NCONS < NB * DM / 4) v[r] = __ldcg((const float4*)acc_attn + tid + r * NCONS);
#pragma unroll
            for (int r = 0; r < 3; ++r)
                if (tid + r * NCONS < NB * DM / 4) ((float4*)s_part)[tid + r * NCONS] = v[r];
        }
        cons_sync();
#pragma unroll
        for (int i = 0; i < 5; ++i) {
            const float2 av = *((const float2*)(s_part + lrow * DM + lcol) + i);
            const float2 xv = *((const float2*)(s_xp + lrow * DM + lcol) + i);
            nv[2 * i] = bf16r(xv.x + bf16r(bf_lo(m_ga[i]) * bf16r(av.x)));
            nv[2 * i + 1] = bf16r(xv.y + bf16r(bf_hi(m_ga[i]) * bf16r(av.y)));
        }
        ln_norm(nv, s_red, tid);
        modulate(nv, m_sb, m_cb, h_dst);
        cons_sync();
        frag_mma<5, 2>(fe, sbase + SM_A + warp * 160, A_PITCH, s_part + warp * 320, lane);
        cons_sync();
        if (tid < 32) {
            const int b = tid >> 3, n = (tid & 7) * 2;
            const float g0 = bf16r(tall_sum(s_part, b, n)), g1 = bf16r(tall_sum(s_part, b, n + 1));
            const float u0 = bf16r(tall_sum(s_part, b, 16 + n)), u1 = bf16r(tall_sum(s_part, b, 17 + n));
            ll_store(g_act + (b * FF + cta * 16 + n) / 2, bf16r(gelu_tanh(g0)) * u0, bf16r(gelu_tanh(g1)) * u1, ep);
        }
        PROF(10);
        if (fcta < 0) return;
    } else {
        grid_wait(&g_bar[3], ep * ND, tid);
    }
    {
        float x10 = 0.f, x11 = 0.f;
        if (tid < 64) {
            const int b = tid >> 4, col = fcta * 32 + (tid & 15) * 2;
            const float2 av = __ldcg((const float2*)(acc_attn + b * DM + col));
            x10 = bf16r(s_xp[b * DM + col] + bf16r(bf_lo(m_fa[0]) * bf16r(av.x)));
            x11 = bf16r(s_xp[b * DM + col + 1] + bf16r(bf_hi(m_fa[0]) * bf16r(av.y)));
        }
        mbar_wait(bar_wd, 0);
        uint32_t ff[12][2][4];
        frag_load<12, 2>(ff, sbase + SM_WD + warp * 192 * P32, P32, lane);
        long long t0 = 0;
        for (uint32_t pend = 0x3fu;;) {
            uint4 v[6];
#pragma unroll
            for (int r = 0; r < 6; ++r) {
                const int i = lane + r * 32, b = i / 48;
                v[r] = make_uint4(0u, ~ep, 0u, ~ep);
                if (pend >> r & 1u) v[r] = ll_ld2(g_act + b * (FF / 2) + 2 * (warp * 48 + i - b * 48));
            }
#pragma unroll
            for (int r = 0; r < 6; ++r) {
                const int i = lane + r * 32, b = i / 48;
                if (v[r].y == ep && v[r].w == ep) {
                    *(uint2*)(smem + SM_ACT + b * ACT_PITCH + (warp * 48 + i - b * 48) * 8) = make_uint2(v[r].x, v[r].z);
                    pend &= ~(1u << r);
                }
            }
            if (!pend) break;
            if (t0 == 0) t0 = clock64();
            else if (clock64() - t0 > WAIT_LIMIT_CYCLES) __trap();
        }
        __syncwarp();
        PROF(11);
        frag_mma<12, 2>(ff, sbase + SM_ACT + warp * 384, ACT_PITCH, s_part + warp * 320, lane);
        cons_sync();
        if (tid < 64) {
            const int b = tid >> 4, n = (tid & 15) * 2;
            const float f0 = bf16r(tall_sum(s_part, b, n)), f1 = bf16r(tall_sum(s_part, b, n + 1));
            *(__nv_bfloat162*)(out + b * DM + fcta * 32 + n) =
                __floats2bfloat162_rn(x10 + bf16r(bf_lo(m_fb[0]) * f0), x11 + bf16r(bf_hi(m_fb[0]) * f1));
        }
    }
    PROF(12);
}

}

extern "C" void kernel_launch(void* const* d_in, const int* in_sizes, int n_in, void* d_out, int out_size) {
    (void)in_sizes; (void)n_in; (void)out_size;
    const __nv_bfloat16* A_x = (const __nv_bfloat16*)d_in[0];
    const __nv_bfloat16* A_k = (const __nv_bfloat16*)d_in[1];
    const __nv_bfloat16* A_v = (const __nv_bfloat16*)d_in[2];
    const __nv_bfloat16* A_wq = (const __nv_bfloat16*)d_in[3];
    const __nv_bfloat16* A_wo = (const __nv_bfloat16*)d_in[4];
    const __nv_bfloat16* B_wg = (const __nv_bfloat16*)d_in[6];
    const __nv_bfloat16* B_wu = (const __nv_bfloat16*)d_in[7];
    const __nv_bfloat16* B_wd = (const __nv_bfloat16*)d_in[8];
    const __nv_bfloat16* c = (const __nv_bfloat16*)d_in[9];
    const __nv_bfloat16* w_mod = (const __nv_bfloat16*)d_in[10];
    typedef CUresult (*encode_fn)(CUtensorMap*, CUtensorMapDataType, cuuint32_t, void*, const cuuint64_t*, const cuuint64_t*,
                                  const cuuint32_t*, const cuuint32_t*, CUtensorMapInterleave, CUtensorMapSwizzle,
                                  CUtensorMapL2promotion, CUtensorMapFloatOOBfill);
    static int grid = 0;
    static encode_fn encode = nullptr;
    if (grid == 0) {
        cudaFuncSetAttribute(decode_block_kernel, cudaFuncAttributeMaxDynamicSharedMemorySize, SM_TOTAL);
        int dev = 0, sms = 0;
        cudaGetDevice(&dev);
        cudaDeviceGetAttribute(&sms, cudaDevAttrMultiProcessorCount, dev);
        grid = sms < 132 ? sms : 132;
        void* fn = nullptr;
        cudaDriverEntryPointQueryResult qres;
        cudaGetDriverEntryPoint("cuTensorMapEncodeTiled", &fn, cudaEnableDefault, &qres);
        encode = (encode_fn)fn;
    }
    auto make_map = [&](const __nv_bfloat16* w, int rows, int cols, int box_bytes) {
        CUtensorMap m;
        const cuuint64_t dims[2] = {(cuuint64_t)cols, (cuuint64_t)rows};
        const cuuint64_t strides[1] = {(cuuint64_t)cols * 2};
        const cuuint32_t box[2] = {(cuuint32_t)(box_bytes / 2), (cuuint32_t)BOX};
        const cuuint32_t estr[2] = {1, 1};
        encode(&m, CU_TENSOR_MAP_DATA_TYPE_BFLOAT16, 2, (void*)w, dims, strides, box, estr, CU_TENSOR_MAP_INTERLEAVE_NONE,
               CU_TENSOR_MAP_SWIZZLE_NONE, CU_TENSOR_MAP_L2_PROMOTION_L2_128B, CU_TENSOR_MAP_FLOAT_OOB_FILL_NONE);
        return m;
    };
    decode_block_kernel<<<grid, NTHREADS, SM_TOTAL>>>(A_x, A_k, A_v, c, (__nv_bfloat16*)d_out, make_map(w_mod, DM, MODN, P32),
                                                      make_map(A_wq, DM, QN, P48), make_map(A_wo, QN, DM, P80),
                                                      make_map(B_wg, DM, FF, 32), make_map(B_wu, DM, FF, 32),
                                                      make_map(B_wd, FF, DM, P32));
}
```
